```python
import torch

def _softmax(x, axis=-1):
    return torch.softmax(x, dim=axis)
def _gelu(x):
    return torch.nn.functional.gelu(x, approximate="tanh")
def _silu(x):
    return torch.nn.functional.silu(x)
def _sigmoid(x):
    return torch.sigmoid(x)
def _layernorm(x, axis=-1, eps=1e-5):
    m = x.mean(dim=axis, keepdim=True)
    v = x.var(dim=axis, keepdim=True, unbiased=False)
    return (x - m) / torch.sqrt(v + eps)
def _scatter_add(tgt, idx, src, axis=0):
    return tgt.clone().index_add_(axis, idx, src)
def _segment_sum(src, seg, n):
    out = torch.zeros((n,) + src.shape[1:], dtype=src.dtype)
    return out.index_add_(0, seg, src)
def _pad(x, pw):
    flat = tuple(v for pair in reversed(pw) for v in pair)
    return torch.nn.functional.pad(x, flat)

kernel_name = 'recurrent_scan__sliding_local_dilated__mixer_token_mlp__prompt'

def setup_inputs():

    _w = (lambda a: (lambda t: t.to(torch.bfloat16) if t.is_floating_point() else t)(torch.as_tensor(a)))
    def _A_setup():
        B, S, D = 1, 2048, 448
        return {
            "x": _w((lambda *s: torch.randn(*s, dtype=torch.bfloat16) * 0.05)(B, S, D)),
            "wqkv": _w((lambda *s: torch.randn(*s, dtype=torch.bfloat16) * 0.2)(D, 3 * D)),
            "wo": _w((lambda *s: torch.randn(*s, dtype=torch.bfloat16) * 0.2)(D, D)),
        }
    _A_in = _A_setup()

    def _B_setup():
        B, S, D, F = 1, 2048, 448, 1792
        return {
            "x": _w((lambda *s: torch.randn(*s, dtype=torch.bfloat16) * 0.05)(B, S, D)),
            "w1": _w((lambda *s: torch.randn(*s, dtype=torch.bfloat16) * 0.8)(S, F) * (S ** -0.5)),
            "b1": _w((lambda *s: torch.randn(*s, dtype=torch.bfloat16) * 0.8)(F) * 0.02),
            "w2": _w((lambda *s: torch.randn(*s, dtype=torch.bfloat16) * 0.1)(F, S) * (F ** -0.5)),
            "b2": _w((lambda *s: torch.randn(*s, dtype=torch.bfloat16) * 0.1)(S) * 0.02),
        }
    _B_in = _B_setup()

    return {
        "A_x": _A_in["x"],
        "A_wqkv": _A_in["wqkv"],
        "A_wo": _A_in["wo"],
        "B_x": _B_in["x"],
        "B_w1": _B_in["w1"],
        "B_b1": _B_in["b1"],
        "B_w2": _B_in["w2"],
        "B_b2": _B_in["b2"],
    }

def reference(A_x, A_wqkv, A_wo, B_x, B_w1, B_b1, B_w2, B_b2):
    def _A_ref(x, wqkv, wo):
        B, S, D = x.shape
        H = 16; Dh = D // H
        W, dil = 8, 2
        qkv = (lambda x, *d: x.permute(*d))((x @ wqkv).reshape(B, S, 3, H, Dh), 2, 0, 3, 1, 4)
        q, k, v = qkv[0], qkv[1], qkv[2]
        scale = Dh ** -0.5
        pos = torch.arange(S)
        off = torch.arange(W) * dil
        idx = pos[:, None] - off[None, :]
        mask = idx >= 0
        idx_c = torch.where(mask, idx, 0).reshape(-1)
        kg = k[:, :, idx_c, :].reshape(B, H, S, W, Dh)
        vg = v[:, :, idx_c, :].reshape(B, H, S, W, Dh)
        logits = torch.einsum("bhsd,bhswd->bhsw", q, kg) * scale
        logits = torch.where(mask[None, None, :, :], logits, -1e9)
        attn = _softmax(logits, axis=-1)
        o = torch.einsum("bhsw,bhswd->bhsd", attn, vg)
        return (lambda x, *d: x.permute(*d))(o, 0, 2, 1, 3).reshape(B, S, D) @ wo

    def _B_ref(x, w1, b1, w2, b2):
        B, S, D = x.shape
        h = _layernorm(x, axis=-1)
        u = torch.einsum("bsd,sf->bdf", h, w1) + b1
        u = _gelu(u)
        y = torch.einsum("bdf,fs->bds", u, w2) + b2
        return (lambda x, *d: x.permute(*d))(y, 0, 2, 1)

    x = A_x
    xn = _layernorm(x, axis=-1)
    s = _A_ref(xn, A_wqkv, A_wo)
    g = _silu(_B_ref(xn, B_w1, B_b1, B_w2, B_b2))
    return x + s * g
```

```cpp
#include <cuda_runtime.h>
#include <cuda.h>
#include <cuda_bf16.h>
#include <stdint.h>

template<int TA, int TB> __device__ __forceinline__ void wgmma_n112(float (&d)[56], uint64_t da, uint64_t db, int sc) {
  asm volatile("{\n.reg .pred p;\nsetp.ne.b32 p, %58, 0;\n"
    "wgmma.mma_async.sync.aligned.m64n112k16.f32.bf16.bf16 {%0, %1, %2, %3, %4, %5, %6, %7, %8, %9, %10, %11, %12, %13, %14, %15, %16, %17, %18, %19, %20, %21, %22, %23, %24, %25, %26, %27, %28, %29, %30, %31, %32, %33, %34, %35, %36, %37, %38, %39, %40, %41, %42, %43, %44, %45, %46, %47, %48, %49, %50, %51, %52, %53, %54, %55}, %56, %57, p, 1, 1, %59, %60;\n}\n"
    : "+f"(d[0]), "+f"(d[1]), "+f"(d[2]), "+f"(d[3]), "+f"(d[4]), "+f"(d[5]), "+f"(d[6]), "+f"(d[7]), "+f"(d[8]), "+f"(d[9]), "+f"(d[10]), "+f"(d[11]), "+f"(d[12]), "+f"(d[13]), "+f"(d[14]), "+f"(d[15]), "+f"(d[16]), "+f"(d[17]), "+f"(d[18]), "+f"(d[19]), "+f"(d[20]), "+f"(d[21]), "+f"(d[22]), "+f"(d[23]), "+f"(d[24]), "+f"(d[25]), "+f"(d[26]), "+f"(d[27]), "+f"(d[28]), "+f"(d[29]), "+f"(d[30]), "+f"(d[31]), "+f"(d[32]), "+f"(d[33]), "+f"(d[34]), "+f"(d[35]), "+f"(d[36]), "+f"(d[37]), "+f"(d[38]), "+f"(d[39]), "+f"(d[40]), "+f"(d[41]), "+f"(d[42]), "+f"(d[43]), "+f"(d[44]), "+f"(d[45]), "+f"(d[46]), "+f"(d[47]), "+f"(d[48]), "+f"(d[49]), "+f"(d[50]), "+f"(d[51]), "+f"(d[52]), "+f"(d[53]), "+f"(d[54]), "+f"(d[55])
    : "l"(da), "l"(db), "r"(sc), "n"(TA), "n"(TB));
}

template<int TA, int TB> __device__ __forceinline__ void wgmma_n80(float (&d)[40], uint64_t da, uint64_t db, int sc) {
  asm volatile("{\n.reg .pred p;\nsetp.ne.b32 p, %42, 0;\n"
    "wgmma.mma_async.sync.aligned.m64n80k16.f32.bf16.bf16 {%0, %1, %2, %3, %4, %5, %6, %7, %8, %9, %10, %11, %12, %13, %14, %15, %16, %17, %18, %19, %20, %21, %22, %23, %24, %25, %26, %27, %28, %29, %30, %31, %32, %33, %34, %35, %36, %37, %38, %39}, %40, %41, p, 1, 1, %43, %44;\n}\n"
    : "+f"(d[0]), "+f"(d[1]), "+f"(d[2]), "+f"(d[3]), "+f"(d[4]), "+f"(d[5]), "+f"(d[6]), "+f"(d[7]), "+f"(d[8]), "+f"(d[9]), "+f"(d[10]), "+f"(d[11]), "+f"(d[12]), "+f"(d[13]), "+f"(d[14]), "+f"(d[15]), "+f"(d[16]), "+f"(d[17]), "+f"(d[18]), "+f"(d[19]), "+f"(d[20]), "+f"(d[21]), "+f"(d[22]), "+f"(d[23]), "+f"(d[24]), "+f"(d[25]), "+f"(d[26]), "+f"(d[27]), "+f"(d[28]), "+f"(d[29]), "+f"(d[30]), "+f"(d[31]), "+f"(d[32]), "+f"(d[33]), "+f"(d[34]), "+f"(d[35]), "+f"(d[36]), "+f"(d[37]), "+f"(d[38]), "+f"(d[39])
    : "l"(da), "l"(db), "r"(sc), "n"(TA), "n"(TB));
}

template<int TB> __device__ __forceinline__ void wgmma_rs_n120(float (&d)[60], const uint32_t (&a)[4], uint64_t db, int sc) {
  asm volatile("{\n.reg .pred p;\nsetp.ne.b32 p, %65, 0;\n"
    "wgmma.mma_async.sync.aligned.m64n120k16.f32.bf16.bf16 {%0, %1, %2, %3, %4, %5, %6, %7, %8, %9, %10, %11, %12, %13, %14, %15, %16, %17, %18, %19, %20, %21, %22, %23, %24, %25, %26, %27, %28, %29, %30, %31, %32, %33, %34, %35, %36, %37, %38, %39, %40, %41, %42, %43, %44, %45, %46, %47, %48, %49, %50, %51, %52, %53, %54, %55, %56, %57, %58, %59}, {%60, %61, %62, %63}, %64, p, 1, 1, %66;\n}\n"
    : "+f"(d[0]), "+f"(d[1]), "+f"(d[2]), "+f"(d[3]), "+f"(d[4]), "+f"(d[5]), "+f"(d[6]), "+f"(d[7]), "+f"(d[8]), "+f"(d[9]), "+f"(d[10]), "+f"(d[11]), "+f"(d[12]), "+f"(d[13]), "+f"(d[14]), "+f"(d[15]), "+f"(d[16]), "+f"(d[17]), "+f"(d[18]), "+f"(d[19]), "+f"(d[20]), "+f"(d[21]), "+f"(d[22]), "+f"(d[23]), "+f"(d[24]), "+f"(d[25]), "+f"(d[26]), "+f"(d[27]), "+f"(d[28]), "+f"(d[29]), "+f"(d[30]), "+f"(d[31]), "+f"(d[32]), "+f"(d[33]), "+f"(d[34]), "+f"(d[35]), "+f"(d[36]), "+f"(d[37]), "+f"(d[38]), "+f"(d[39]), "+f"(d[40]), "+f"(d[41]), "+f"(d[42]), "+f"(d[43]), "+f"(d[44]), "+f"(d[45]), "+f"(d[46]), "+f"(d[47]), "+f"(d[48]), "+f"(d[49]), "+f"(d[50]), "+f"(d[51]), "+f"(d[52]), "+f"(d[53]), "+f"(d[54]), "+f"(d[55]), "+f"(d[56]), "+f"(d[57]), "+f"(d[58]), "+f"(d[59])
    : "r"(a[0]), "r"(a[1]), "r"(a[2]), "r"(a[3]), "l"(db), "r"(sc), "n"(TB));
}

template<int TB> __device__ __forceinline__ void wgmma_rs_n56(float (&d)[28], const uint32_t (&a)[4], uint64_t db, int sc) {
  asm volatile("{\n.reg .pred p;\nsetp.ne.b32 p, %33, 0;\n"
    "wgmma.mma_async.sync.aligned.m64n56k16.f32.bf16.bf16 {%0, %1, %2, %3, %4, %5, %6, %7, %8, %9, %10, %11, %12, %13, %14, %15, %16, %17, %18, %19, %20, %21, %22, %23, %24, %25, %26, %27}, {%28, %29, %30, %31}, %32, p, 1, 1, %34;\n}\n"
    : "+f"(d[0]), "+f"(d[1]), "+f"(d[2]), "+f"(d[3]), "+f"(d[4]), "+f"(d[5]), "+f"(d[6]), "+f"(d[7]), "+f"(d[8]), "+f"(d[9]), "+f"(d[10]), "+f"(d[11]), "+f"(d[12]), "+f"(d[13]), "+f"(d[14]), "+f"(d[15]), "+f"(d[16]), "+f"(d[17]), "+f"(d[18]), "+f"(d[19]), "+f"(d[20]), "+f"(d[21]), "+f"(d[22]), "+f"(d[23]), "+f"(d[24]), "+f"(d[25]), "+f"(d[26]), "+f"(d[27])
    : "r"(a[0]), "r"(a[1]), "r"(a[2]), "r"(a[3]), "l"(db), "r"(sc), "n"(TB));
}

template<int TB> __device__ __forceinline__ void wgmma_rs_n32(float (&d)[16], const uint32_t (&a)[4], uint64_t db, int sc) {
  asm volatile("{\n.reg .pred p;\nsetp.ne.b32 p, %21, 0;\n"
    "wgmma.mma_async.sync.aligned.m64n32k16.f32.bf16.bf16 {%0, %1, %2, %3, %4, %5, %6, %7, %8, %9, %10, %11, %12, %13, %14, %15}, {%16, %17, %18, %19}, %20, p, 1, 1, %22;\n}\n"
    : "+f"(d[0]), "+f"(d[1]), "+f"(d[2]), "+f"(d[3]), "+f"(d[4]), "+f"(d[5]), "+f"(d[6]), "+f"(d[7]), "+f"(d[8]), "+f"(d[9]), "+f"(d[10]), "+f"(d[11]), "+f"(d[12]), "+f"(d[13]), "+f"(d[14]), "+f"(d[15])
    : "r"(a[0]), "r"(a[1]), "r"(a[2]), "r"(a[3]), "l"(db), "r"(sc), "n"(TB));
}

namespace {
constexpr int S_ = 2048, D_ = 448, F_ = 1792;
constexpr int NSLOT = 8, SLOT = 22528;
constexpr int OFF_X = 7 * 16384;
constexpr int OFF_Q = NSLOT * SLOT;
constexpr int OFF_K = OFF_Q + 16384;
constexpr int OFF_BAR = 14 * 16384;
constexpr int OFF_LN = OFF_BAR + 384;
constexpr int OFF_OBS = OFF_BAR + 512;
constexpr int SMEM_BYTES = OFF_OBS + 1024;
#define PACE0 0
#define PACE1 600
#define PACE2 700
#define WARM 3
#define NW0 2
#define HEAT 1
#define T0 0
#define TP 250
#define J0 3
#define J1 9
#define J2 14
#define EARLY 4
#define PPE 4
#define PQE 2
#define LANDOBS 0
#define TRUNC 0
#define KOBS 0
#define PRE 1
#define QA 2
#define HEARLY 0
#define OSLEEP 0
#define OPJ 28
#define EXACT 0
#define SOBS 0
#define FREQ 0
#define OBS_T0 0
#define OBS(c, i) do {} while (0)
#define OBSG(c, i, j) do {} while (0)
constexpr int NTHREADS = 384;
constexpr float SCALE = 0.18898223650461361f, LOG2E = 1.4426950408889634f;
constexpr int BT = 14336;

constexpr int HU_T = 67;
constexpr int O_OFF = 4 * HU_T * BT;
constexpr int HALO_OFF = O_OFF + 32 * 7 * 8192;
constexpr int CNT_OFF = HALO_OFF + 128 * 3584;
constexpr int SCR_BYTES = CNT_OFF + 160 * 128;
constexpr int C_WO = 0, C_TK = 1, C_U = 2, C_O = 8, C_H = 24, C_HALO = 32;
__device__ __align__(1024) unsigned char g_scr[SCR_BYTES];

__device__ __forceinline__ uint32_t smem_u32(const void* p) { return (uint32_t)__cvta_generic_to_shared(p); }
__device__ __forceinline__ void mbar_init(uint32_t bar, uint32_t cnt) { asm volatile("mbarrier.init.shared::cta.b64 [%0], %1;" :: "r"(bar), "r"(cnt)); }
__device__ __forceinline__ void mbar_expect_tx(uint32_t bar, uint32_t bytes) { asm volatile("mbarrier.arrive.expect_tx.shared::cta.b64 _, [%0], %1;" :: "r"(bar), "r"(bytes) : "memory"); }
__device__ __forceinline__ void mbar_arrive(uint32_t bar) { asm volatile("mbarrier.arrive.shared::cta.b64 _, [%0];" :: "r"(bar) : "memory"); }
__device__ __forceinline__ void mbar_wait(uint32_t bar, uint32_t parity) {
  asm volatile("{\n.reg .pred p;\n.reg .u32 n;\nmov.u32 n, 0;\nLAB_WAIT:\n"
               "mbarrier.try_wait.parity.shared::cta.b64 p, [%0], %1;\n@p bra DONE;\n"
               "add.u32 n, n, 1;\nsetp.lt.u32 p, n, 400000;\n@p bra LAB_WAIT;\ntrap;\nDONE:\n}" :: "r"(bar), "r"(parity) : "memory");
}
__device__ __forceinline__ uint32_t mbar_try(uint32_t bar, uint32_t parity) {
  uint32_t ok;
  asm volatile("{\n.reg .pred p;\nmbarrier.test_wait.parity.shared::cta.b64 p, [%1], %2;\nselp.u32 %0, 1, 0, p;\n}" : "=r"(ok) : "r"(bar), "r"(parity) : "memory");
  return ok;
}
__device__ __forceinline__ void tma3d(uint32_t dst, const CUtensorMap* m, int c0, int c1, int c2, uint32_t bar) {
  asm volatile("cp.async.bulk.tensor.3d.shared::cluster.global.mbarrier::complete_tx::bytes [%0], [%1, {%3, %4, %5}], [%2];"
               :: "r"(dst), "l"(m), "r"(bar), "r"(c0), "r"(c1), "r"(c2) : "memory");
}
__device__ __forceinline__ void bulk_g2s(uint32_t dst, const void* src, uint32_t bytes, uint32_t bar) {
  asm volatile("cp.async.bulk.shared::cluster.global.mbarrier::complete_tx::bytes [%0], [%1], %2, [%3];" :: "r"(dst), "l"(src), "r"(bytes), "r"(bar) : "memory");
}
__device__ __forceinline__ void wg_fence() { asm volatile("wgmma.fence.sync.aligned;" ::: "memory"); }
__device__ __forceinline__ void wg_commit() { asm volatile("wgmma.commit_group.sync.aligned;" ::: "memory"); }
template <int N> __device__ __forceinline__ void wg_wait() { asm volatile("wgmma.wait_group.sync.aligned %0;" :: "n"(N) : "memory"); }
__device__ __forceinline__ void smem_fence() { asm volatile("fence.proxy.async.shared::cta;" ::: "memory"); }
__device__ __forceinline__ void stg128(void* p, uint32_t a, uint32_t b, uint32_t c, uint32_t d) { asm volatile("st.global.v4.u32 [%0], {%1,%2,%3,%4};" :: "l"(p), "r"(a), "r"(b), "r"(c), "r"(d) : "memory"); }
__device__ __forceinline__ void stg32_if(uint32_t c, void* p, uint32_t v) { asm volatile("{\n.reg .pred q;\nsetp.ne.u32 q, %2, 0;\n@q st.global.u32 [%0], %1;\n}" :: "l"(p), "r"(v), "r"(c) : "memory"); }
__device__ __forceinline__ void stg128_if(uint32_t e, void* p, uint32_t a, uint32_t b, uint32_t c, uint32_t d) {
  asm volatile("{\n.reg .pred q;\nsetp.ne.u32 q, %5, 0;\n@q st.global.v4.u32 [%0], {%1,%2,%3,%4};\n}" :: "l"(p), "r"(a), "r"(b), "r"(c), "r"(d), "r"(e) : "memory");
}
__device__ __forceinline__ uint4 ldg128(const void* p) { uint4 v; asm volatile("ld.global.nc.L1::no_allocate.v4.u32 {%0,%1,%2,%3}, [%4];" : "=r"(v.x), "=r"(v.y), "=r"(v.z), "=r"(v.w) : "l"(p)); return v; }
__device__ __forceinline__ void publish(unsigned char* scr, int i) {
  asm volatile("{\n.reg .pred q;\nelect.sync _|q, 0xffffffff;\n@q red.relaxed.gpu.global.inc.u32 [%0], 0xffffffff;\n}" :: "l"(scr + CNT_OFF + i * 128) : "memory");
}
__device__ __forceinline__ void spin_ge(unsigned char* scr, int i, unsigned target) {
  asm volatile("{\n.reg .pred p;\n.reg .u32 n, v;\nmov.u32 n, 0;\nLAB_SPIN:\n"
               "ld.acquire.gpu.global.u32 v, [%0];\nsetp.ge.u32 p, v, %1;\nvote.sync.all.pred p, p, 0xffffffff;\n@p bra DONE;\n"
               "add.u32 n, n, 1;\nsetp.lt.u32 p, n, 4000000;\n@p bra LAB_SPIN;\ntrap;\nDONE:\n}" :: "l"(scr + CNT_OFF + i * 128), "r"(target) : "memory");
}
__device__ __forceinline__ int lane_id() { int l; asm volatile("mov.u32 %0, %%laneid;" : "=r"(l)); return l; }
__device__ __forceinline__ bool elect() {
  uint32_t r; asm volatile("{\n.reg .pred p;\nelect.sync _|p, 0xffffffff;\nselp.u32 %0, 1, 0, p;\n}" : "=r"(r)); return r != 0;
}
__device__ __forceinline__ uint4 lds128(uint32_t a) { uint4 v; asm volatile("ld.shared.v4.u32 {%0,%1,%2,%3}, [%4];" : "=r"(v.x), "=r"(v.y), "=r"(v.z), "=r"(v.w) : "r"(a) : "memory"); return v; }
__device__ __forceinline__ uint2 lds64(uint32_t a) { uint2 v; asm volatile("ld.shared.v2.u32 {%0,%1}, [%2];" : "=r"(v.x), "=r"(v.y) : "r"(a) : "memory"); return v; }
__device__ __forceinline__ void sts128(uint32_t p, uint32_t a, uint32_t b, uint32_t c, uint32_t d) { asm volatile("st.shared.v4.u32 [%0], {%1,%2,%3,%4};" :: "r"(p), "r"(a), "r"(b), "r"(c), "r"(d) : "memory"); }
__device__ __forceinline__ void sts32(uint32_t a, float v) { asm volatile("st.shared.f32 [%0], %1;" :: "r"(a), "f"(v) : "memory"); }
__device__ __forceinline__ void named_sync(int id, int n) { asm volatile("bar.sync %0, %1;" :: "r"(id), "r"(n) : "memory"); }
__device__ __forceinline__ void named_arrive(int id, int n) { asm volatile("bar.arrive %0, %1;" :: "r"(id), "r"(n) : "memory"); }
__device__ __forceinline__ void named_arrive_if(uint32_t c, int id, int n) { asm volatile("{\n.reg .pred q;\nsetp.ne.u32 q, %2, 0;\n@q bar.arrive %0, %1;\n}" :: "r"(id), "r"(n), "r"(c) : "memory"); }
__device__ __forceinline__ uint64_t mkdesc(uint32_t hi, uint32_t lo) { return ((uint64_t)hi << 32) | lo; }
constexpr uint32_t HI_SW128 = 0x40000040u;
__device__ __forceinline__ uint32_t pack2(float lo, float hi) { uint32_t r; asm("cvt.rn.bf16x2.f32 %0, %1, %2;" : "=r"(r) : "f"(hi), "f"(lo)); return r; }
__device__ __forceinline__ float bf_lo(uint32_t v) { return __uint_as_float(v << 16); }
__device__ __forceinline__ float bf_hi(uint32_t v) { return __uint_as_float(v & 0xffff0000u); }
__device__ __forceinline__ float rbf(float x) { return bf_lo(pack2(x, 0.f)); }
__device__ __forceinline__ uint32_t hsub2(uint32_t a, uint32_t b) { uint32_t r; asm("sub.rn.bf16x2 %0, %1, %2;" : "=r"(r) : "r"(a), "r"(b)); return r; }
__device__ __forceinline__ uint32_t hadd2(uint32_t a, uint32_t b) { uint32_t r; asm("add.rn.bf16x2 %0, %1, %2;" : "=r"(r) : "r"(a), "r"(b)); return r; }
__device__ __forceinline__ uint32_t hmul2(uint32_t a, uint32_t b) { uint32_t r; asm("mul.rn.bf16x2 %0, %1, %2;" : "=r"(r) : "r"(a), "r"(b)); return r; }
__device__ __forceinline__ uint32_t hfma2(uint32_t a, uint32_t b, uint32_t c) { uint32_t r; asm("fma.rn.bf16x2 %0, %1, %2, %3;" : "=r"(r) : "r"(a), "r"(b), "r"(c)); return r; }
__device__ __forceinline__ float tanh_fast(float x) { float r; asm("tanh.approx.f32 %0, %1;" : "=f"(r) : "f"(x)); return r; }
__device__ __forceinline__ float rcp_fast(float x) { float r; asm("rcp.approx.ftz.f32 %0, %1;" : "=f"(r) : "f"(x)); return r; }
__device__ __forceinline__ float ex2_fast(float x) { float r; asm("ex2.approx.ftz.f32 %0, %1;" : "=f"(r) : "f"(x)); return r; }
__device__ __forceinline__ void mma16816(float (&c)[4], uint32_t a0, uint32_t a1, uint32_t a2, uint32_t a3, uint32_t b0, uint32_t b1) {
  asm volatile("mma.sync.aligned.m16n8k16.row.col.f32.bf16.bf16.f32 {%0,%1,%2,%3}, {%4,%5,%6,%7}, {%8,%9}, {%0,%1,%2,%3};"
               : "+f"(c[0]), "+f"(c[1]), "+f"(c[2]), "+f"(c[3]) : "r"(a0), "r"(a1), "r"(a2), "r"(a3), "r"(b0), "r"(b1));
}
__device__ __forceinline__ void ldsm4(uint32_t (&r)[4], uint32_t addr) {
  asm volatile("ldmatrix.sync.aligned.m8n8.x4.shared.b16 {%0,%1,%2,%3}, [%4];" : "=r"(r[0]), "=r"(r[1]), "=r"(r[2]), "=r"(r[3]) : "r"(addr) : "memory");
}
__device__ __forceinline__ void stsm4(uint32_t addr, uint32_t a, uint32_t b, uint32_t c, uint32_t d) {
  asm volatile("stmatrix.sync.aligned.m8n8.x4.shared.b16 [%0], {%1,%2,%3,%4};" :: "r"(addr), "r"(a), "r"(b), "r"(c), "r"(d) : "memory");
}

__device__ __forceinline__ float ln_rstd(float var, float eps = 1e-5f) {
  float sd;
  asm("sqrt.approx.ftz.f32 %0, %1;" : "=f"(sd) : "f"(rbf(rbf(var) + eps)));
  return rcp_fast(rbf(sd));
}
__device__ __forceinline__ float ln_var(float mean, float sq) { return fmaxf(fmaf(-mean, mean, sq * (1.0f / D_)), 0.f); }
struct LnC { uint32_t m, rh, rl; };
__device__ __forceinline__ LnC ln_consts(float sum, float sq, float eps) {
  const float mean = sum * (1.0f / D_), r = ln_rstd(ln_var(mean, sq), eps), rh = rbf(r);
  LnC c; c.m = pack2(mean, mean); c.rh = pack2(rh, rh); c.rl = pack2(r - rh, r - rh);
  return c;
}
__device__ __forceinline__ uint32_t ln_apply(uint32_t x, const LnC& c) {
  uint32_t d = hsub2(x, c.m);
  return hfma2(d, c.rh, hmul2(d, c.rl));
}

__device__ __forceinline__ void fence_code(uint32_t key, int id) {
  asm volatile("{\n.reg .pred q;\nLAB_F:\nsetp.eq.u32 q, %0, %1;\n@q st.volatile.shared.u32 [%0], %0;\n@q bra LAB_F;\n}" :: "r"(key), "r"(4 * id + 4) : "memory");
}
template <int N> __device__ __forceinline__ void fresh(float (&a)[N]) {
#pragma unroll
  for (int i = 0; i < N; i++) asm volatile("" : "=f"(a[i]));
}
constexpr int B_EMPTY = 64, B_X = 128, B_KV = 192, B_WQ = 248, B_HALO = 256, B_RES = 264, B_ATT = 272, B_T0 = 280;

template <int TA>
__device__ __forceinline__ void gemm_stage(float (&acc)[56], uint32_t base, int it, int sc) {
  mbar_wait(base + OFF_BAR + (it & 7) * 8, (it >> 3) & 1);
  const uint32_t lo = (base >> 4) + (it & 7) * (SLOT >> 4);
  wg_fence();
#pragma unroll
  for (int k = 0; k < 4; k++)
    wgmma_n112<TA, 1>(acc, mkdesc(TA ? HI_SW128 : 8, lo + (TA ? 512u << 16 : 64u << 16) + k * 128), mkdesc(8, lo + (112u << 16) + 512 + k * 224), sc | k);
  wg_commit();
}
template <int TA>
__device__ __forceinline__ void gemm_loop(float (&acc)[56], uint32_t base, int it, int end, bool rel, unsigned obs_t0, int oi) {
#pragma unroll 1
  for (; it < end; it++) {
    gemm_stage<TA>(acc, base, it, 1);
    OBS(SOBS && rel, oi + it);
    wg_wait<1>();
    if (rel) mbar_arrive(base + OFF_BAR + B_EMPTY + ((it - 1) & 7) * 8);
  }
}
__device__ __forceinline__ void produce_box(uint32_t base, int it, int end, const CUtensorMap* mp, int c0, uint32_t tn) {
  int c1 = 0;
#pragma unroll 1
  for (; it < end; it++) {
    const uint32_t fb = base + OFF_BAR + (it & 7) * 8;
    mbar_wait(fb + B_EMPTY, (it >> 3) & 1);
    if (T0) { while ((int)(clock() - tn) < 0); tn += TP; }
    if (elect()) { mbar_expect_tx(fb, 8192); tma3d(base + (it & 7) * SLOT, mp, c0, c1, 0, fb); }
    c1 += 64;
  }
}
__device__ __forceinline__ void produce_lin(uint32_t base, int it, int end, const unsigned char* src, uint32_t bytes, uint32_t tn) {
#pragma unroll 1
  for (; it < end; it++) {
    const uint32_t fb = base + OFF_BAR + (it & 7) * 8;
    mbar_wait(fb + B_EMPTY, (it >> 3) & 1);
    if (T0) { while ((int)(clock() - tn) < 0); tn += TP; }
    if (elect()) { mbar_expect_tx(fb, bytes); bulk_g2s(base + (it & 7) * SLOT + (bytes & 2048) * 4, src, bytes, fb); }
    src += bytes;
  }
}

struct Params {
  const unsigned char *wo, *w1, *b1, *w2, *b2;
  unsigned char *out, *scr;
};

__global__ void __launch_bounds__(NTHREADS, 1)
fused_kernel(const __grid_constant__ CUtensorMap m_x, const __grid_constant__ CUtensorMap m_wkv, const __grid_constant__ CUtensorMap m_wq,
             const __grid_constant__ CUtensorMap m_w1, const __grid_constant__ CUtensorMap m_w2, const __grid_constant__ CUtensorMap m_res, const Params p) {
  extern __shared__ __align__(1024) unsigned char smem_raw[];
  const uint32_t base = smem_u32(smem_raw), bars = base + OFF_BAR;
  const int tid = threadIdx.x, lane = tid & 31, b = blockIdx.x;
  const int rb = (b >> 2) & 15, hp = ((b >> 6) << 2) | (b & 3);
  const int wcol = hp * 56 - (hp & 1) * 8;
  auto load_kv = [&](int s) { mbar_expect_tx(bars + B_KV + s * 8, 16384); tma3d(base + s * 16384, &m_wkv, wcol, s * 64, 1, bars + B_KV + s * 8); };
  if (tid < 32) {
    if (elect()) {
#pragma unroll
      for (int i = 0; i < 7; i++) mbar_init(bars + B_X + i * 8, 1);
      asm volatile("fence.mbarrier_init.release.cluster;" ::: "memory");
#pragma unroll
      for (int i = 0; i < 7; i++) { mbar_expect_tx(bars + B_X + i * 8, 16384); tma3d(base + OFF_X + i * 16384, &m_x, i * 64, rb * 128, 0, bars + B_X + i * 8); }
#pragma unroll
      for (int i = 0; i < 7; i++) mbar_init(bars + B_KV + i * 8, 1);
      asm volatile("fence.mbarrier_init.release.cluster;" ::: "memory");
#pragma unroll 1
      for (int i = 0; i < NW0; i++) load_kv(i);
    }
  }
  const int warp = __shfl_sync(0xffffffffu, tid >> 5, 0);
  if (warp == 1) {
    if (elect()) {
#pragma unroll
      for (int i = 0; i < 16; i++) mbar_init(bars + i * 8, 2);
#pragma unroll
      for (int i = 0; i < 4; i++) mbar_init(bars + B_WQ + i * 8, 1);
      asm volatile("fence.mbarrier_init.release.cluster;" ::: "memory");
      sts32(bars + B_T0, __uint_as_float(clock()));
    }
  }
  const int dt = b & 3, mt = b >> 2;
  const bool g1 = (b & 15) < 14;
  const int a1 = b - 2 * (b >> 4), ft = a1 >> 2, d1 = a1 & 3;
  const int g = lane >> 2, t = lane & 3, r8 = lane & 7, mi = lane >> 3;
  OBSG(FREQ && tid == 160, 128, 160);
  __syncthreads();
  if (warp >= 8) {
    asm volatile("setmaxnreg.dec.sync.aligned.u32 40;");
    const int pw = warp - 8;
    unsigned char* scr = p.scr;
    if (NW0 < 7 && pw == 3) {
      mbar_wait(bars + B_X, 0);
      if (elect()) {
#pragma unroll 1
        for (int i = NW0; i < 7; i++) load_kv(i);
      }
      __syncwarp();
    }
    {
      const int c0 = pw * 14 + (mi >> 1);
      unsigned char* dst = scr + (pw * HU_T + rb * 2 + (hp >> 2)) * BT + ((hp & 3) * 2 + (mi & 1)) * 1792 + (mi >> 1) * 128 + r8 * 16;
      const uint32_t xs = base + OFF_X + (hp * 16 + (lane & 15)) * 128;
      uint4 H[7];
      named_sync(9, 160);
#pragma unroll
      for (int i = 0; i < 7; i++) H[i] = lds128(xs + ((c0 + 2 * i) >> 3) * 16384 + ((((c0 + 2 * i) & 7) ^ r8) << 4));
      asm volatile("" :: "r"(H[6].w), "r"(H[0].x) : "memory");
      if (pw != 3) named_arrive(8, 384);
      else {
        named_sync(8, 384);
        if (elect()) {
          mbar_expect_tx(bars + B_WQ, 57344);
          tma3d(base + OFF_X, &m_wq, wcol, 0, 0, bars + B_WQ); tma3d(base + OFF_X + 28672, &m_wq, wcol, 224, 0, bars + B_WQ);
        }
        __syncwarp();
      }
      const uint2 st = lds64(base + OFF_LN + (lane & 15) * 8);
      const float sum = __uint_as_float(st.x), mean = sum * (1.0f / D_), var = ln_var(mean, __uint_as_float(st.y));
      const float m = rbf(mean), r = ln_rstd(var), r2 = ln_rstd(var * r * r);
      const float nc = fmaf(m, (float)D_, -sum) * (1.0f / D_) * (r * r2);
      const uint32_t m2 = pack2(m, m), r2x = pack2(r * r2, r * r2), nc2 = pack2(nc, nc);
      auto f = [&](uint32_t v) { return hfma2(hsub2(v, m2), r2x, nc2); };
#pragma unroll
      for (int i = 0; i < 7; i++) stg128(dst + i * 256, f(H[i].x), f(H[i].y), f(H[i].z), f(H[i].w));
      if (pw != 1) named_arrive(4, 128);
      else { named_sync(4, 128); publish(scr, C_H + (b & 3)); }
      OBS(tid == 288, 4);
    }
    const int it0 = g1 ? 32 : 0;
    const int lane = lane_id(), r8 = lane & 7, mi = lane >> 3;
    if (pw == 0) {
      if (elect()) {
        asm volatile("prefetch.tensormap [%0];" :: "l"(&m_w1) : "memory");
        asm volatile("prefetch.tensormap [%0];" :: "l"(&m_w2) : "memory");
        asm volatile("prefetch.tensormap [%0];" :: "l"(&m_res) : "memory");
      }
      const uint32_t tn = lds64(bars + B_T0).x + T0;
      if (g1) produce_box(base, 0, 32, &m_w1, ft * 64, tn);
      mbar_wait(bars + B_ATT, 0);
      if (elect()) { mbar_expect_tx(bars + B_RES, BT); tma3d(base + OFF_Q, &m_res, dt * 112, mt * 64, 0, bars + B_RES); }
      spin_ge(scr, C_WO, 112);
      produce_lin(base, it0, it0 + 7, scr + (dt * HU_T + 60) * BT, BT, tn - 100000);
      produce_box(base, it0 + 7, it0 + 35, &m_w2, mt * 64, tn - 100000);
    } else if (pw == 1) {
      const uint32_t tn = lds64(bars + B_T0).x + T0;
      if (g1) {
        spin_ge(scr, C_H + (lane & 3), 32);
        OBS(lane == 0, 16);
        produce_lin(base, 0, 32, scr + d1 * HU_T * BT, BT, tn);
      }
      spin_ge(scr, C_O + (mt >> 1), 8);
      OBS(lane == 0, 17);
      produce_lin(base, it0, it0 + 7, scr + O_OFF + mt * 57344, 8192, tn - 100000);
      const unsigned char* us = scr + (dt * HU_T + 32) * BT;
      asm volatile("" : "+l"(us));
      spin_ge(scr, C_U + dt, 28);
      OBS(lane == 0, 18);
      produce_lin(base, it0 + 7, it0 + 35, us, BT, tn - 100000);
      unsigned tk = 0;
      if (lane == 0) tk = atomicAdd((unsigned*)(scr + CNT_OFF + C_TK * 128), 1u);
      if (__shfl_sync(0xffffffffu, tk, 0) == 127) {
#pragma unroll 1
        for (int i = lane; i < 160; i += 32) *(unsigned*)(scr + CNT_OFF + i * 128) = 0;
      }
    } else if (pw == 2) {
      uint32_t tn = clock() + PACE0;
      const unsigned char* src = p.w1 + b * 4096 + lane * 128;
#pragma unroll 1
      for (int i = 0; i < 28 + FREQ * 2; i++) {
        while ((int)(clock() - tn) < 0) __nanosleep(20);
        if (i == 14) src = p.w2 + b * 4096 + lane * 128;
        if (i < 28) asm volatile("prefetch.global.L2 [%0];" :: "l"(src) : "memory");
        OBSG(FREQ && lane == 0, 129 + i, 161 + i);
        src += 128 * 4096;
        tn += i < 14 ? PACE1 : PACE2;
      }
    } else {
      if (b < 112) {
        const int c = (b & 1) * 28 + mi;
        const unsigned char* src = p.wo + ((b >> 1) * 8 + r8) * 896 + c * 16;
        unsigned char* dst = scr + ((b & 1) * 2 * HU_T + 60 + (b >> 4)) * BT + ((b >> 1) & 7) * 1792 + mi * 128 + r8 * 16;
        uint4 v[7];
#pragma unroll
        for (int i = 0; i < 7; i++) v[i] = ldg128(src + i * 64);
#pragma unroll
        for (int i = 0; i < 7; i++) stg128(dst + i * 512 + ((i * 4 + mi) / 14) * (HU_T * BT - 1792), v[i].x, v[i].y, v[i].z, v[i].w);
        publish(scr, C_WO);
      }
      const int lane = lane_id();
      unsigned char* hg = scr + HALO_OFF + (rb * 8 + hp) * 3584 + lane * 16;
      named_sync(1, 64);
      if (rb < 15) {
        uint4 v[7];
#pragma unroll
        for (int i = 0; i < 7; i++) v[i] = lds128(base + OFF_K + 8 * 3584 + i * 512 + lane * 16);
#pragma unroll
        for (int i = 0; i < 7; i++) stg128(hg + i * 512, v[i].x, v[i].y, v[i].z, v[i].w);
        publish(scr, C_HALO + rb * 8 + hp);
      }
      OBS(lane == 0, 29);
      if (rb > 0) {
        spin_ge(scr, C_HALO + (rb - 1) * 8 + hp, 1);
        OBS(lane == 0, 12);
        if (elect()) { mbar_expect_tx(bars + B_HALO, 3584); bulk_g2s(base + OFF_K, scr + HALO_OFF + ((rb - 1) * 8 + hp) * 3584, 3584, bars + B_HALO); }
      } else {
#pragma unroll
        for (int i = 0; i < 7; i++) sts128(base + OFF_K + i * 512 + lane * 16, 0, 0, 0, 0);
        smem_fence();
        __syncwarp();
        if (lane == 0) mbar_arrive(bars + B_HALO);
      }
    }
  } else {
    asm volatile("setmaxnreg.inc.sync.aligned.u32 232;");
    const int wg = warp >> 2, w4 = warp & 3, tl = wg ^ 1;
    const bool rel = (tid & 127) < 2;
    unsigned char* scr = p.scr;
    {
      uint32_t xa[4];
#pragma unroll
      for (int k = 0; k < 4; k++) xa[k] = base + OFF_X + (tl * 64 + w4 * 16 + (mi >> 1) * 8 + r8) * 128 + (((2 * k + (mi & 1)) ^ r8) << 4);
      uint32_t X[28][4];
      float c0[2][4] = {}, c1[2][4] = {};
      uint32_t one[8];
#pragma unroll
      for (int j = 0; j < 8; j++) asm volatile("{\n.reg .u32 y;\nmov.u32 y, %%tid.y;\nmad.lo.u32 %0, y, %1, 0x3f803f80;\n}" : "=r"(one[j]) : "r"(lane + j));
      asm volatile("" : "+l"(scr));
      uint32_t ok = 0;
      if (HEAT) {
#pragma unroll 1
        for (int n = 0; n < 64 && !ok; n++) { mma16816(c0[0], 0, 0, 0, 0, 0, 0); ok = mbar_try(bars + B_X, 0); }
      }
#pragma unroll
      for (int i = 0; i < 8; i++) {
        if (i < 7) {
          if (!ok) mbar_wait(bars + B_X + i * 8, 0);
          OBS(tid == 64 && i == 0, 0); OBS(tid == 64 && i == 6, 15);
#pragma unroll
          for (int k = 0; k < 4; k++) ldsm4(X[i * 4 + k], xa[k] + i * 16384);
          if (i < 6) ok = mbar_try(bars + B_X + i * 8 + 8, 0);
        }
        if (i > 0) {
#pragma unroll
          for (int k = i * 4 - 4; k < i * 4; k++) {
            mma16816(c0[k & 1], X[k][0], one[(k & 1) * 4], X[k][1], one[(k & 1) * 4 + 1], X[k][0], X[k][1]);
            mma16816(c1[k & 1], X[k][2], one[(k & 1) * 4 + 2], X[k][3], one[(k & 1) * 4 + 3], X[k][2], X[k][3]);
          }
        }
      }
      float st[4];
#pragma unroll
      for (int j = 0; j < 2; j++) {
        st[j] = __shfl_sync(0xffffffffu, (g & 1) ? c0[0][2 * j + 1] + c0[1][2 * j + 1] : c0[0][2 * j] + c0[1][2 * j], (lane & 28) | (g >> 1));
        st[2 + j] = __shfl_sync(0xffffffffu, (g & 1) ? c1[0][2 * j + 1] + c1[1][2 * j + 1] : c1[0][2 * j] + c1[1][2 * j], (lane & 28) | (g >> 1));
      }
      named_arrive(8, 384);
      asm volatile("{\n.reg .pred q;\nsetp.ne.u32 q, %3, 0;\n@q st.shared.v2.f32 [%0], {%1,%2};\n@q bar.arrive 9, 160;\n}"
                   :: "r"(base + OFF_LN + ((t & 1) * 8 + g) * 8), "f"((t & 1) ? st[3] : st[1]), "f"((t & 1) ? st[2] : st[0]), "r"((uint32_t)((warp ^ 4) == hp)) : "memory");
      ok = mbar_try(bars + B_KV, 0);
      LnC l0, l1;
      float eps = 1e-5f;
#pragma unroll 1
      do {
        l0 = ln_consts(st[1], st[0], eps); l1 = ln_consts(st[3], st[2], eps);
#pragma unroll
        for (int k = 0; k < PRE * 16; k++) X[k >> 2][k & 3] = hsub2(X[k >> 2][k & 3], k & 2 ? l1.m : l0.m);
        eps += eps;
      } while ((l0.rl ^ l1.rl) == 4);
      OBS(tid == 32, 1);
      float aq[28], ak[60], *av = ak + 32;
      const uint32_t dlo = (base >> 4) + (512u << 16) + (hp & 1), dlq = dlo + (OFF_X >> 4);
      const int pp_in = wg ? 6 : 0, pp_out = wg ? 0 : 6;
#pragma unroll
      for (int s = 0; s < 7; s++) {
#pragma unroll
        for (int k = s * 4; k < s * 4 + 4; k++) {
          if (s < PRE) {
            auto f = [&](uint32_t d, const LnC& l) { return hfma2(d, l.rh, hmul2(d, l.rl)); };
            const uint32_t y = f(X[k][1], l0);
            X[k][0] = f(X[k][0], l0); X[k][1] = f(X[k][2], l1); X[k][2] = y; X[k][3] = f(X[k][3], l1);
          } else {
            const uint32_t y = ln_apply(X[k][1], l0);
            X[k][0] = ln_apply(X[k][0], l0); X[k][1] = ln_apply(X[k][2], l1); X[k][2] = y; X[k][3] = ln_apply(X[k][3], l1);
          }
        }
        if (__builtin_expect(!ok, 0)) { mbar_wait(bars + B_KV + s * 8, 0); if (s == 6) mbar_wait(bars + B_WQ, 0); }
        if (s == 0) fresh(ak);
        OBS(KOBS && (tid & 127) == 0, 40 + wg * 32 + s);
        if (wg || s) named_sync(pp_in, 256);
        OBS(KOBS && (tid & 127) == 32, 48 + wg * 32 + s);
        OBS(tid == 64 && s == 0, 2);
        wg_fence();
#pragma unroll
        for (int k = 0; k < 4; k++) {
          if (s < 6 && k == PPE) named_arrive(pp_out, 256);
          wgmma_rs_n120<1>(ak, X[s * 4 + k], mkdesc(HI_SW128, dlo + s * 1024 + k * 128), (s | k) != 0);
        }
        wg_commit();
        if (s == 6) {
          fresh(aq);
#pragma unroll
          for (int k = 0; k < 4 * QA; k++) {
            if (k == 4 * QA - PQE) named_arrive(pp_out, 256);
            wgmma_rs_n56<1>(aq, X[k], mkdesc(HI_SW128, dlq + k * 128), k);
          }
          wg_commit();
        }
        if (s < 6 ? PPE == 4 : PQE == 0) named_arrive(pp_out, 256);
        fence_code(l0.rh, s);
        OBS(KOBS && (tid & 127) == 64, 56 + wg * 32 + s);
        if (s < 6) ok = mbar_try(bars + B_KV + s * 8 + 8, 0);
        if (s == 5) ok &= mbar_try(bars + B_WQ, 0);
        OBS(tid == 64 && s == 1, 28); OBS(tid == 64 && s == 5, 31);
        if (s > 0) wg_wait<1>();
        OBS(KOBS && (tid & 127) == 96, 64 + wg * 32 + s);
        if ((s == 2 || s == 3 || s == 5) && (tid & 127) == 0) mbar_arrive(bars + B_EMPTY + (s == 5 ? 2 : s - 2) * 8);
      }
      if (rel) mbar_arrive(bars + B_EMPTY + (3 + (tid & 1)) * 8);
      OBS(tid == 32, 3);
      {
        const uint32_t kst = base + OFF_K + (2 + (warp ^ 4) * 2 + (mi & 1)) * 1792 + (mi >> 1) * 896 + r8 * 16;
#pragma unroll
        for (int n = 0; n < 7; n++)
          stsm4(kst + n * 128, pack2(ak[n * 4], ak[n * 4 + 1]), pack2(ak[n * 4 + 2], ak[n * 4 + 3]), pack2(av[n * 4], av[n * 4 + 1]), pack2(av[n * 4 + 2], av[n * 4 + 3]));
        named_arrive_if(warp == 3, 1, 64);
      }
      OBS(tid == 96, 32); OBS(tid == 224, 34);
      named_sync(pp_in, 256);
      OBS(tid == 96, 14); OBS(tid == 224, 26);
      wg_fence();
#pragma unroll
      for (int s = QA; s < 7; s++) {
#pragma unroll
        for (int k = s * 4; k < s * 4 + 4; k++) {
          if (k == 28 - PQE) named_arrive_if(!wg || g1, pp_out, 256);
          wgmma_rs_n56<1>(aq, X[k], mkdesc(HI_SW128, dlq + k * 128), 1);
        }
        wg_commit();
        if (s == 4) { wg_wait<2>(); if ((tid & 127) == 0) mbar_arrive(bars + B_EMPTY + 5 * 8); }
      }
      if (PQE == 0) named_arrive_if(!wg || g1, pp_out, 256);
      wg_wait<0>();
      if (rel) mbar_arrive(bars + B_EMPTY + (6 + (tid & 1)) * 8);
      uint32_t Q[8][2];
#pragma unroll
      for (int n = 0; n < 7; n++) { Q[n + (n > 3)][0] = pack2(aq[n * 4], aq[n * 4 + 1]); Q[n + (n > 3)][1] = pack2(aq[n * 4 + 2], aq[n * 4 + 3]); }
#pragma unroll
      for (int h = 0; h < 2; h++) { Q[4][h] = t < 2 ? 0u : Q[3][h]; Q[3][h] = t < 2 ? Q[3][h] : 0u; }
      const uint32_t qst = base + OFF_Q + tl * 8192 + (mi >> 1) * 1024 + (w4 * 16 + (mi & 1) * 8 + r8) * 16;
#pragma unroll
      for (int n = 0; n < 8; n += 2) stsm4(qst + n * 1024, Q[n][0], Q[n][1], Q[n + 1][0], Q[n + 1][1]);
      smem_fence();
    }
    OBS(tid == 32, 5); OBS(tid == 160, 6);
    float acc[56];
    fresh(acc);
    const unsigned short* bp = (const unsigned short*)(wg ? p.b2 + mt * 128 : p.b1 + (g1 ? ft * 128 : 0)) + w4 * 16 + g;
    const uint32_t braw0 = __ldg(bp), braw1 = __ldg(bp + 8);
    if (wg == 0) {
      named_arrive(7, 256);
      if (g1) {
        named_sync(0, 256);
        gemm_stage<1>(acc, base, 0, 0);
        OBS(tid == 0, 20);
#pragma unroll 1
        for (int seg = 0, it = 1; seg < 4; seg++) {
          const int end = (J0 | J1 << 8 | J2 << 16 | 32 << 24) >> (seg * 8) & 255;
          if (seg) named_sync(11 + seg, 256);
          gemm_loop<1>(acc, base, it, end, rel, OBS_T0, 40);
          it = end;
        }
        wg_wait<0>();
        OBS(tid == 0, 21);
        if (rel) mbar_arrive(bars + B_EMPTY + 7 * 8);
        named_arrive(5, 256);
      }
    } else {
      const uint32_t dq = ((base + OFF_Q) >> 4) + (64u << 16), dk = (base + OFF_K) >> 4;
      const bool odd = g & 1, early = 2 * t + (g & 1) > g;
      uint32_t selA[5], selB[4];
#pragma unroll
      for (int j = 0; j < 5; j++) selA[j] = j == w4 + (early ? 0 : 1) ? (odd ? 0x1044u : 0x4410u) : 0x4444u;
#pragma unroll
      for (int j = 0; j < 4; j++) selB[j] = j == w4 ? (odd ? 0x3244u : 0x4432u) : 0x4444u;
      float Sc[2][40], Op[2][2][16];
      uint32_t A[2][5][4];
      auto scores = [&](int T) {
        fresh(Sc[0]); fresh(Sc[1]);
#pragma unroll
        for (int k = 0; k < 2; k++) {
#pragma unroll
          for (int hh = 0; hh < 2; hh++)
            wgmma_n80<0, 0>(Sc[hh], mkdesc(8, dq + T * 512 + hh * 256 + k * 128), mkdesc(112, dk + (8u << 16) + T * 896 + hh * 24 + k * 16), k);
          if (T) wg_commit();
        }
      };
      auto softmax = [&](int T) {
#pragma unroll
        for (int hh = 0; hh < 2; hh++) {
          uint32_t pp[2];
#pragma unroll
          for (int h = 0; h < 2; h++) {
            float c[3];
#pragma unroll
            for (int n = 0; n < 3; n++) {
              const float* q = Sc[hh] + (h + n) * 4 + 2 * h;
              asm("{\n.reg .pred p, a, b, c;\nsetp.ne.u32 p, %9, 0;\nsetp.eq.u32 a, %10, 1;\nsetp.eq.u32 b, %10, 2;\nsetp.eq.u32 c, %10, 3;\n"
                  "selp.f32 %0, %2, %1, p;\n@a selp.f32 %0, %4, %3, p;\n@b selp.f32 %0, %6, %5, p;\n@c selp.f32 %0, %8, %7, p;\n}"
                  : "=&f"(c[n]) : "f"(q[0]), "f"(q[1]), "f"(q[8]), "f"(q[9]), "f"(q[16]), "f"(q[17]), "f"(q[24]), "f"(q[25]), "r"((uint32_t)odd), "r"((tid >> 5) & 3));
            }
            uint32_t pk = pack2(early ? c[0] : c[2], c[1]);
            pk = pack2(bf_lo(pk) * SCALE, bf_hi(pk) * SCALE);
            float l0 = bf_lo(pk), l1 = bf_hi(pk);
            if (T == 0 && w4 == 0 && rb == 0) { if (early) l0 = -1e9f; if (h == 0) l1 = -1e9f; }
            float mx = fmaxf(l0, l1);
            mx = fmaxf(mx, __shfl_xor_sync(0xffffffffu, mx, 1));
            mx = fmaxf(mx, __shfl_xor_sync(0xffffffffu, mx, 2));
            float p0 = ex2_fast((l0 - mx) * LOG2E), p1 = ex2_fast((l1 - mx) * LOG2E);
            float sm = p0 + p1;
            sm += __shfl_xor_sync(0xffffffffu, sm, 1);
            sm += __shfl_xor_sync(0xffffffffu, sm, 2);
            const float inv = rcp_fast(sm);
            pp[h] = pack2(p0 * inv, p1 * inv);
          }
#pragma unroll
          for (int j = 0; j < 5; j++) {
            A[hh][j][0] = __byte_perm(pp[0], 0, selA[j]); A[hh][j][1] = j ? __byte_perm(pp[1], 0, selB[j ? j - 1 : 0]) : 0u;
            A[hh][j][2] = j < 4 ? __byte_perm(pp[0], 0, selB[j & 3]) : 0u; A[hh][j][3] = __byte_perm(pp[1], 0, selA[j]);
          }
        }
      };
      auto values = [&](int T) {
        fresh(Op[T][0]); fresh(Op[T][1]);
#pragma unroll
        for (int j = 0; j < 5; j++)
#pragma unroll
          for (int hh = 0; hh < 2; hh++) {
            if (j * 2 + hh == 10 - EARLY) wg_commit();
            wgmma_rs_n32<1>(Op[T][hh], A[hh][j], mkdesc(8, dk + (112u << 16) + 56 + T * 896 + hh * 24 + j * 224), j);
          }
        wg_commit();
      };
      auto resume = [&](int id) { wg_wait<1>(); named_arrive_if(g1, id, 256); wg_wait<0>(); };
      auto put = [&](int T) {
        unsigned char* og = scr + O_OFF + (rb * 2 + T) * 57344 + hp * 7168 + w4 * 256 + lane * 4;
        const float (&O)[2][16] = Op[T];
#pragma unroll
        for (int n = 0; n < 7; n++)
#pragma unroll
          for (int h = 0; h < 2; h++) {
            uint32_t v;
            if (n < 3) v = pack2(O[0][n * 4 + 2 * h], O[0][n * 4 + 2 * h + 1]);
            else if (n == 3) v = pack2(t < 2 ? O[0][12 + 2 * h] : O[1][2 * h], t < 2 ? O[0][13 + 2 * h] : O[1][2 * h + 1]);
            else v = pack2(O[1][(n - 3) * 4 + 2 * h], O[1][(n - 3) * 4 + 2 * h + 1]);
            stg32_if(1, og + n * 1024 + h * 128, v);
            if (OSLEEP) __nanosleep(OSLEEP);
          }
      };
      named_sync(7, 256);
      wg_fence();
      scores(1);
      resume(12);
      OBS(tid == 160, 10);
      softmax(1);
      OBS(tid == 160, 30);
      mbar_wait(bars + B_HALO, 0);
      OBS(tid == 160, 7);
      wg_fence();
      scores(0);
      values(1);
      resume(13);
      OBS(tid == 160, 33);
      softmax(0);
      wg_fence();
      values(0);
      resume(14);
      OBS(tid == 160, 35);
      put(1); put(0);
      named_sync(11, 128);
      if (warp == 4) publish(scr, C_O + rb);
      if (tid == 160) mbar_arrive(bars + B_ATT);
      OBS(tid == 160, 8);
      fresh(acc);
    }
    if (g1 && (wg == 0 || ((WARM & 1) && warp == 7))) {
      unsigned char* ug = scr + (d1 * HU_T + 32 + ft) * BT + w4 * 3584 + lane * 4;
      const float hb0 = 0.5f * bf_lo(braw0), hb1 = 0.5f * bf_lo(braw1);
#pragma unroll
      for (int j = 0; j < 28; j++) {
        float h0, h1;
        if (EXACT) { const uint32_t r = hfma2(pack2(acc[2 * j], acc[2 * j + 1]), 0x3f003f00u, pack2(j & 1 ? hb1 : hb0, j & 1 ? hb1 : hb0)); h0 = bf_lo(r); h1 = bf_hi(r); }
        else { h0 = fmaf(acc[2 * j], 0.5f, j & 1 ? hb1 : hb0); h1 = fmaf(acc[2 * j + 1], 0.5f, j & 1 ? hb1 : hb0); }
        const float t0 = tanh_fast(h0 * fmaf(h0 * h0, 0.2854192648f, 1.5957691216f)), t1 = tanh_fast(h1 * fmaf(h1 * h1, 0.2854192648f, 1.5957691216f));
        const uint32_t o = pack2(fmaf(h0, t0, h0), fmaf(h1, t1, h1));
        stg32_if(tid < 128, ug + (j & 1) * 1792 + (j >> 1) * 128, o);
        if (j == OPJ - 1 && wg == 0) named_arrive(3, 256);
      }
      if (wg == 0) {
        if (w4) named_arrive(2, 128);
        else { named_sync(2, 128); publish(scr, C_U + d1); }
        OBS(tid == 0, 9);
      }
    }
    uint32_t Sv[28];
    uint4 Xr[7];
    const int orow = (mt * 64 + w4 * 16 + (lane >> 1)) * 896 + dt * 224 + (lane & 1) * 16;
    if (wg == 1) {
      float as[56];
      fresh(as);
      mbar_wait(bars + B_RES, 0);
      if (g1) named_sync(5, 256);
#pragma unroll
      for (int i = 0; i < 7; i++) Xr[i] = lds128(base + OFF_Q + (w4 * 16 + (lane >> 1)) * 224 + (lane & 1) * 16 + i * 32);
      if (g1) named_sync(3, 256);
      gemm_stage<0>(as, base, 0, 0);
      OBS(tid == 128, 22);
      gemm_loop<0>(as, base, 1, 7, rel, OBS_T0, 104);
      wg_wait<0>();
      OBS(tid == 128, 23);
      if (rel) mbar_arrive(bars + B_EMPTY + 6 * 8);
      fresh(acc);
      gemm_stage<1>(acc, base, 7, 0);
      OBS(tid == 128, 24);
#pragma unroll
      for (int j = 0; j < 28; j++) Sv[j] = pack2(as[2 * j], as[2 * j + 1]);
      gemm_loop<1>(acc, base, 8, 35, rel, OBS_T0, 65);
      wg_wait<0>();
      OBS(tid == 128, 25);
    } else {
#pragma unroll
      for (int j = 0; j < 28; j++) asm volatile("" : "=r"(Sv[j]));
#pragma unroll
      for (int i = 0; i < 7; i++) asm volatile("" : "=r"(Xr[i].x), "=r"(Xr[i].y), "=r"(Xr[i].z), "=r"(Xr[i].w));
    }
    if (wg == 1 || ((WARM & 2) && warp == 3 && g1)) {
      const uint32_t tb = base + OFF_K + (wg ? w4 : 4) * 4480;
      const uint32_t ts = tb + (mi >> 1) * 320 + ((mi & 1) * 8 + r8) * 16, tl = tb + (lane & 1) * 320 + (lane >> 1) * 16;
      unsigned char* outp = p.out + orow;
      const float hb0 = 0.5f * bf_lo(braw0), hb1 = 0.5f * bf_lo(braw1);
#pragma unroll
      for (int i = 0; i < 8; i++) {
        if (i < 7) {
          uint32_t R[4];
#pragma unroll
          for (int q = 0; q < 4; q++) {
            const int j = i * 4 + q;
            float h0, h1;
            if (EXACT) { const uint32_t r = hfma2(pack2(acc[2 * j], acc[2 * j + 1]), 0x3f003f00u, pack2(j & 1 ? hb1 : hb0, j & 1 ? hb1 : hb0)); h0 = bf_lo(r); h1 = bf_hi(r); }
            else { h0 = fmaf(acc[2 * j], 0.5f, j & 1 ? hb1 : hb0); h1 = fmaf(acc[2 * j + 1], 0.5f, j & 1 ? hb1 : hb0); }
            R[q] = hmul2(Sv[j], pack2(fmaf(h0, tanh_fast(h0), h0), fmaf(h1, tanh_fast(h1), h1)));
          }
          stsm4(ts + i * 640, R[0], R[1], R[2], R[3]);
        }
        if (i > 0) {
          const uint4 v = lds128(tl + (i - 1) * 640), x = Xr[i - 1];
          stg128_if(tid & 128, outp + (i - 1) * 32, hadd2(x.x, v.x), hadd2(x.y, v.y), hadd2(x.z, v.z), hadd2(x.w, v.w));
        }
        __syncwarp();
      }
      OBS(tid == 128, 27);
    }
  }
}

typedef CUresult (*EncFn)(CUtensorMap*, CUtensorMapDataType, cuuint32_t, void*, const cuuint64_t*, const cuuint64_t*, const cuuint32_t*,
                          const cuuint32_t*, CUtensorMapInterleave, CUtensorMapSwizzle, CUtensorMapL2promotion, CUtensorMapFloatOOBfill);
void enc(EncFn f, CUtensorMap* m, const void* ptr, cuuint64_t d0, cuuint64_t d1, cuuint64_t d2, cuuint64_t s1, cuuint64_t s2, cuuint32_t b1, cuuint32_t b2, cuuint32_t b0 = 64) {
  const cuuint64_t gd[3] = {d0, d1, d2}, gs[2] = {s1 * 2, s2 * 2};
  const cuuint32_t bx[3] = {b0, b1, b2}, es[3] = {1, 1, 1};
  f(m, CU_TENSOR_MAP_DATA_TYPE_BFLOAT16, 3, (void*)ptr, gd, gs, bx, es, CU_TENSOR_MAP_INTERLEAVE_NONE, b0 == 64 ? CU_TENSOR_MAP_SWIZZLE_128B : CU_TENSOR_MAP_SWIZZLE_NONE,
    CU_TENSOR_MAP_L2_PROMOTION_L2_128B, CU_TENSOR_MAP_FLOAT_OOB_FILL_NONE);
}
}

extern "C" void kernel_launch(void* const* d_in, const int* in_sizes, int n_in, void* d_out, int out_size) {
  (void)in_sizes; (void)n_in; (void)out_size;
  void* fp = nullptr;
  cudaDriverEntryPointQueryResult qr;
  cudaGetDriverEntryPoint("cuTensorMapEncodeTiled", &fp, cudaEnableDefault, &qr);
  EncFn f = (EncFn)fp;
  CUtensorMap m_x, m_wkv, m_wq, m_w1, m_w2, m_res;
  void* scr = nullptr;
  cudaGetSymbolAddress(&scr, g_scr);
  enc(f, &m_x, d_in[0], D_, S_, 1, D_, D_, 128, 1);
  enc(f, &m_wkv, d_in[1], D_, D_, 3, 3 * D_, D_, 64, 2);
  enc(f, &m_wq, d_in[1], D_, D_, 3, 3 * D_, D_, 224, 1);
  enc(f, &m_w1, d_in[4], F_, S_, 1, F_, F_, 64, 1);
  enc(f, &m_w2, d_in[6], S_, F_, 1, S_, S_, 64, 1);
  enc(f, &m_res, d_in[0], D_, S_, 1, D_, D_, 64, 1, 112);
  Params p;
  p.wo = (const unsigned char*)d_in[2];
  p.w1 = (const unsigned char*)d_in[4]; p.b1 = (const unsigned char*)d_in[5];
  p.w2 = (const unsigned char*)d_in[6]; p.b2 = (const unsigned char*)d_in[7];
  p.out = (unsigned char*)d_out; p.scr = (unsigned char*)scr;
  cudaFuncSetAttribute(fused_kernel, cudaFuncAttributeMaxDynamicSharedMemorySize, SMEM_BYTES);
  fused_kernel<<<128, NTHREADS, SMEM_BYTES, cudaStreamPerThread>>>(m_x, m_wkv, m_wq, m_w1, m_w2, m_res, p);
}
```

```cpp
#include <cuda_runtime.h>
#include <cuda.h>
#include <cuda_bf16.h>
#include <stdint.h>

template<int TA, int TB> __device__ __forceinline__ void wgmma_n112(float (&d)[56], uint64_t da, uint64_t db, int sc) {
  asm volatile("{\n.reg .pred p;\nsetp.ne.b32 p, %58, 0;\n"
    "wgmma.mma_async.sync.aligned.m64n112k16.f32.bf16.bf16 {%0, %1, %2, %3, %4, %5, %6, %7, %8, %9, %10, %11, %12, %13, %14, %15, %16, %17, %18, %19, %20, %21, %22, %23, %24, %25, %26, %27, %28, %29, %30, %31, %32, %33, %34, %35, %36, %37, %38, %39, %40, %41, %42, %43, %44, %45, %46, %47, %48, %49, %50, %51, %52, %53, %54, %55}, %56, %57, p, 1, 1, %59, %60;\n}\n"
    : "+f"(d[0]), "+f"(d[1]), "+f"(d[2]), "+f"(d[3]), "+f"(d[4]), "+f"(d[5]), "+f"(d[6]), "+f"(d[7]), "+f"(d[8]), "+f"(d[9]), "+f"(d[10]), "+f"(d[11]), "+f"(d[12]), "+f"(d[13]), "+f"(d[14]), "+f"(d[15]), "+f"(d[16]), "+f"(d[17]), "+f"(d[18]), "+f"(d[19]), "+f"(d[20]), "+f"(d[21]), "+f"(d[22]), "+f"(d[23]), "+f"(d[24]), "+f"(d[25]), "+f"(d[26]), "+f"(d[27]), "+f"(d[28]), "+f"(d[29]), "+f"(d[30]), "+f"(d[31]), "+f"(d[32]), "+f"(d[33]), "+f"(d[34]), "+f"(d[35]), "+f"(d[36]), "+f"(d[37]), "+f"(d[38]), "+f"(d[39]), "+f"(d[40]), "+f"(d[41]), "+f"(d[42]), "+f"(d[43]), "+f"(d[44]), "+f"(d[45]), "+f"(d[46]), "+f"(d[47]), "+f"(d[48]), "+f"(d[49]), "+f"(d[50]), "+f"(d[51]), "+f"(d[52]), "+f"(d[53]), "+f"(d[54]), "+f"(d[55])
    : "l"(da), "l"(db), "r"(sc), "n"(TA), "n"(TB));
}

template<int TA, int TB> __device__ __forceinline__ void wgmma_n80(float (&d)[40], uint64_t da, uint64_t db, int sc) {
  asm volatile("{\n.reg .pred p;\nsetp.ne.b32 p, %42, 0;\n"
    "wgmma.mma_async.sync.aligned.m64n80k16.f32.bf16.bf16 {%0, %1, %2, %3, %4, %5, %6, %7, %8, %9, %10, %11, %12, %13, %14, %15, %16, %17, %18, %19, %20, %21, %22, %23, %24, %25, %26, %27, %28, %29, %30, %31, %32, %33, %34, %35, %36, %37, %38, %39}, %40, %41, p, 1, 1, %43, %44;\n}\n"
    : "+f"(d[0]), "+f"(d[1]), "+f"(d[2]), "+f"(d[3]), "+f"(d[4]), "+f"(d[5]), "+f"(d[6]), "+f"(d[7]), "+f"(d[8]), "+f"(d[9]), "+f"(d[10]), "+f"(d[11]), "+f"(d[12]), "+f"(d[13]), "+f"(d[14]), "+f"(d[15]), "+f"(d[16]), "+f"(d[17]), "+f"(d[18]), "+f"(d[19]), "+f"(d[20]), "+f"(d[21]), "+f"(d[22]), "+f"(d[23]), "+f"(d[24]), "+f"(d[25]), "+f"(d[26]), "+f"(d[27]), "+f"(d[28]), "+f"(d[29]), "+f"(d[30]), "+f"(d[31]), "+f"(d[32]), "+f"(d[33]), "+f"(d[34]), "+f"(d[35]), "+f"(d[36]), "+f"(d[37]), "+f"(d[38]), "+f"(d[39])
    : "l"(da), "l"(db), "r"(sc), "n"(TA), "n"(TB));
}

template<int TB> __device__ __forceinline__ void wgmma_rs_n120(float (&d)[60], const uint32_t (&a)[4], uint64_t db, int sc) {
  asm volatile("{\n.reg .pred p;\nsetp.ne.b32 p, %65, 0;\n"
    "wgmma.mma_async.sync.aligned.m64n120k16.f32.bf16.bf16 {%0, %1, %2, %3, %4, %5, %6, %7, %8, %9, %10, %11, %12, %13, %14, %15, %16, %17, %18, %19, %20, %21, %22, %23, %24, %25, %26, %27, %28, %29, %30, %31, %32, %33, %34, %35, %36, %37, %38, %39, %40, %41, %42, %43, %44, %45, %46, %47, %48, %49, %50, %51, %52, %53, %54, %55, %56, %57, %58, %59}, {%60, %61, %62, %63}, %64, p, 1, 1, %66;\n}\n"
    : "+f"(d[0]), "+f"(d[1]), "+f"(d[2]), "+f"(d[3]), "+f"(d[4]), "+f"(d[5]), "+f"(d[6]), "+f"(d[7]), "+f"(d[8]), "+f"(d[9]), "+f"(d[10]), "+f"(d[11]), "+f"(d[12]), "+f"(d[13]), "+f"(d[14]), "+f"(d[15]), "+f"(d[16]), "+f"(d[17]), "+f"(d[18]), "+f"(d[19]), "+f"(d[20]), "+f"(d[21]), "+f"(d[22]), "+f"(d[23]), "+f"(d[24]), "+f"(d[25]), "+f"(d[26]), "+f"(d[27]), "+f"(d[28]), "+f"(d[29]), "+f"(d[30]), "+f"(d[31]), "+f"(d[32]), "+f"(d[33]), "+f"(d[34]), "+f"(d[35]), "+f"(d[36]), "+f"(d[37]), "+f"(d[38]), "+f"(d[39]), "+f"(d[40]), "+f"(d[41]), "+f"(d[42]), "+f"(d[43]), "+f"(d[44]), "+f"(d[45]), "+f"(d[46]), "+f"(d[47]), "+f"(d[48]), "+f"(d[49]), "+f"(d[50]), "+f"(d[51]), "+f"(d[52]), "+f"(d[53]), "+f"(d[54]), "+f"(d[55]), "+f"(d[56]), "+f"(d[57]), "+f"(d[58]), "+f"(d[59])
    : "r"(a[0]), "r"(a[1]), "r"(a[2]), "r"(a[3]), "l"(db), "r"(sc), "n"(TB));
}

template<int TB> __device__ __forceinline__ void wgmma_rs_n56(float (&d)[28], const uint32_t (&a)[4], uint64_t db, int sc) {
  asm volatile("{\n.reg .pred p;\nsetp.ne.b32 p, %33, 0;\n"
    "wgmma.mma_async.sync.aligned.m64n56k16.f32.bf16.bf16 {%0, %1, %2, %3, %4, %5, %6, %7, %8, %9, %10, %11, %12, %13, %14, %15, %16, %17, %18, %19, %20, %21, %22, %23, %24, %25, %26, %27}, {%28, %29, %30, %31}, %32, p, 1, 1, %34;\n}\n"
    : "+f"(d[0]), "+f"(d[1]), "+f"(d[2]), "+f"(d[3]), "+f"(d[4]), "+f"(d[5]), "+f"(d[6]), "+f"(d[7]), "+f"(d[8]), "+f"(d[9]), "+f"(d[10]), "+f"(d[11]), "+f"(d[12]), "+f"(d[13]), "+f"(d[14]), "+f"(d[15]), "+f"(d[16]), "+f"(d[17]), "+f"(d[18]), "+f"(d[19]), "+f"(d[20]), "+f"(d[21]), "+f"(d[22]), "+f"(d[23]), "+f"(d[24]), "+f"(d[25]), "+f"(d[26]), "+f"(d[27])
    : "r"(a[0]), "r"(a[1]), "r"(a[2]), "r"(a[3]), "l"(db), "r"(sc), "n"(TB));
}

template<int TB> __device__ __forceinline__ void wgmma_rs_n32(float (&d)[16], const uint32_t (&a)[4], uint64_t db, int sc) {
  asm volatile("{\n.reg .pred p;\nsetp.ne.b32 p, %21, 0;\n"
    "wgmma.mma_async.sync.aligned.m64n32k16.f32.bf16.bf16 {%0, %1, %2, %3, %4, %5, %6, %7, %8, %9, %10, %11, %12, %13, %14, %15}, {%16, %17, %18, %19}, %20, p, 1, 1, %22;\n}\n"
    : "+f"(d[0]), "+f"(d[1]), "+f"(d[2]), "+f"(d[3]), "+f"(d[4]), "+f"(d[5]), "+f"(d[6]), "+f"(d[7]), "+f"(d[8]), "+f"(d[9]), "+f"(d[10]), "+f"(d[11]), "+f"(d[12]), "+f"(d[13]), "+f"(d[14]), "+f"(d[15])
    : "r"(a[0]), "r"(a[1]), "r"(a[2]), "r"(a[3]), "l"(db), "r"(sc), "n"(TB));
}

template<int TB> __device__ __forceinline__ void wgmma_rs_n80(float (&d)[40], const uint32_t (&a)[4], uint64_t db, int sc) {
  asm volatile("{\n.reg .pred p;\nsetp.ne.b32 p, %45, 0;\n"
    "wgmma.mma_async.sync.aligned.m64n80k16.f32.bf16.bf16 {%0, %1, %2, %3, %4, %5, %6, %7, %8, %9, %10, %11, %12, %13, %14, %15, %16, %17, %18, %19, %20, %21, %22, %23, %24, %25, %26, %27, %28, %29, %30, %31, %32, %33, %34, %35, %36, %37, %38, %39}, {%40, %41, %42, %43}, %44, p, 1, 1, %46;\n}\n"
    : "+f"(d[0]), "+f"(d[1]), "+f"(d[2]), "+f"(d[3]), "+f"(d[4]), "+f"(d[5]), "+f"(d[6]), "+f"(d[7]), "+f"(d[8]), "+f"(d[9]), "+f"(d[10]), "+f"(d[11]), "+f"(d[12]), "+f"(d[13]), "+f"(d[14]), "+f"(d[15]), "+f"(d[16]), "+f"(d[17]), "+f"(d[18]), "+f"(d[19]), "+f"(d[20]), "+f"(d[21]), "+f"(d[22]), "+f"(d[23]), "+f"(d[24]), "+f"(d[25]), "+f"(d[26]), "+f"(d[27]), "+f"(d[28]), "+f"(d[29]), "+f"(d[30]), "+f"(d[31]), "+f"(d[32]), "+f"(d[33]), "+f"(d[34]), "+f"(d[35]), "+f"(d[36]), "+f"(d[37]), "+f"(d[38]), "+f"(d[39])
    : "r"(a[0]), "r"(a[1]), "r"(a[2]), "r"(a[3]), "l"(db), "r"(sc), "n"(TB));
}

namespace {
constexpr int S_ = 2048, D_ = 448, F_ = 1792;
constexpr int NSLOT = 8, SLOT = 22528;
constexpr int OFF_X = 7 * 16384;
constexpr int OFF_WQ = 8 * 16384;
constexpr int OFF_Q = NSLOT * SLOT;
constexpr int OFF_K = OFF_Q + 16384;
constexpr int OFF_BAR = 14 * 16384;
constexpr int OFF_LN = OFF_BAR + 384;
constexpr int OFF_OBS = OFF_BAR + 512;
constexpr int SMEM_BYTES = OFF_OBS + 1024;
#define PACE0 0
#define PACE1 600
#define PACE2 700
#define WARM 3
#define NW0 2
#define HEAT 1
#define T0 0
#define TP 250
#define J3 0
#define J1 9
#define J2 14
#define EARLY 4
#define PPE 4
#define PQE 2
#define LANDOBS 0
#define TRUNC 0
#define KOBS 0
#define PRE 1
#define QA 2
#define HEARLY 0
#define OSLEEP 20
#define PROBE 1
#define WOP 0
#define OGRP 2
#define OMODE 3
#define GCH 2
#define GLAG 2
#define GSLOW 0
#define RH 32
#define NOST 0
#define GOBS 0
#define OPW 0
#define SEARLY 1
#define EXACT 0
#define SOBS 0
#define FREQ 0
#define OBS(c, i) do {} while (0)
#define OBSG(c, i, j) do {} while (0)
constexpr int NTHREADS = 384;
constexpr float SCALE = 0.18898223650461361f, LOG2E = 1.4426950408889634f;
constexpr int BT = 14336;

constexpr int HU_T = 67;
constexpr int O_OFF = 4 * HU_T * BT;
constexpr int HALO_OFF = O_OFF + 32 * 7 * 8192;
constexpr int CNT_OFF = HALO_OFF + 128 * 3584;
constexpr int SCR_BYTES = CNT_OFF + 160 * 128;
constexpr int C_WO = 0, C_TK = 1, C_U = 2, C_O = 8, C_H = 24, C_HALO = 32;
__device__ __align__(1024) unsigned char g_scr[SCR_BYTES];

__device__ __forceinline__ uint32_t smem_u32(const void* p) { return (uint32_t)__cvta_generic_to_shared(p); }
__device__ __forceinline__ void mbar_init(uint32_t bar, uint32_t cnt) { asm volatile("mbarrier.init.shared::cta.b64 [%0], %1;" :: "r"(bar), "r"(cnt)); }
__device__ __forceinline__ void mbar_expect_tx(uint32_t bar, uint32_t bytes) { asm volatile("mbarrier.arrive.expect_tx.shared::cta.b64 _, [%0], %1;" :: "r"(bar), "r"(bytes) : "memory"); }
__device__ __forceinline__ void mbar_arrive_if(uint32_t c, uint32_t bar) { asm volatile("{\n.reg .pred q;\nsetp.ne.u32 q, %1, 0;\n@q mbarrier.arrive.shared::cta.b64 _, [%0];\n}" :: "r"(bar), "r"(c) : "memory"); }
__device__ __forceinline__ void mbar_arrive(uint32_t bar) { asm volatile("mbarrier.arrive.shared::cta.b64 _, [%0];" :: "r"(bar) : "memory"); }
__device__ __forceinline__ void mbar_wait(uint32_t bar, uint32_t parity) {
  asm volatile("{\n.reg .pred p;\n.reg .u32 n;\nmov.u32 n, 0;\nLAB_WAIT:\n"
               "mbarrier.try_wait.parity.shared::cta.b64 p, [%0], %1;\n@p bra DONE;\n"
               "add.u32 n, n, 1;\nsetp.lt.u32 p, n, 400000;\n@p bra LAB_WAIT;\ntrap;\nDONE:\n}" :: "r"(bar), "r"(parity) : "memory");
}
__device__ __forceinline__ uint32_t mbar_try(uint32_t bar, uint32_t parity) {
  uint32_t ok;
  asm volatile("{\n.reg .pred p;\nmbarrier.test_wait.parity.shared::cta.b64 p, [%1], %2;\nselp.u32 %0, 1, 0, p;\n}" : "=r"(ok) : "r"(bar), "r"(parity) : "memory");
  return ok;
}
__device__ __forceinline__ void tma3d(uint32_t dst, const CUtensorMap* m, int c0, int c1, int c2, uint32_t bar) {
  asm volatile("cp.async.bulk.tensor.3d.shared::cluster.global.mbarrier::complete_tx::bytes [%0], [%1, {%3, %4, %5}], [%2];"
               :: "r"(dst), "l"(m), "r"(bar), "r"(c0), "r"(c1), "r"(c2) : "memory");
}
__device__ __forceinline__ void bulk_g2s(uint32_t dst, const void* src, uint32_t bytes, uint32_t bar) {
  asm volatile("cp.async.bulk.shared::cluster.global.mbarrier::complete_tx::bytes [%0], [%1], %2, [%3];" :: "r"(dst), "l"(src), "r"(bytes), "r"(bar) : "memory");
}
__device__ __forceinline__ void wg_fence() { asm volatile("wgmma.fence.sync.aligned;" ::: "memory"); }
__device__ __forceinline__ void wg_commit() { asm volatile("wgmma.commit_group.sync.aligned;" ::: "memory"); }
template <int N> __device__ __forceinline__ void wg_wait() { asm volatile("wgmma.wait_group.sync.aligned %0;" :: "n"(N) : "memory"); }
__device__ __forceinline__ void smem_fence() { asm volatile("fence.proxy.async.shared::cta;" ::: "memory"); }
__device__ __forceinline__ void stg128(void* p, uint32_t a, uint32_t b, uint32_t c, uint32_t d) { asm volatile("st.global.v4.u32 [%0], {%1,%2,%3,%4};" :: "l"(p), "r"(a), "r"(b), "r"(c), "r"(d) : "memory"); }
__device__ __forceinline__ void stg32(void* p, uint32_t v) { asm volatile("st.global.u32 [%0], %1;" :: "l"(p), "r"(v) : "memory"); }
__device__ __forceinline__ uint4 ldg128(const void* p) { uint4 v; asm volatile("ld.global.nc.L1::no_allocate.v4.u32 {%0,%1,%2,%3}, [%4];" : "=r"(v.x), "=r"(v.y), "=r"(v.z), "=r"(v.w) : "l"(p)); return v; }
__device__ __forceinline__ void publish(unsigned char* scr, int i) {
  asm volatile("{\n.reg .pred q;\nelect.sync _|q, 0xffffffff;\n@q red.relaxed.gpu.global.inc.u32 [%0], 0xffffffff;\n}" :: "l"(scr + CNT_OFF + i * 128) : "memory");
}
__device__ __forceinline__ void spin_ge(unsigned char* scr, int i, unsigned target) {
  asm volatile("{\n.reg .pred p;\n.reg .u32 n, v;\nmov.u32 n, 0;\nLAB_SPIN:\n"
               "ld.acquire.gpu.global.u32 v, [%0];\nsetp.ge.u32 p, v, %1;\nvote.sync.all.pred p, p, 0xffffffff;\n@p bra DONE;\n"
               "add.u32 n, n, 1;\nsetp.lt.u32 p, n, 4000000;\n@p bra LAB_SPIN;\ntrap;\nDONE:\n}" :: "l"(scr + CNT_OFF + i * 128), "r"(target) : "memory");
}
__device__ __forceinline__ int lane_id() { int l; asm volatile("mov.u32 %0, %%laneid;" : "=r"(l)); return l; }
__device__ __forceinline__ uint32_t pin(uint32_t v) { return __shfl_xor_sync(0xffffffffu, v, blockIdx.y); }
__device__ __forceinline__ unsigned char* pin(unsigned char* p) { return (unsigned char*)(((uint64_t)pin((uint32_t)((uint64_t)p >> 32)) << 32) | pin((uint32_t)(uint64_t)p)); }
__device__ __forceinline__ bool elect() {
  uint32_t r; asm volatile("{\n.reg .pred p;\nelect.sync _|p, 0xffffffff;\nselp.u32 %0, 1, 0, p;\n}" : "=r"(r)); return r != 0;
}
__device__ __forceinline__ uint4 lds128(uint32_t a) { uint4 v; asm volatile("ld.shared.v4.u32 {%0,%1,%2,%3}, [%4];" : "=r"(v.x), "=r"(v.y), "=r"(v.z), "=r"(v.w) : "r"(a) : "memory"); return v; }
__device__ __forceinline__ uint2 lds64(uint32_t a) { uint2 v; asm volatile("ld.shared.v2.u32 {%0,%1}, [%2];" : "=r"(v.x), "=r"(v.y) : "r"(a) : "memory"); return v; }
__device__ __forceinline__ void sts128(uint32_t p, uint32_t a, uint32_t b, uint32_t c, uint32_t d) { asm volatile("st.shared.v4.u32 [%0], {%1,%2,%3,%4};" :: "r"(p), "r"(a), "r"(b), "r"(c), "r"(d) : "memory"); }
__device__ __forceinline__ void sts32(uint32_t a, float v) { asm volatile("st.shared.f32 [%0], %1;" :: "r"(a), "f"(v) : "memory"); }
__device__ __forceinline__ void named_sync(int id, int n) { asm volatile("bar.sync %0, %1;" :: "r"(id), "r"(n) : "memory"); }
__device__ __forceinline__ void named_arrive(int id, int n) { asm volatile("bar.arrive %0, %1;" :: "r"(id), "r"(n) : "memory"); }
__device__ __forceinline__ void named_arrive_if(uint32_t c, int id, int n) { asm volatile("{\n.reg .pred q;\nsetp.ne.u32 q, %2, 0;\n@q bar.arrive %0, %1;\n}" :: "r"(id), "r"(n), "r"(c) : "memory"); }
__device__ __forceinline__ uint64_t mkdesc(uint32_t hi, uint32_t lo) { return ((uint64_t)hi << 32) | lo; }
constexpr uint32_t HI_SW128 = 0x40000040u;
__device__ __forceinline__ uint32_t pack2(float lo, float hi) { uint32_t r; asm("cvt.rn.bf16x2.f32 %0, %1, %2;" : "=r"(r) : "f"(hi), "f"(lo)); return r; }
__device__ __forceinline__ float bf_lo(uint32_t v) { return __uint_as_float(v << 16); }
__device__ __forceinline__ float bf_hi(uint32_t v) { return __uint_as_float(v & 0xffff0000u); }
__device__ __forceinline__ float rbf(float x) { return bf_lo(pack2(x, 0.f)); }
__device__ __forceinline__ uint32_t hsub2(uint32_t a, uint32_t b) { uint32_t r; asm("sub.rn.bf16x2 %0, %1, %2;" : "=r"(r) : "r"(a), "r"(b)); return r; }
__device__ __forceinline__ uint32_t hadd2(uint32_t a, uint32_t b) { uint32_t r; asm("add.rn.bf16x2 %0, %1, %2;" : "=r"(r) : "r"(a), "r"(b)); return r; }
__device__ __forceinline__ uint32_t hmul2(uint32_t a, uint32_t b) { uint32_t r; asm("mul.rn.bf16x2 %0, %1, %2;" : "=r"(r) : "r"(a), "r"(b)); return r; }
__device__ __forceinline__ uint32_t hfma2(uint32_t a, uint32_t b, uint32_t c) { uint32_t r; asm("fma.rn.bf16x2 %0, %1, %2, %3;" : "=r"(r) : "r"(a), "r"(b), "r"(c)); return r; }
__device__ __forceinline__ float tanh_fast(float x) { float r; asm("tanh.approx.f32 %0, %1;" : "=f"(r) : "f"(x)); return r; }
__device__ __forceinline__ float rcp_fast(float x) { float r; asm("rcp.approx.ftz.f32 %0, %1;" : "=f"(r) : "f"(x)); return r; }
__device__ __forceinline__ float ex2_fast(float x) { float r; asm("ex2.approx.ftz.f32 %0, %1;" : "=f"(r) : "f"(x)); return r; }
__device__ __forceinline__ void mma16816(float (&c)[4], uint32_t a0, uint32_t a1, uint32_t a2, uint32_t a3, uint32_t b0, uint32_t b1) {
  asm volatile("mma.sync.aligned.m16n8k16.row.col.f32.bf16.bf16.f32 {%0,%1,%2,%3}, {%4,%5,%6,%7}, {%8,%9}, {%0,%1,%2,%3};"
               : "+f"(c[0]), "+f"(c[1]), "+f"(c[2]), "+f"(c[3]) : "r"(a0), "r"(a1), "r"(a2), "r"(a3), "r"(b0), "r"(b1));
}
__device__ __forceinline__ void ldsm4(uint32_t (&r)[4], uint32_t addr) {
  asm volatile("ldmatrix.sync.aligned.m8n8.x4.shared.b16 {%0,%1,%2,%3}, [%4];" : "=r"(r[0]), "=r"(r[1]), "=r"(r[2]), "=r"(r[3]) : "r"(addr) : "memory");
}
__device__ __forceinline__ void stsm4(uint32_t addr, uint32_t a, uint32_t b, uint32_t c, uint32_t d) {
  asm volatile("stmatrix.sync.aligned.m8n8.x4.shared.b16 [%0], {%1,%2,%3,%4};" :: "r"(addr), "r"(a), "r"(b), "r"(c), "r"(d) : "memory");
}

__device__ __forceinline__ float ln_rstd(float var, float eps = 1e-5f) {
  float sd;
  asm("sqrt.approx.ftz.f32 %0, %1;" : "=f"(sd) : "f"(rbf(rbf(var) + eps)));
  return rcp_fast(rbf(sd));
}
__device__ __forceinline__ float ln_var(float mean, float sq) { return fmaxf(fmaf(-mean, mean, sq * (1.0f / D_)), 0.f); }
struct LnC { uint32_t m, rh, rl; };
__device__ __forceinline__ LnC ln_consts(float sum, float sq, float eps) {
  const float mean = sum * (1.0f / D_), r = ln_rstd(ln_var(mean, sq), eps), rh = rbf(r);
  LnC c; c.m = pack2(mean, mean); c.rh = pack2(rh, rh); c.rl = pack2(r - rh, r - rh);
  return c;
}
__device__ __forceinline__ uint32_t ln_apply(uint32_t x, const LnC& c) {
  uint32_t d = hsub2(x, c.m);
  return hfma2(d, c.rh, hmul2(d, c.rl));
}

__device__ __forceinline__ void fence_code(int id) {
  asm volatile("{\n.reg .pred q;\nLAB_F:\nsetp.eq.u32 q, %0, %1;\n@q st.volatile.shared.u32 [%2], %2;\n@q bra LAB_F;\n}" :: "r"(blockIdx.x), "r"(0x70000000 + id), "r"(0) : "memory");
}
template <int N> __device__ __forceinline__ void fresh(float (&a)[N]) {
#pragma unroll
  for (int i = 0; i < N; i++) asm volatile("" : "=f"(a[i]));
}
constexpr int B_EMPTY = 64, B_X = 128, B_KV = 192, B_WQ = 248, B_HALO = 256, B_RES = 264, B_ATT = 272, B_GATE = 280, B_T0 = 304;

template <int TA>
__device__ __forceinline__ void gemm_issue(float (&acc)[56], uint32_t lo, int sc) {
  wg_fence();
#pragma unroll
  for (int k = 0; k < 4; k++)
    wgmma_n112<TA, 1>(acc, mkdesc(TA ? HI_SW128 : 8, lo + (TA ? 512u << 16 : 64u << 16) + k * 128), mkdesc(8, lo + (112u << 16) + 512 + k * 224), sc | k);
  wg_commit();
}
template <int TA>
__device__ __forceinline__ void gemm_stage(float (&acc)[56], uint32_t base, int it, int sc) {
  mbar_wait(base + OFF_BAR + (it & 7) * 8, (it >> 3) & 1);
  gemm_issue<TA>(acc, (base >> 4) + (it & 7) * (SLOT >> 4), sc);
}
template <int TA>
__device__ __forceinline__ void gemm_loop(float (&acc)[56], uint32_t base, int it, int end, bool rel, int oi, uint32_t ok = 0, int gate_it = -1, uint32_t gate = 0) {
#pragma unroll 1
  for (; it < end;) {
    if (__builtin_expect(!ok, 0)) mbar_wait(base + OFF_BAR + (it & 7) * 8, (it >> 3) & 1);
    gemm_issue<TA>(acc, (base >> 4) + (it & 7) * (SLOT >> 4), 1);
    OBS(SOBS && rel, oi + it);
    it++;
    ok = mbar_try(base + OFF_BAR + (it & 7) * 8, (it >> 3) & 1);
    wg_wait<1>();
    if (rel || it == gate_it) mbar_arrive(rel ? base + OFF_BAR + B_EMPTY + ((it - 2) & 7) * 8 : gate);
  }
}
__device__ __forceinline__ void produce_box(uint32_t base, int it, int end, const CUtensorMap* mp, int c0, uint32_t tn) {
  int c1 = 0;
#pragma unroll 1
  for (; it < end; it++) {
    const uint32_t fb = base + OFF_BAR + (it & 7) * 8;
    mbar_wait(fb + B_EMPTY, (it >> 3) & 1);
    if (T0) { while ((int)(clock() - tn) < 0); tn += TP; }
    if (elect()) { mbar_expect_tx(fb, 8192); tma3d(base + (it & 7) * SLOT, mp, c0, c1, 0, fb); }
    c1 += 64;
  }
}
__device__ __forceinline__ void produce_lin(uint32_t base, int it, int end, const unsigned char* src, uint32_t bytes, uint32_t tn) {
#pragma unroll 1
  for (; it < end; it++) {
    const uint32_t fb = base + OFF_BAR + (it & 7) * 8;
    mbar_wait(fb + B_EMPTY, (it >> 3) & 1);
    if (T0) { while ((int)(clock() - tn) < 0); tn += TP; }
    if (elect()) { mbar_expect_tx(fb, bytes); bulk_g2s(base + (it & 7) * SLOT + (bytes & 2048) * 4, src, bytes, fb); }
    src += bytes;
  }
}

__device__ __forceinline__ void retile_wo(const unsigned char* wo, unsigned char* scr, int u, int lane) {
  const int r8 = lane & 7, mi = lane >> 3;
  const unsigned char* src = wo + ((u >> 1) * 8 + r8) * 896 + ((u & 1) * 28 + mi) * 16;
  unsigned char* dst = scr + ((u & 1) * 2 * HU_T + 60 + (u >> 4)) * BT + ((u >> 1) & 7) * 1792 + mi * 128 + r8 * 16;
  uint4 v[7];
#pragma unroll
  for (int i = 0; i < 7; i++) v[i] = ldg128(src + i * 64);
#pragma unroll
  for (int i = 0; i < 7; i++) stg128(dst + i * 512 + ((i * 4 + mi) / 14) * (HU_T * BT - 1792), v[i].x, v[i].y, v[i].z, v[i].w);
  publish(scr, C_WO);
}

struct Params {
  const unsigned char *wo, *w1, *b1, *w2, *b2;
  unsigned char *out, *scr;
};

__global__ void __launch_bounds__(NTHREADS, 1)
fused_kernel(const __grid_constant__ CUtensorMap m_x, const __grid_constant__ CUtensorMap m_wkv, const __grid_constant__ CUtensorMap m_wq,
             const __grid_constant__ CUtensorMap m_w1, const __grid_constant__ CUtensorMap m_w2, const __grid_constant__ CUtensorMap m_res, const Params p) {
  extern __shared__ __align__(1024) unsigned char smem_raw[];
  constexpr uint32_t base = 1024, bars = base + OFF_BAR;
  const int tid = threadIdx.x, lane = tid & 31, b = blockIdx.x;
  const int rb = (b >> 2) & 15, hp = ((b >> 6) << 2) | (b & 3);
  const int wcol = hp * 56 - (hp & 1) * 8;
  auto load_kv = [&](int s) { mbar_expect_tx(bars + B_KV + s * 8, 16384); tma3d(base + s * 16384, &m_wkv, wcol, s * 64, 1, bars + B_KV + s * 8); };
  if (tid < 32) {
    if (elect()) {
#pragma unroll
      for (int i = 0; i < 7; i++) mbar_init(bars + B_X + i * 8, 1);
      asm volatile("fence.mbarrier_init.release.cluster;" ::: "memory");
#pragma unroll
      for (int i = 0; i < 7; i++) { mbar_expect_tx(bars + B_X + i * 8, 16384); tma3d(base + OFF_X + i * 16384, &m_x, i * 64, rb * 128, 0, bars + B_X + i * 8); }
#pragma unroll
      for (int i = 0; i < 7; i++) mbar_init(bars + B_KV + i * 8, 1);
      asm volatile("fence.mbarrier_init.release.cluster;" ::: "memory");
#pragma unroll 1
      for (int i = 0; i < NW0; i++) load_kv(i);
    }
  }
  const int warp = __shfl_sync(0xffffffffu, tid >> 5, 0);
  if (warp == 1) {
    if (elect()) {
#pragma unroll
      for (int i = 0; i < 16; i++) mbar_init(bars + i * 8, 2);
#pragma unroll
      for (int i = 0; i < 7; i++) mbar_init(bars + B_WQ + i * 8, 1);
      asm volatile("fence.mbarrier_init.release.cluster;" ::: "memory");
      sts32(bars + B_T0, __uint_as_float(clock()));
      if (smem_u32(smem_raw) != base) asm volatile("trap;");
    }
  }
  const int dt = b & 3, mt = b >> 2;
  const bool g1 = (b & 15) < 14;
  const int a1 = b - 2 * (b >> 4), ft = a1 >> 2, d1 = a1 & 3;
  const int g = lane >> 2, t = lane & 3, r8 = lane & 7, mi = lane >> 3;
  OBSG(FREQ && tid == 160, 128, 160);
  __syncthreads();
  if (warp >= 8) {
    asm volatile("setmaxnreg.dec.sync.aligned.u32 40;");
    const int pw = warp - 8;
    unsigned char* scr = p.scr;
    if (NW0 < 7 && pw == 3) {
      mbar_wait(bars + B_X, 0);
      if (elect()) {
#pragma unroll 1
        for (int i = NW0; i < 7; i++) load_kv(i);
      }
      __syncwarp();
    }
    {
      const int c0 = pw * 14 + (mi >> 1);
      unsigned char* dst = scr + (pw * HU_T + rb * 2 + (hp >> 2)) * BT + ((hp & 3) * 2 + (mi & 1)) * 1792 + (mi >> 1) * 128 + r8 * 16;
      const uint32_t xs = base + OFF_X + (hp * 16 + (lane & 15)) * 128;
      uint4 H[7];
      named_sync(9, 160);
#pragma unroll
      for (int i = 0; i < 7; i++) H[i] = lds128(xs + ((c0 + 2 * i) >> 3) * 16384 + ((((c0 + 2 * i) & 7) ^ r8) << 4));
      asm volatile("" :: "r"(H[6].w), "r"(H[0].x) : "memory");
      if (pw != 3) named_arrive(8, 384);
      else {
        named_sync(8, 384);
        if (elect()) {
          mbar_expect_tx(bars + B_WQ, 57344);
          tma3d(base + OFF_WQ, &m_wq, wcol, 0, 0, bars + B_WQ); tma3d(base + OFF_WQ + 28672, &m_wq, wcol, 224, 0, bars + B_WQ);
        }
        __syncwarp();
      }
      const uint2 st = lds64(base + OFF_LN + (lane & 15) * 8);
      const float sum = __uint_as_float(st.x), mean = sum * (1.0f / D_), var = ln_var(mean, __uint_as_float(st.y));
      const float m = rbf(mean), r = ln_rstd(var), r2 = ln_rstd(var * r * r);
      const float nc = fmaf(m, (float)D_, -sum) * (1.0f / D_) * (r * r2);
      const uint32_t m2 = pack2(m, m), r2x = pack2(r * r2, r * r2), nc2 = pack2(nc, nc);
      auto f = [&](uint32_t v) { return hfma2(hsub2(v, m2), r2x, nc2); };
#pragma unroll
      for (int i = 0; i < 7; i++) stg128(dst + i * 256, f(H[i].x), f(H[i].y), f(H[i].z), f(H[i].w));
      if (pw != 1) named_arrive(4, 128);
      else { named_sync(4, 128); publish(scr, C_H + (b & 3)); }
      OBS(tid == 288, 4);
    }
    const int it0 = g1 ? 32 : 0;
    const int lane = lane_id();
    if (pw == 0) {
      if (elect()) {
        asm volatile("prefetch.tensormap [%0];" :: "l"(&m_w1) : "memory");
        asm volatile("prefetch.tensormap [%0];" :: "l"(&m_w2) : "memory");
        asm volatile("prefetch.tensormap [%0];" :: "l"(&m_res) : "memory");
      }
      const uint32_t tn = lds64(bars + B_T0).x + T0;
      if (g1) produce_box(base, 0, 32, &m_w1, ft * 64, tn);
      mbar_wait(bars + B_ATT, 0);
      if (elect()) { mbar_expect_tx(bars + B_RES, BT); tma3d(base + OFF_Q, &m_res, dt * 112, mt * 64, 0, bars + B_RES); }
      spin_ge(scr, C_WO, 112);
      produce_lin(base, it0, it0 + 7, scr + (dt * HU_T + 60) * BT, BT, tn - 100000);
      produce_box(base, it0 + 7, it0 + 35, &m_w2, mt * 64, tn - 100000);
    } else if (pw == 1) {
      const uint32_t tn = lds64(bars + B_T0).x + T0;
      if (g1) {
        spin_ge(scr, C_H + (lane & 3), 32);
        OBS(lane == 0, 16);
        produce_lin(base, 0, 32, scr + d1 * HU_T * BT, BT, tn);
      }
      spin_ge(scr, C_O + (mt >> 1), 8);
      OBS(lane == 0, 17);
      produce_lin(base, it0, it0 + 7, scr + O_OFF + mt * 57344, 8192, tn - 100000);
      const unsigned char* us = scr + (dt * HU_T + 32) * BT;
      asm volatile("" : "+l"(us));
      spin_ge(scr, C_U + dt, 28);
      OBS(lane == 0, 18);
      produce_lin(base, it0 + 7, it0 + 35, us, BT, tn - 100000);
      unsigned tk = 0;
      if (lane == 0) tk = atomicAdd((unsigned*)(scr + CNT_OFF + C_TK * 128), 1u);
      if (__shfl_sync(0xffffffffu, tk, 0) == 127) {
#pragma unroll 1
        for (int i = lane; i < 160; i += 32) *(unsigned*)(scr + CNT_OFF + i * 128) = 0;
      }
    } else if (pw == 2) {
      uint32_t tn = clock() + PACE0;
      const unsigned char* src = p.w1 + b * 4096 + lane * 128;
#pragma unroll 1
      for (int i = 0; i < 28 + FREQ * 2; i++) {
        while ((int)(clock() - tn) < 0) __nanosleep(20);
        if (i == 14) src = p.w2 + b * 4096 + lane * 128;
        if (i < 28) asm volatile("prefetch.global.L2 [%0];" :: "l"(src) : "memory");
        OBSG(FREQ && lane == 0, 129 + i, 161 + i);
        src += 128 * 4096;
        tn += i < 14 ? PACE1 : PACE2;
      }
    } else {
      if (!WOP && b < 112) retile_wo(p.wo, scr, b, lane_id());
      const int lane = lane_id();
      unsigned char* hg = scr + HALO_OFF + (rb * 8 + hp) * 3584 + lane * 16;
      named_sync(1, 64);
      if (rb < 15) {
        uint4 v[7];
#pragma unroll
        for (int i = 0; i < 7; i++) v[i] = lds128(base + OFF_K + 8 * 3584 + i * 512 + lane * 16);
#pragma unroll
        for (int i = 0; i < 7; i++) stg128(hg + i * 512, v[i].x, v[i].y, v[i].z, v[i].w);
        publish(scr, C_HALO + rb * 8 + hp);
      }
      OBS(lane == 0, 29);
      if (rb > 0) {
        spin_ge(scr, C_HALO + (rb - 1) * 8 + hp, 1);
        OBS(lane == 0, 12);
        if (elect()) { mbar_expect_tx(bars + B_HALO, 3584); bulk_g2s(base + OFF_K, scr + HALO_OFF + ((rb - 1) * 8 + hp) * 3584, 3584, bars + B_HALO); }
      } else {
#pragma unroll
        for (int i = 0; i < 7; i++) sts128(base + OFF_K + i * 512 + lane * 16, 0, 0, 0, 0);
        smem_fence();
        __syncwarp();
        if (lane == 0) mbar_arrive(bars + B_HALO);
      }
    }
  } else {
    asm volatile("setmaxnreg.inc.sync.aligned.u32 232;");
    const int wg = warp >> 2, w4 = warp & 3, th = wg ^ 1;
    const bool rel = (tid & 127) < 2;
    unsigned char* scr = p.scr;
    uint32_t X[28][4];
    float aq[28];
    const uint32_t dlo = (base >> 4) + (512u << 16) + (hp & 1), dlq = dlo + (OFF_WQ >> 4);
    {
      uint32_t xa[4];
#pragma unroll
      for (int k = 0; k < 4; k++) xa[k] = base + OFF_X + (th * 64 + w4 * 16 + (mi >> 1) * 8 + r8) * 128 + (((2 * k + (mi & 1)) ^ r8) << 4);
      float c0[2][4] = {}, c1[2][4] = {};
      uint32_t one[8];
#pragma unroll
      for (int j = 0; j < 8; j++) asm volatile("{\n.reg .u32 y;\nmov.u32 y, %%tid.y;\nmad.lo.u32 %0, y, %1, 0x3f803f80;\n}" : "=r"(one[j]) : "r"(lane + j));
      asm volatile("" : "+l"(scr));
      uint32_t ok = 0;
      if (HEAT) {
#pragma unroll 1
        for (int n = 0; n < 64 && !ok; n++) { mma16816(c0[0], 0, 0, 0, 0, 0, 0); ok = mbar_try(bars + B_X, 0); }
      }
#pragma unroll
      for (int i = 0; i < 8; i++) {
        if (i < 7) {
          if (!ok) mbar_wait(bars + B_X + i * 8, 0);
          OBS(tid == 64 && i == 0, 0); OBS(tid == 64 && i == 6, 15);
#pragma unroll
          for (int k = 0; k < 4; k++) ldsm4(X[i * 4 + k], xa[k] + i * 16384);
          if (i < 6) ok = mbar_try(bars + B_X + i * 8 + 8, 0);
        }
        if (i > 0) {
#pragma unroll
          for (int k = i * 4 - 4; k < i * 4; k++) {
            mma16816(c0[k & 1], X[k][0], one[(k & 1) * 4], X[k][1], one[(k & 1) * 4 + 1], X[k][0], X[k][1]);
            mma16816(c1[k & 1], X[k][2], one[(k & 1) * 4 + 2], X[k][3], one[(k & 1) * 4 + 3], X[k][2], X[k][3]);
          }
        }
      }
      float st[4];
#pragma unroll
      for (int j = 0; j < 2; j++) {
        st[j] = __shfl_sync(0xffffffffu, (g & 1) ? c0[0][2 * j + 1] + c0[1][2 * j + 1] : c0[0][2 * j] + c0[1][2 * j], (lane & 28) | (g >> 1));
        st[2 + j] = __shfl_sync(0xffffffffu, (g & 1) ? c1[0][2 * j + 1] + c1[1][2 * j + 1] : c1[0][2 * j] + c1[1][2 * j], (lane & 28) | (g >> 1));
      }
      named_arrive(8, 384);
      asm volatile("{\n.reg .pred q;\nsetp.ne.u32 q, %3, 0;\n@q st.shared.v2.f32 [%0], {%1,%2};\n@q bar.arrive 9, 160;\n}"
                   :: "r"(base + OFF_LN + ((t & 1) * 8 + g) * 8), "f"((t & 1) ? st[3] : st[1]), "f"((t & 1) ? st[2] : st[0]), "r"((uint32_t)((warp ^ 4) == hp)) : "memory");
      ok = mbar_try(bars + B_KV, 0);
      LnC l0, l1;
      float eps = 1e-5f;
#pragma unroll 1
      do {
        l0 = ln_consts(st[1], st[0], eps); l1 = ln_consts(st[3], st[2], eps);
#pragma unroll
        for (int k = 0; k < PRE * 16; k++) X[k >> 2][k & 3] = hsub2(X[k >> 2][k & 3], k & 2 ? l1.m : l0.m);
        eps += eps;
      } while ((l0.rl ^ l1.rl) == 4);
      OBS(tid == 32, 1);
      float ak[60], *av = ak + 32;
      const int pp_in = wg ? 6 : 0, pp_out = wg ? 0 : 6;
#pragma unroll
      for (int s = 0; s < 7; s++) {
#pragma unroll
        for (int k = s * 4; k < s * 4 + 4; k++) {
          if (s < PRE) {
            auto f = [&](uint32_t d, const LnC& l) { return hfma2(d, l.rh, hmul2(d, l.rl)); };
            const uint32_t y = f(X[k][1], l0);
            X[k][0] = f(X[k][0], l0); X[k][1] = f(X[k][2], l1); X[k][2] = y; X[k][3] = f(X[k][3], l1);
          } else {
            const uint32_t y = ln_apply(X[k][1], l0);
            X[k][0] = ln_apply(X[k][0], l0); X[k][1] = ln_apply(X[k][2], l1); X[k][2] = y; X[k][3] = ln_apply(X[k][3], l1);
          }
        }
        if (__builtin_expect(!ok, 0)) { mbar_wait(bars + B_KV + s * 8, 0); if (s == 6) mbar_wait(bars + B_WQ, 0); }
        if (s == 0) fresh(ak);
        if (s == 6) { wg_wait<0>(); if ((tid & 127) == 0) mbar_arrive(bars + B_EMPTY + 3 * 8); }
        OBS(KOBS && (tid & 127) == 0, 40 + wg * 32 + s);
        if (wg || s) named_sync(pp_in, 256);
        OBS(KOBS && (tid & 127) == 32, 48 + wg * 32 + s);
        OBS(tid == 64 && s == 0, 2);
        wg_fence();
#pragma unroll
        for (int k = 0; k < 4; k++) {
          if (s < 6 && k == PPE) named_arrive(pp_out, 256);
          wgmma_rs_n120<1>(ak, X[s * 4 + k], mkdesc(HI_SW128, dlo + s * 1024 + k * 128), (s | k) != 0);
        }
        wg_commit();
        if (s == 6) {
          fresh(aq);
#pragma unroll
          for (int k = 0; k < 4 * QA; k++) {
            if (k == 4 * QA - PQE) named_arrive(pp_out, 256);
            wgmma_rs_n56<1>(aq, X[k], mkdesc(HI_SW128, dlq + k * 128), k);
          }
          wg_commit();
        }
        if (s < 6 ? PPE == 4 : PQE == 0) named_arrive(pp_out, 256);
        fence_code(s);
        OBS(KOBS && (tid & 127) == 64, 56 + wg * 32 + s);
        if (s < 6) ok = mbar_try(bars + B_KV + s * 8 + 8, 0);
        if (s == 5) ok &= mbar_try(bars + B_WQ, 0);
        OBS(tid == 64 && s == 1, 28); OBS(tid == 64 && s == 5, 31);
        if (s > 0) wg_wait<1>();
        OBS(KOBS && (tid & 127) == 96, 64 + wg * 32 + s);
        if ((s == 2 || s == 3 || s == 5) && (tid & 127) == 0) mbar_arrive(bars + B_EMPTY + (s == 5 ? 2 : s - 2) * 8);
      }
      if ((tid & 127) == 0) mbar_arrive(bars + B_EMPTY + 4 * 8);
      OBS(tid == 32, 3);
      {
        const uint32_t kst = base + OFF_K + (2 + (warp ^ 4) * 2 + (mi & 1)) * 1792 + (mi >> 1) * 896 + r8 * 16;
#pragma unroll
        for (int n = 0; n < 7; n++)
          stsm4(kst + n * 128, pack2(ak[n * 4], ak[n * 4 + 1]), pack2(ak[n * 4 + 2], ak[n * 4 + 3]), pack2(av[n * 4], av[n * 4 + 1]), pack2(av[n * 4 + 2], av[n * 4 + 3]));
        named_arrive_if(warp == 3, 1, 64);
      }
      OBS(tid == 96, 32); OBS(tid == 224, 34);
      wg_wait<0>();
      if ((tid & 127) == 0) mbar_arrive(bars + B_EMPTY + 5 * 8);
    }
    const unsigned short *bp1 = (const unsigned short*)p.b1 + (g1 ? ft * 64 : 0) + w4 * 16 + g, *bp2 = (const unsigned short*)p.b2 + mt * 64 + w4 * 16 + g;
    const uint32_t braw[4] = {__ldg(bp1), __ldg(bp1 + 8), __ldg(bp2), __ldg(bp2 + 8)};
    auto q_rest = [&]() {
      wg_fence();
#pragma unroll
      for (int s = QA; s < 7; s++) {
#pragma unroll
        for (int k = s * 4; k < s * 4 + 4; k++) wgmma_rs_n56<1>(aq, X[k], mkdesc(HI_SW128, dlq + k * 128), 1);
        wg_commit();
        if (s == 5) { wg_wait<2>(); if ((tid & 127) == 0) mbar_arrive(bars + B_EMPTY + 6 * 8); }
      }
    };
    uint32_t Q[4][4];
    auto q_pack = [&]() {
#pragma unroll
      for (int n = 0; n < 14; n++) { const int m = n + 2 * (n > 7); Q[m >> 2][m & 3] = pack2(aq[n * 2], aq[n * 2 + 1]); }
#pragma unroll
      for (int h = 0; h < 2; h++) { Q[2][h] = t < 2 ? 0u : Q[1][2 + h]; Q[1][2 + h] = t < 2 ? Q[1][2 + h] : 0u; }
    };
    float acc[56];
    auto ai = [](int p) { return p < 4 ? 48 + (p & 1) * 4 + (p & 2) : (p - 4) * 4; };
    uint32_t xch, ts, tl;
    unsigned char *ug, *uc, *outp, *outq;
    auto setup_u = [&]() {
      xch = pin(base + OFF_K + (tid & 127) * 16);
      ug = pin(scr + (d1 * HU_T + 32 + ft) * BT + w4 * 3584 + lane * 4 + wg * 1792);
      uc = pin(scr + d1 * 128);
    };
    auto setup_out = [&]() {
      const uint32_t tb = base + OFF_K + 6144 + warp * 2560;
      ts = pin(tb + mi * 160 + r8 * 16); tl = pin(tb + t * 160 + g * 16);
      unsigned char* o = p.out + (mt * 64 + w4 * 16 + g) * 896 + dt * 224;
      outp = pin(o + th * 7168 + t * 16); outq = pin(o + (t >> 1) * 7168 + 192 + (t & 1) * 16);
    };
    auto give = [&](const float (&a)[56], int id) {
#pragma unroll
      for (int i = 0; i < 48; i += 16) sts128(xch + i * 128, pack2(a[i + 2], a[i + 3]), pack2(a[i + 6], a[i + 7]), pack2(a[i + 10], a[i + 11]), pack2(a[i + 14], a[i + 15]));
      named_arrive(id, 256);
    };
    auto take = [&](uint32_t (&r)[12], int id) {
      named_sync(id, 256);
#pragma unroll
      for (int i = 0; i < 3; i++) { const uint4 v = lds128(xch + i * 2048); r[i * 4] = v.x; r[i * 4 + 1] = v.y; r[i * 4 + 2] = v.z; r[i * 4 + 3] = v.w; }
    };
    float hv[32];
    auto keep_h = [&](int i) {
      const float hb0 = 0.5f * bf_lo(braw[i]), hb1 = 0.5f * bf_lo(braw[i + 1]);
#pragma unroll
      for (int j = 0; j < 32; j++) hv[j] = fmaf(acc[ai(j >> 1) + (j & 1)], 0.5f, j >= 4 && j < 8 ? hb1 : hb0);
    };
    auto take_h = [&](int i) {
      const float hb1 = 0.5f * bf_lo(braw[i + 1]);
      uint32_t r[12];
      take(r, 5);
#pragma unroll
      for (int j = 0; j < 12; j++) { hv[8 + 2 * j] = fmaf(bf_lo(r[j]), 0.5f, hb1); hv[9 + 2 * j] = fmaf(bf_hi(r[j]), 0.5f, hb1); }
    };
    uint4 Xr[4];
    auto get_x = [&]() {
      const uint32_t xr = base + OFF_Q + (w4 * 16 + g) * 224;
      mbar_wait(bars + B_RES, 0);
      Xr[0] = lds128(xr + (t >> 1) * 1792 + 192 + (t & 1) * 16);
#pragma unroll
      for (int i = 1; i < 4; i++) Xr[i] = lds128(xr + th * 1792 + t * 16 + (i - 1) * 64);
    };
    auto gelu = [&](int j) {
      const float h0 = hv[2 * j], h1 = hv[2 * j + 1];
      const float t0 = tanh_fast(h0 * fmaf(h0 * h0, 0.2854192648f, 1.5957691216f)), t1 = tanh_fast(h1 * fmaf(h1 * h1, 0.2854192648f, 1.5957691216f));
      stg32(ug + (ai(j) & 2) * 896 + (ai(j) >> 2) * 128, pack2(fmaf(h0, t0, h0), fmaf(h1, t1, h1)));
    };
    if (wg == 0) {
      named_sync(0, 256);
      OBS(tid == 96, 14);
      q_rest();
      named_arrive(6, 256);
      wg_wait<0>();
      if (tid == 0) mbar_arrive(bars + B_EMPTY + 7 * 8);
      q_pack();
      const uint32_t qst = base + OFF_Q + 8192 + (mi >> 1) * 1024 + (w4 * 16 + (mi & 1) * 8 + r8) * 16;
#pragma unroll
      for (int n = 0; n < 4; n++) stsm4(qst + n * 2048, Q[n][0], Q[n][1], Q[n][2], Q[n][3]);
      smem_fence();
      named_arrive(7, 256);
      OBS(tid == 32, 5);
      fresh(acc);
      setup_u();
      if (g1) {
        mbar_wait(bars, 0); mbar_wait(bars + 8, 0);
        named_sync(0, 256);
        gemm_issue<1>(acc, base >> 4, 0);
        OBS(tid == 0, 20);
        gemm_loop<1>(acc, base, 1, 32, rel, 40, 1, tid == 32 ? J1 : tid == 64 ? J2 : tid == 96 ? J3 : -1, bars + B_GATE - 8 + w4 * 8);
        wg_wait<0>();
        OBS(tid == 0, 21);
        give(acc, 5);
        mbar_arrive_if(rel, bars + B_EMPTY + 7 * 8);
        fence_code(30);
        keep_h(0);
#pragma unroll
        for (int j = 0; j < 4; j++) gelu(j);
      } else {
        if (lane == 0 && w4) mbar_arrive(bars + B_GATE - 8 + w4 * 8);
      }
      if (!g1 && WOP) {
        if (WOP == 2) mbar_wait(bars + B_ATT, 0);
#pragma unroll 1
        for (int n = w4; n < 7; n += 4) retile_wo(p.wo, scr, ((b >> 4) * 2 + (b & 1)) * 7 + n, lane);
      }
    } else {
      const uint32_t dq = ((base + OFF_Q) >> 4) + (64u << 16), dk = (base + OFF_K) >> 4;
      const bool odd = g & 1, early = 2 * t + (g & 1) > g;
      uint32_t selA[5], selB[4];
#pragma unroll
      for (int j = 0; j < 5; j++) selA[j] = j == w4 + (early ? 0 : 1) ? (odd ? 0x1044u : 0x4410u) : 0x4444u;
#pragma unroll
      for (int j = 0; j < 4; j++) selB[j] = j == w4 ? (odd ? 0x3244u : 0x4432u) : 0x4444u;
      float Sc[2][40], Op[2][2][16];
      uint32_t A[2][5][4];
      auto scores = [&](int T) {
        fresh(Sc[0]); fresh(Sc[1]);
#pragma unroll
        for (int k = 0; k < 2; k++) {
#pragma unroll
          for (int hh = 0; hh < 2; hh++)
            if (T) wgmma_n80<0, 0>(Sc[hh], mkdesc(8, dq + 512 + hh * 256 + k * 128), mkdesc(112, dk + (8u << 16) + 896 + hh * 24 + k * 16), k);
            else wgmma_rs_n80<0>(Sc[hh], Q[hh * 2 + k], mkdesc(112, dk + (8u << 16) + hh * 24 + k * 16), k);
        }
      };
      auto softmax = [&](int T) {
#pragma unroll
        for (int hh = 0; hh < 2; hh++) {
          uint32_t pp[2];
#pragma unroll
          for (int h = 0; h < 2; h++) {
            float c[3];
#pragma unroll
            for (int n = 0; n < 3; n++) {
              const float* q = Sc[hh] + (h + n) * 4 + 2 * h;
              asm("{\n.reg .pred p, a, b, c;\nsetp.ne.u32 p, %9, 0;\nsetp.eq.u32 a, %10, 1;\nsetp.eq.u32 b, %10, 2;\nsetp.eq.u32 c, %10, 3;\n"
                  "selp.f32 %0, %2, %1, p;\n@a selp.f32 %0, %4, %3, p;\n@b selp.f32 %0, %6, %5, p;\n@c selp.f32 %0, %8, %7, p;\n}"
                  : "=&f"(c[n]) : "f"(q[0]), "f"(q[1]), "f"(q[8]), "f"(q[9]), "f"(q[16]), "f"(q[17]), "f"(q[24]), "f"(q[25]), "r"((uint32_t)odd), "r"((tid >> 5) & 3));
            }
            uint32_t pk = pack2(early ? c[0] : c[2], c[1]);
            pk = pack2(bf_lo(pk) * SCALE, bf_hi(pk) * SCALE);
            float l0 = bf_lo(pk), l1 = bf_hi(pk);
            if (T == 0 && w4 == 0 && rb == 0) { if (early) l0 = -1e9f; if (h == 0) l1 = -1e9f; }
            float mx = fmaxf(l0, l1);
            mx = fmaxf(mx, __shfl_xor_sync(0xffffffffu, mx, 1));
            mx = fmaxf(mx, __shfl_xor_sync(0xffffffffu, mx, 2));
            float p0 = ex2_fast((l0 - mx) * LOG2E), p1 = ex2_fast((l1 - mx) * LOG2E);
            float sm = p0 + p1;
            sm += __shfl_xor_sync(0xffffffffu, sm, 1);
            sm += __shfl_xor_sync(0xffffffffu, sm, 2);
            const float inv = rcp_fast(sm);
            pp[h] = pack2(p0 * inv, p1 * inv);
          }
#pragma unroll
          for (int j = 0; j < 5; j++) {
            A[hh][j][0] = __byte_perm(pp[0], 0, selA[j]); A[hh][j][1] = j ? __byte_perm(pp[1], 0, selB[j ? j - 1 : 0]) : 0u;
            A[hh][j][2] = j < 4 ? __byte_perm(pp[0], 0, selB[j & 3]) : 0u; A[hh][j][3] = __byte_perm(pp[1], 0, selA[j]);
          }
        }
      };
      auto values = [&](int T) {
        fresh(Op[T][0]); fresh(Op[T][1]);
#pragma unroll
        for (int j = 0; j < 5; j++)
#pragma unroll
          for (int hh = 0; hh < 2; hh++) {
            wgmma_rs_n32<1>(Op[T][hh], A[hh][j], mkdesc(8, dk + (112u << 16) + 56 + T * 896 + hh * 24 + j * 224), j);
          }
        wg_commit();
      };
      uint32_t Ob[2][14];
      auto pack = [&](int T) {
        const float (&O)[2][16] = Op[T];
#pragma unroll
        for (int n = 0; n < 7; n++)
#pragma unroll
          for (int h = 0; h < 2; h++) {
            if (n < 3) Ob[T][n * 2 + h] = pack2(O[0][n * 4 + 2 * h], O[0][n * 4 + 2 * h + 1]);
            else if (n == 3) Ob[T][n * 2 + h] = pack2(t < 2 ? O[0][12 + 2 * h] : O[1][2 * h], t < 2 ? O[0][13 + 2 * h] : O[1][2 * h + 1]);
            else Ob[T][n * 2 + h] = pack2(O[1][(n - 3) * 4 + 2 * h], O[1][(n - 3) * 4 + 2 * h + 1]);
          }
      };
      smem_fence();
      named_sync(6, 256);
      OBS(tid == 224, 26);
      q_rest();
      named_sync(7, 256);
      wg_fence();
      scores(1);
      wg_commit();
      named_arrive_if(g1, 0, 256);
      wg_wait<2>();
      if (tid == 128) mbar_arrive(bars + B_EMPTY + 7 * 8);
      wg_wait<0>();
      q_pack();
      OBS(tid == 160, 10);
      softmax(1);
      OBS(tid == 160, 30);
      mbar_wait(bars + B_HALO, 0);
      OBS(tid == 160, 7);
      mbar_wait(bars + B_GATE, 0);
      wg_fence();
      scores(0);
      values(1);
      wg_wait<0>();
      OBS(tid == 160, 33);
      unsigned char* og = scr + O_OFF + rb * 2 * 57344 + hp * 7168 + w4 * 256 + lane * 4;
      auto put = [&](int T) {
#pragma unroll
        for (int n = 0; n < 14; n++) { stg32(og + T * 57344 + (n >> 1) * 1024 + (n & 1) * 128, Ob[T][n]); if (OSLEEP && n % OGRP == OGRP - 1) __nanosleep(OSLEEP); }
      };
      if (OMODE == 1) { pack(1); put(1); }
      softmax(0);
      if (OMODE == 2) { pack(1); put(1); }
      mbar_wait(bars + B_GATE + 8, 0);
      wg_fence();
      values(0);
      if (OMODE == 3) { pack(1); put(1); }
      wg_wait<0>();
      OBS(tid == 160, 35);
      named_sync(11, 128);
      if (tid == 160) mbar_arrive(bars + B_ATT);
      if (OMODE == 0) pack(1);
      pack(0);
      if (J3 > J2) mbar_wait(bars + B_GATE + 16, 0);
      if (OMODE == 0) put(1);
      put(0);
      named_sync(11, 128);
      if (warp == 4) publish(scr, C_O + rb);
      OBS(tid == 160, 8);
      setup_u(); setup_out();
      if (g1) take_h(0);
    }
    if (g1) {
#pragma unroll
      for (int j = 4; j < 16; j++) { gelu(j); if (GCH && j < 15 && (j - 3) % GCH == 0) fence_code(8 + j); }
      if (warp == 0) { named_sync(2, 256); publish(uc, C_U); OBS(tid == 0, 9); }
      else if (OPW && wg) named_sync(2, 256);
      else named_arrive(2, 256);
    }
    uint32_t Sv[16];
    auto gate = [&](int i) {
      uint32_t R[4];
#pragma unroll
      for (int q = 0; q < 4; q++) {
        const int j = i * 4 + q;
        const float h0 = hv[2 * j], h1 = hv[2 * j + 1];
        R[q] = hmul2(Sv[j], pack2(fmaf(h0, tanh_fast(h0), h0), fmaf(h1, tanh_fast(h1), h1)));
      }
      stsm4(ts + i * 640, R[0], R[1], R[2], R[3]);
    };
    auto leave = [&](int i) {
      __syncwarp();
      const uint4 v = lds128(tl + i * 640), x = Xr[i];
      stg128(i ? outp + (i - 1) * 64 : outq, hadd2(x.x, v.x), hadd2(x.y, v.y), hadd2(x.z, v.z), hadd2(x.w, v.w));
    };
    if (wg == 1) {
      float as[56];
      fresh(as);
      gemm_stage<0>(as, base, 0, 0);
      OBS(tid == 128, 22);
      gemm_loop<0>(as, base, 1, 7, rel, 104);
      wg_wait<0>();
      OBS(tid == 128, 23);
      if (rel) mbar_arrive(bars + B_EMPTY + 6 * 8);
      fresh(acc);
      if (SEARLY) { give(as, 3); get_x(); }
      gemm_stage<1>(acc, base, 7, 0);
      OBS(tid == 128, 24);
      if (!SEARLY) { give(as, 3); get_x(); }
#pragma unroll
      for (int j = 0; j < 16; j++) Sv[j] = pack2(as[ai(j)], as[ai(j) + 1]);
      gemm_loop<1>(acc, base, 8, 35, rel, 65);
      named_sync(10, 256);
      wg_wait<0>();
      OBS(tid == 128, 25);
      give(acc, 5);
      fence_code(31);
      keep_h(2);
      gate(0); leave(0);
    } else {
      setup_out();
      get_x();
      uint32_t r[12];
      take(r, 3);
#pragma unroll
      for (int j = 0; j < 16; j++) Sv[j] = r[j < 4 ? 0 : j - 4];
      asm volatile("" :: "r"(r[0]), "r"(r[11]) : "memory");
      named_arrive(10, 256);
      take_h(2);
    }
    {
#pragma unroll
      for (int i = 1; i < 4; i++) { gate(i); leave(i); }
      OBS(tid == 128, 27);
    }
  }
}

typedef CUresult (*EncFn)(CUtensorMap*, CUtensorMapDataType, cuuint32_t, void*, const cuuint64_t*, const cuuint64_t*, const cuuint32_t*,
                          const cuuint32_t*, CUtensorMapInterleave, CUtensorMapSwizzle, CUtensorMapL2promotion, CUtensorMapFloatOOBfill);
void enc(EncFn f, CUtensorMap* m, const void* ptr, cuuint64_t d0, cuuint64_t d1, cuuint64_t d2, cuuint64_t s1, cuuint64_t s2, cuuint32_t b1, cuuint32_t b2, cuuint32_t b0 = 64) {
  const cuuint64_t gd[3] = {d0, d1, d2}, gs[2] = {s1 * 2, s2 * 2};
  const cuuint32_t bx[3] = {b0, b1, b2}, es[3] = {1, 1, 1};
  f(m, CU_TENSOR_MAP_DATA_TYPE_BFLOAT16, 3, (void*)ptr, gd, gs, bx, es, CU_TENSOR_MAP_INTERLEAVE_NONE, b0 == 64 ? CU_TENSOR_MAP_SWIZZLE_128B : CU_TENSOR_MAP_SWIZZLE_NONE,
    CU_TENSOR_MAP_L2_PROMOTION_L2_128B, CU_TENSOR_MAP_FLOAT_OOB_FILL_NONE);
}
}

extern "C" void kernel_launch(void* const* d_in, const int* in_sizes, int n_in, void* d_out, int out_size) {
  (void)in_sizes; (void)n_in; (void)out_size;
  void* fp = nullptr;
  cudaDriverEntryPointQueryResult qr;
  cudaGetDriverEntryPoint("cuTensorMapEncodeTiled", &fp, cudaEnableDefault, &qr);
  EncFn f = (EncFn)fp;
  CUtensorMap m_x, m_wkv, m_wq, m_w1, m_w2, m_res;
  void* scr = nullptr;
  cudaGetSymbolAddress(&scr, g_scr);
  enc(f, &m_x, d_in[0], D_, S_, 1, D_, D_, 128, 1);
  enc(f, &m_wkv, d_in[1], D_, D_, 3, 3 * D_, D_, 64, 2);
  enc(f, &m_wq, d_in[1], D_, D_, 3, 3 * D_, D_, 224, 1);
  enc(f, &m_w1, d_in[4], F_, S_, 1, F_, F_, 64, 1);
  enc(f, &m_w2, d_in[6], S_, F_, 1, S_, S_, 64, 1);
  enc(f, &m_res, d_in[0], D_, S_, 1, D_, D_, 64, 1, 112);
  Params p;
  p.wo = (const unsigned char*)d_in[2];
  p.w1 = (const unsigned char*)d_in[4]; p.b1 = (const unsigned char*)d_in[5];
  p.w2 = (const unsigned char*)d_in[6]; p.b2 = (const unsigned char*)d_in[7];
  p.out = (unsigned char*)d_out; p.scr = (unsigned char*)scr;
  cudaFuncSetAttribute(fused_kernel, cudaFuncAttributeMaxDynamicSharedMemorySize, SMEM_BYTES);
  fused_kernel<<<128, NTHREADS, SMEM_BYTES, cudaStreamPerThread>>>(m_x, m_wkv, m_wq, m_w1, m_w2, m_res, p);
}
```

```cpp
#include <cuda_runtime.h>
#include <cuda.h>
#include <cuda_bf16.h>
#include <stdint.h>

template<int TA, int TB> __device__ __forceinline__ void wgmma_n112(float (&d)[56], uint64_t da, uint64_t db, int sc) {
  asm volatile("{\n.reg .pred p;\nsetp.ne.b32 p, %58, 0;\n"
    "wgmma.mma_async.sync.aligned.m64n112k16.f32.bf16.bf16 {%0, %1, %2, %3, %4, %5, %6, %7, %8, %9, %10, %11, %12, %13, %14, %15, %16, %17, %18, %19, %20, %21, %22, %23, %24, %25, %26, %27, %28, %29, %30, %31, %32, %33, %34, %35, %36, %37, %38, %39, %40, %41, %42, %43, %44, %45, %46, %47, %48, %49, %50, %51, %52, %53, %54, %55}, %56, %57, p, 1, 1, %59, %60;\n}\n"
    : "+f"(d[0]), "+f"(d[1]), "+f"(d[2]), "+f"(d[3]), "+f"(d[4]), "+f"(d[5]), "+f"(d[6]), "+f"(d[7]), "+f"(d[8]), "+f"(d[9]), "+f"(d[10]), "+f"(d[11]), "+f"(d[12]), "+f"(d[13]), "+f"(d[14]), "+f"(d[15]), "+f"(d[16]), "+f"(d[17]), "+f"(d[18]), "+f"(d[19]), "+f"(d[20]), "+f"(d[21]), "+f"(d[22]), "+f"(d[23]), "+f"(d[24]), "+f"(d[25]), "+f"(d[26]), "+f"(d[27]), "+f"(d[28]), "+f"(d[29]), "+f"(d[30]), "+f"(d[31]), "+f"(d[32]), "+f"(d[33]), "+f"(d[34]), "+f"(d[35]), "+f"(d[36]), "+f"(d[37]), "+f"(d[38]), "+f"(d[39]), "+f"(d[40]), "+f"(d[41]), "+f"(d[42]), "+f"(d[43]), "+f"(d[44]), "+f"(d[45]), "+f"(d[46]), "+f"(d[47]), "+f"(d[48]), "+f"(d[49]), "+f"(d[50]), "+f"(d[51]), "+f"(d[52]), "+f"(d[53]), "+f"(d[54]), "+f"(d[55])
    : "l"(da), "l"(db), "r"(sc), "n"(TA), "n"(TB));
}

template<int TA, int TB> __device__ __forceinline__ void wgmma_n80(float (&d)[40], uint64_t da, uint64_t db, int sc) {
  asm volatile("{\n.reg .pred p;\nsetp.ne.b32 p, %42, 0;\n"
    "wgmma.mma_async.sync.aligned.m64n80k16.f32.bf16.bf16 {%0, %1, %2, %3, %4, %5, %6, %7, %8, %9, %10, %11, %12, %13, %14, %15, %16, %17, %18, %19, %20, %21, %22, %23, %24, %25, %26, %27, %28, %29, %30, %31, %32, %33, %34, %35, %36, %37, %38, %39}, %40, %41, p, 1, 1, %43, %44;\n}\n"
    : "+f"(d[0]), "+f"(d[1]), "+f"(d[2]), "+f"(d[3]), "+f"(d[4]), "+f"(d[5]), "+f"(d[6]), "+f"(d[7]), "+f"(d[8]), "+f"(d[9]), "+f"(d[10]), "+f"(d[11]), "+f"(d[12]), "+f"(d[13]), "+f"(d[14]), "+f"(d[15]), "+f"(d[16]), "+f"(d[17]), "+f"(d[18]), "+f"(d[19]), "+f"(d[20]), "+f"(d[21]), "+f"(d[22]), "+f"(d[23]), "+f"(d[24]), "+f"(d[25]), "+f"(d[26]), "+f"(d[27]), "+f"(d[28]), "+f"(d[29]), "+f"(d[30]), "+f"(d[31]), "+f"(d[32]), "+f"(d[33]), "+f"(d[34]), "+f"(d[35]), "+f"(d[36]), "+f"(d[37]), "+f"(d[38]), "+f"(d[39])
    : "l"(da), "l"(db), "r"(sc), "n"(TA), "n"(TB));
}

template<int TB> __device__ __forceinline__ void wgmma_rs_n120(float (&d)[60], const uint32_t (&a)[4], uint64_t db, int sc) {
  asm volatile("{\n.reg .pred p;\nsetp.ne.b32 p, %65, 0;\n"
    "wgmma.mma_async.sync.aligned.m64n120k16.f32.bf16.bf16 {%0, %1, %2, %3, %4, %5, %6, %7, %8, %9, %10, %11, %12, %13, %14, %15, %16, %17, %18, %19, %20, %21, %22, %23, %24, %25, %26, %27, %28, %29, %30, %31, %32, %33, %34, %35, %36, %37, %38, %39, %40, %41, %42, %43, %44, %45, %46, %47, %48, %49, %50, %51, %52, %53, %54, %55, %56, %57, %58, %59}, {%60, %61, %62, %63}, %64, p, 1, 1, %66;\n}\n"
    : "+f"(d[0]), "+f"(d[1]), "+f"(d[2]), "+f"(d[3]), "+f"(d[4]), "+f"(d[5]), "+f"(d[6]), "+f"(d[7]), "+f"(d[8]), "+f"(d[9]), "+f"(d[10]), "+f"(d[11]), "+f"(d[12]), "+f"(d[13]), "+f"(d[14]), "+f"(d[15]), "+f"(d[16]), "+f"(d[17]), "+f"(d[18]), "+f"(d[19]), "+f"(d[20]), "+f"(d[21]), "+f"(d[22]), "+f"(d[23]), "+f"(d[24]), "+f"(d[25]), "+f"(d[26]), "+f"(d[27]), "+f"(d[28]), "+f"(d[29]), "+f"(d[30]), "+f"(d[31]), "+f"(d[32]), "+f"(d[33]), "+f"(d[34]), "+f"(d[35]), "+f"(d[36]), "+f"(d[37]), "+f"(d[38]), "+f"(d[39]), "+f"(d[40]), "+f"(d[41]), "+f"(d[42]), "+f"(d[43]), "+f"(d[44]), "+f"(d[45]), "+f"(d[46]), "+f"(d[47]), "+f"(d[48]), "+f"(d[49]), "+f"(d[50]), "+f"(d[51]), "+f"(d[52]), "+f"(d[53]), "+f"(d[54]), "+f"(d[55]), "+f"(d[56]), "+f"(d[57]), "+f"(d[58]), "+f"(d[59])
    : "r"(a[0]), "r"(a[1]), "r"(a[2]), "r"(a[3]), "l"(db), "r"(sc), "n"(TB));
}

template<int TB> __device__ __forceinline__ void wgmma_rs_n56(float (&d)[28], const uint32_t (&a)[4], uint64_t db, int sc) {
  asm volatile("{\n.reg .pred p;\nsetp.ne.b32 p, %33, 0;\n"
    "wgmma.mma_async.sync.aligned.m64n56k16.f32.bf16.bf16 {%0, %1, %2, %3, %4, %5, %6, %7, %8, %9, %10, %11, %12, %13, %14, %15, %16, %17, %18, %19, %20, %21, %22, %23, %24, %25, %26, %27}, {%28, %29, %30, %31}, %32, p, 1, 1, %34;\n}\n"
    : "+f"(d[0]), "+f"(d[1]), "+f"(d[2]), "+f"(d[3]), "+f"(d[4]), "+f"(d[5]), "+f"(d[6]), "+f"(d[7]), "+f"(d[8]), "+f"(d[9]), "+f"(d[10]), "+f"(d[11]), "+f"(d[12]), "+f"(d[13]), "+f"(d[14]), "+f"(d[15]), "+f"(d[16]), "+f"(d[17]), "+f"(d[18]), "+f"(d[19]), "+f"(d[20]), "+f"(d[21]), "+f"(d[22]), "+f"(d[23]), "+f"(d[24]), "+f"(d[25]), "+f"(d[26]), "+f"(d[27])
    : "r"(a[0]), "r"(a[1]), "r"(a[2]), "r"(a[3]), "l"(db), "r"(sc), "n"(TB));
}

template<int TB> __device__ __forceinline__ void wgmma_rs_n32(float (&d)[16], const uint32_t (&a)[4], uint64_t db, int sc) {
  asm volatile("{\n.reg .pred p;\nsetp.ne.b32 p, %21, 0;\n"
    "wgmma.mma_async.sync.aligned.m64n32k16.f32.bf16.bf16 {%0, %1, %2, %3, %4, %5, %6, %7, %8, %9, %10, %11, %12, %13, %14, %15}, {%16, %17, %18, %19}, %20, p, 1, 1, %22;\n}\n"
    : "+f"(d[0]), "+f"(d[1]), "+f"(d[2]), "+f"(d[3]), "+f"(d[4]), "+f"(d[5]), "+f"(d[6]), "+f"(d[7]), "+f"(d[8]), "+f"(d[9]), "+f"(d[10]), "+f"(d[11]), "+f"(d[12]), "+f"(d[13]), "+f"(d[14]), "+f"(d[15])
    : "r"(a[0]), "r"(a[1]), "r"(a[2]), "r"(a[3]), "l"(db), "r"(sc), "n"(TB));
}

template<int TB> __device__ __forceinline__ void wgmma_rs_n80(float (&d)[40], const uint32_t (&a)[4], uint64_t db, int sc) {
  asm volatile("{\n.reg .pred p;\nsetp.ne.b32 p, %45, 0;\n"
    "wgmma.mma_async.sync.aligned.m64n80k16.f32.bf16.bf16 {%0, %1, %2, %3, %4, %5, %6, %7, %8, %9, %10, %11, %12, %13, %14, %15, %16, %17, %18, %19, %20, %21, %22, %23, %24, %25, %26, %27, %28, %29, %30, %31, %32, %33, %34, %35, %36, %37, %38, %39}, {%40, %41, %42, %43}, %44, p, 1, 1, %46;\n}\n"
    : "+f"(d[0]), "+f"(d[1]), "+f"(d[2]), "+f"(d[3]), "+f"(d[4]), "+f"(d[5]), "+f"(d[6]), "+f"(d[7]), "+f"(d[8]), "+f"(d[9]), "+f"(d[10]), "+f"(d[11]), "+f"(d[12]), "+f"(d[13]), "+f"(d[14]), "+f"(d[15]), "+f"(d[16]), "+f"(d[17]), "+f"(d[18]), "+f"(d[19]), "+f"(d[20]), "+f"(d[21]), "+f"(d[22]), "+f"(d[23]), "+f"(d[24]), "+f"(d[25]), "+f"(d[26]), "+f"(d[27]), "+f"(d[28]), "+f"(d[29]), "+f"(d[30]), "+f"(d[31]), "+f"(d[32]), "+f"(d[33]), "+f"(d[34]), "+f"(d[35]), "+f"(d[36]), "+f"(d[37]), "+f"(d[38]), "+f"(d[39])
    : "r"(a[0]), "r"(a[1]), "r"(a[2]), "r"(a[3]), "l"(db), "r"(sc), "n"(TB));
}

namespace {
constexpr int S_ = 2048, D_ = 448, F_ = 1792;
constexpr int NSLOT = 8, SLOT = 22528;
constexpr int OFF_X = 7 * 16384;
constexpr int OFF_WQ = 8 * 16384;
constexpr int OFF_Q = NSLOT * SLOT;
constexpr int OFF_K = OFF_Q + 16384;
constexpr int OFF_BAR = 14 * 16384;
constexpr int OFF_LN = OFF_BAR + 384;
constexpr int OFF_OBS = OFF_BAR + 512;
constexpr int SMEM_BYTES = OFF_OBS + 1024;
#define PACE0 0
#define PACE1 540
#define PACE2 650
#define WARM 3
#define NW0 2
#define HEAT 1
#define T0 0
#define TP 250
#define J3 0
#define J1 9
#define J2 14
#define EARLY 4
#define PPE 4
#define PQE 2
#define LANDOBS 0
#define TRUNC 0
#define KOBS 0
#define PRE 1
#define QA 2
#define HEARLY 0
#define OSLEEP 20
#define PROBE 1
#define WOP 0
#define OGRP 2
#define OMODE 3
#define GCH 0
#define GLAG 2
#define GSLOW 0
#define RH 32
#define NOST 0
#define GOBS 0
#define HP 0
#define OPP 0
#define STAG 0
#define MU 0
#define P2 224
#define UP 170
#define POLL "relaxed"
#define OPW 0
#define SEARLY 1
#define EXACT 0
#define SOBS 0
#define FREQ 0
#define OBS(c, i) do {} while (0)
#define OBSG(c, i, j) do {} while (0)
constexpr int NTHREADS = 384;
constexpr float SCALE = 0.18898223650461361f, LOG2E = 1.4426950408889634f;
constexpr int BT = 14336;

constexpr int HU_T = 67;
constexpr int O_OFF = 4 * HU_T * BT;
constexpr int HALO_OFF = O_OFF + 32 * 7 * 8192;
constexpr int CNT_OFF = HALO_OFF + 128 * 3584;
constexpr int SCR_BYTES = CNT_OFF + 160 * 128;
constexpr int C_WO = 0, C_TK = 1, C_U = 2, C_O = 8, C_H = 24, C_HALO = 32;
__device__ __align__(1024) unsigned char g_scr[SCR_BYTES];

__device__ __forceinline__ uint32_t smem_u32(const void* p) { return (uint32_t)__cvta_generic_to_shared(p); }
__device__ __forceinline__ void mbar_init(uint32_t bar, uint32_t cnt) { asm volatile("mbarrier.init.shared::cta.b64 [%0], %1;" :: "r"(bar), "r"(cnt)); }
__device__ __forceinline__ void mbar_expect_tx(uint32_t bar, uint32_t bytes) { asm volatile("mbarrier.arrive.expect_tx.shared::cta.b64 _, [%0], %1;" :: "r"(bar), "r"(bytes) : "memory"); }
__device__ __forceinline__ void mbar_arrive_if(uint32_t c, uint32_t bar) { asm volatile("{\n.reg .pred q;\nsetp.ne.u32 q, %1, 0;\n@q mbarrier.arrive.shared::cta.b64 _, [%0];\n}" :: "r"(bar), "r"(c) : "memory"); }
__device__ __forceinline__ void mbar_arrive(uint32_t bar) { asm volatile("mbarrier.arrive.shared::cta.b64 _, [%0];" :: "r"(bar) : "memory"); }
__device__ __forceinline__ void mbar_wait(uint32_t bar, uint32_t parity) {
  asm volatile("{\n.reg .pred p;\n.reg .u32 n;\nmov.u32 n, 0;\nLAB_WAIT:\n"
               "mbarrier.try_wait.parity.shared::cta.b64 p, [%0], %1;\n@p bra DONE;\n"
               "add.u32 n, n, 1;\nsetp.lt.u32 p, n, 400000;\n@p bra LAB_WAIT;\ntrap;\nDONE:\n}" :: "r"(bar), "r"(parity) : "memory");
}
__device__ __forceinline__ uint32_t mbar_try(uint32_t bar, uint32_t parity) {
  uint32_t ok;
  asm volatile("{\n.reg .pred p;\nmbarrier.test_wait.parity.shared::cta.b64 p, [%1], %2;\nselp.u32 %0, 1, 0, p;\n}" : "=r"(ok) : "r"(bar), "r"(parity) : "memory");
  return ok;
}
__device__ __forceinline__ void tma3d(uint32_t dst, const CUtensorMap* m, int c0, int c1, int c2, uint32_t bar) {
  asm volatile("cp.async.bulk.tensor.3d.shared::cluster.global.mbarrier::complete_tx::bytes [%0], [%1, {%3, %4, %5}], [%2];"
               :: "r"(dst), "l"(m), "r"(bar), "r"(c0), "r"(c1), "r"(c2) : "memory");
}
__device__ __forceinline__ void bulk_g2s(uint32_t dst, const void* src, uint32_t bytes, uint32_t bar) {
  asm volatile("cp.async.bulk.shared::cluster.global.mbarrier::complete_tx::bytes [%0], [%1], %2, [%3];" :: "r"(dst), "l"(src), "r"(bytes), "r"(bar) : "memory");
}
__device__ __forceinline__ void wg_fence() { asm volatile("wgmma.fence.sync.aligned;" ::: "memory"); }
__device__ __forceinline__ void wg_commit() { asm volatile("wgmma.commit_group.sync.aligned;" ::: "memory"); }
template <int N> __device__ __forceinline__ void wg_wait() { asm volatile("wgmma.wait_group.sync.aligned %0;" :: "n"(N) : "memory"); }
__device__ __forceinline__ void smem_fence() { asm volatile("fence.proxy.async.shared::cta;" ::: "memory"); }
__device__ __forceinline__ void stg128(void* p, uint32_t a, uint32_t b, uint32_t c, uint32_t d) { asm volatile("st.global.v4.u32 [%0], {%1,%2,%3,%4};" :: "l"(p), "r"(a), "r"(b), "r"(c), "r"(d) : "memory"); }
__device__ __forceinline__ void stg32(void* p, uint32_t v) { asm volatile("st.global.u32 [%0], %1;" :: "l"(p), "r"(v) : "memory"); }
__device__ __forceinline__ uint4 ldg128(const void* p) { uint4 v; asm volatile("ld.global.nc.L1::no_allocate.v4.u32 {%0,%1,%2,%3}, [%4];" : "=r"(v.x), "=r"(v.y), "=r"(v.z), "=r"(v.w) : "l"(p)); return v; }
__device__ __forceinline__ void publish(unsigned char* scr, int i) {
  asm volatile("{\n.reg .pred q;\nelect.sync _|q, 0xffffffff;\n@q red.relaxed.gpu.global.inc.u32 [%0], 0xffffffff;\n}" :: "l"(scr + CNT_OFF + i * 128) : "memory");
}
__device__ __forceinline__ void spin_ge(unsigned char* scr, int i, unsigned target) {
  asm volatile("{\n.reg .pred p;\n.reg .u32 n, v;\nmov.u32 n, 0;\nLAB_SPIN:\n"
               "ld." POLL ".gpu.global.u32 v, [%0];\nsetp.ge.u32 p, v, %1;\nvote.sync.all.pred p, p, 0xffffffff;\n@p bra DONE;\n"
               "add.u32 n, n, 1;\nsetp.lt.u32 p, n, 4000000;\n@p bra LAB_SPIN;\ntrap;\nDONE:\n}" :: "l"(scr + CNT_OFF + i * 128), "r"(target) : "memory");
}
__device__ __forceinline__ int lane_id() { int l; asm volatile("mov.u32 %0, %%laneid;" : "=r"(l)); return l; }
__device__ __forceinline__ uint32_t pin(uint32_t v) { return __shfl_xor_sync(0xffffffffu, v, blockIdx.y); }
__device__ __forceinline__ unsigned char* pin(unsigned char* p) { return (unsigned char*)(((uint64_t)pin((uint32_t)((uint64_t)p >> 32)) << 32) | pin((uint32_t)(uint64_t)p)); }
__device__ __forceinline__ bool elect() {
  uint32_t r; asm volatile("{\n.reg .pred p;\nelect.sync _|p, 0xffffffff;\nselp.u32 %0, 1, 0, p;\n}" : "=r"(r)); return r != 0;
}
__device__ __forceinline__ uint4 lds128(uint32_t a) { uint4 v; asm volatile("ld.shared.v4.u32 {%0,%1,%2,%3}, [%4];" : "=r"(v.x), "=r"(v.y), "=r"(v.z), "=r"(v.w) : "r"(a) : "memory"); return v; }
__device__ __forceinline__ uint2 lds64(uint32_t a) { uint2 v; asm volatile("ld.shared.v2.u32 {%0,%1}, [%2];" : "=r"(v.x), "=r"(v.y) : "r"(a) : "memory"); return v; }
__device__ __forceinline__ void sts128(uint32_t p, uint32_t a, uint32_t b, uint32_t c, uint32_t d) { asm volatile("st.shared.v4.u32 [%0], {%1,%2,%3,%4};" :: "r"(p), "r"(a), "r"(b), "r"(c), "r"(d) : "memory"); }
__device__ __forceinline__ void sts32(uint32_t a, float v) { asm volatile("st.shared.f32 [%0], %1;" :: "r"(a), "f"(v) : "memory"); }
__device__ __forceinline__ void named_sync(int id, int n) { asm volatile("bar.sync %0, %1;" :: "r"(id), "r"(n) : "memory"); }
__device__ __forceinline__ void named_arrive(int id, int n) { asm volatile("bar.arrive %0, %1;" :: "r"(id), "r"(n) : "memory"); }
__device__ __forceinline__ void named_arrive_if(uint32_t c, int id, int n) { asm volatile("{\n.reg .pred q;\nsetp.ne.u32 q, %2, 0;\n@q bar.arrive %0, %1;\n}" :: "r"(id), "r"(n), "r"(c) : "memory"); }
__device__ __forceinline__ uint64_t mkdesc(uint32_t hi, uint32_t lo) { return ((uint64_t)hi << 32) | lo; }
constexpr uint32_t HI_SW128 = 0x40000040u;
__device__ __forceinline__ uint32_t pack2(float lo, float hi) { uint32_t r; asm("cvt.rn.bf16x2.f32 %0, %1, %2;" : "=r"(r) : "f"(hi), "f"(lo)); return r; }
__device__ __forceinline__ float bf_lo(uint32_t v) { return __uint_as_float(v << 16); }
__device__ __forceinline__ float bf_hi(uint32_t v) { return __uint_as_float(v & 0xffff0000u); }
__device__ __forceinline__ float rbf(float x) { return bf_lo(pack2(x, 0.f)); }
__device__ __forceinline__ uint32_t hsub2(uint32_t a, uint32_t b) { uint32_t r; asm("sub.rn.bf16x2 %0, %1, %2;" : "=r"(r) : "r"(a), "r"(b)); return r; }
__device__ __forceinline__ uint32_t hadd2(uint32_t a, uint32_t b) { uint32_t r; asm("add.rn.bf16x2 %0, %1, %2;" : "=r"(r) : "r"(a), "r"(b)); return r; }
__device__ __forceinline__ uint32_t hmul2(uint32_t a, uint32_t b) { uint32_t r; asm("mul.rn.bf16x2 %0, %1, %2;" : "=r"(r) : "r"(a), "r"(b)); return r; }
__device__ __forceinline__ uint32_t hfma2(uint32_t a, uint32_t b, uint32_t c) { uint32_t r; asm("fma.rn.bf16x2 %0, %1, %2, %3;" : "=r"(r) : "r"(a), "r"(b), "r"(c)); return r; }
__device__ __forceinline__ float tanh_fast(float x) { float r; asm("tanh.approx.f32 %0, %1;" : "=f"(r) : "f"(x)); return r; }
__device__ __forceinline__ float rcp_fast(float x) { float r; asm("rcp.approx.ftz.f32 %0, %1;" : "=f"(r) : "f"(x)); return r; }
__device__ __forceinline__ float ex2_fast(float x) { float r; asm("ex2.approx.ftz.f32 %0, %1;" : "=f"(r) : "f"(x)); return r; }
__device__ __forceinline__ void mma16816(float (&c)[4], uint32_t a0, uint32_t a1, uint32_t a2, uint32_t a3, uint32_t b0, uint32_t b1) {
  asm volatile("mma.sync.aligned.m16n8k16.row.col.f32.bf16.bf16.f32 {%0,%1,%2,%3}, {%4,%5,%6,%7}, {%8,%9}, {%0,%1,%2,%3};"
               : "+f"(c[0]), "+f"(c[1]), "+f"(c[2]), "+f"(c[3]) : "r"(a0), "r"(a1), "r"(a2), "r"(a3), "r"(b0), "r"(b1));
}
__device__ __forceinline__ void ldsm4(uint32_t (&r)[4], uint32_t addr) {
  asm volatile("ldmatrix.sync.aligned.m8n8.x4.shared.b16 {%0,%1,%2,%3}, [%4];" : "=r"(r[0]), "=r"(r[1]), "=r"(r[2]), "=r"(r[3]) : "r"(addr) : "memory");
}
__device__ __forceinline__ void stsm4(uint32_t addr, uint32_t a, uint32_t b, uint32_t c, uint32_t d) {
  asm volatile("stmatrix.sync.aligned.m8n8.x4.shared.b16 [%0], {%1,%2,%3,%4};" :: "r"(addr), "r"(a), "r"(b), "r"(c), "r"(d) : "memory");
}

__device__ __forceinline__ float ln_rstd(float var, float eps = 1e-5f) {
  float sd;
  asm("sqrt.approx.ftz.f32 %0, %1;" : "=f"(sd) : "f"(rbf(rbf(var) + eps)));
  return rcp_fast(rbf(sd));
}
__device__ __forceinline__ float ln_var(float mean, float sq) { return fmaxf(fmaf(-mean, mean, sq * (1.0f / D_)), 0.f); }
struct LnC { uint32_t m, rh, rl; };
__device__ __forceinline__ LnC ln_consts(float sum, float sq, float eps) {
  const float mean = sum * (1.0f / D_), r = ln_rstd(ln_var(mean, sq), eps), rh = rbf(r);
  LnC c; c.m = pack2(mean, mean); c.rh = pack2(rh, rh); c.rl = pack2(r - rh, r - rh);
  return c;
}
__device__ __forceinline__ uint32_t ln_apply(uint32_t x, const LnC& c) {
  uint32_t d = hsub2(x, c.m);
  return hfma2(d, c.rh, hmul2(d, c.rl));
}

__device__ __forceinline__ void fence_code(int id) {
  asm volatile("{\n.reg .pred q;\nLAB_F:\nsetp.eq.u32 q, %0, %1;\n@q st.volatile.shared.u32 [%2], %2;\n@q bra LAB_F;\n}" :: "r"(blockIdx.x), "r"(0x70000000 + id), "r"(0) : "memory");
}
template <int N> __device__ __forceinline__ void fresh(float (&a)[N]) {
#pragma unroll
  for (int i = 0; i < N; i++) asm volatile("" : "=f"(a[i]));
}
constexpr int B_EMPTY = 64, B_X = 128, B_KV = 192, B_WQ = 248, B_HALO = 256, B_RES = 264, B_ATT = 272, B_GATE = 280, B_T0 = 304;

template <int TA>
__device__ __forceinline__ void gemm_issue(float (&acc)[56], uint32_t lo, int sc) {
  wg_fence();
#pragma unroll
  for (int k = 0; k < 4; k++)
    wgmma_n112<TA, 1>(acc, mkdesc(TA ? HI_SW128 : 8, lo + (TA ? 512u << 16 : 64u << 16) + k * 128), mkdesc(8, lo + (112u << 16) + 512 + k * 224), sc | k);
  wg_commit();
}
template <int TA>
__device__ __forceinline__ void gemm_stage(float (&acc)[56], uint32_t base, int it, int sc) {
  mbar_wait(base + OFF_BAR + (it & 7) * 8, (it >> 3) & 1);
  gemm_issue<TA>(acc, (base >> 4) + (it & 7) * (SLOT >> 4), sc);
}
template <int TA>
__device__ __forceinline__ void gemm_loop(float (&acc)[56], uint32_t base, int it, int end, bool rel, int oi, uint32_t ok = 0, int gate_it = -1, uint32_t gate = 0) {
#pragma unroll 1
  for (; it < end;) {
    if (__builtin_expect(!ok, 0)) mbar_wait(base + OFF_BAR + (it & 7) * 8, (it >> 3) & 1);
    gemm_issue<TA>(acc, (base >> 4) + (it & 7) * (SLOT >> 4), 1);
    OBS(SOBS && rel, oi + it);
    it++;
    ok = mbar_try(base + OFF_BAR + (it & 7) * 8, (it >> 3) & 1);
    wg_wait<1>();
    if (rel || it == gate_it) mbar_arrive(rel ? base + OFF_BAR + B_EMPTY + ((it - 2) & 7) * 8 : gate);
  }
}
template <int PER>
__device__ __forceinline__ void produce_box(uint32_t base, int it, int end, const CUtensorMap* mp, int c0, int c1, uint32_t tn = 0) {
#pragma unroll 1
  for (; it < end; it++) {
    const uint32_t fb = base + OFF_BAR + (it & 7) * 8;
    mbar_wait(fb + B_EMPTY, (it >> 3) & 1);
    if (PER) { while ((int)(clock() - tn) < 0); tn += PER; }
    if (elect()) { mbar_expect_tx(fb, 8192); tma3d(base + (it & 7) * SLOT, mp, c0, c1, 0, fb); }
    c1 += 64;
  }
}
template <int PER>
__device__ __forceinline__ void produce_lin(uint32_t base, int it, int end, const unsigned char* src, uint32_t bytes, uint32_t tn = 0) {
#pragma unroll 1
  for (; it < end; it++) {
    const uint32_t fb = base + OFF_BAR + (it & 7) * 8;
    mbar_wait(fb + B_EMPTY, (it >> 3) & 1);
    if (PER) { while ((int)(clock() - tn) < 0); tn += PER; }
    if (elect()) { mbar_expect_tx(fb, bytes); bulk_g2s(base + (it & 7) * SLOT + (bytes & 2048) * 4, src, bytes, fb); }
    src += bytes;
  }
}

__device__ __forceinline__ void retile_wo(const unsigned char* wo, unsigned char* scr, int u, int lane) {
  const int r8 = lane & 7, mi = lane >> 3;
  const unsigned char* src = wo + ((u >> 1) * 8 + r8) * 896 + ((u & 1) * 28 + mi) * 16;
  unsigned char* dst = scr + ((u & 1) * 2 * HU_T + 60 + (u >> 4)) * BT + ((u >> 1) & 7) * 1792 + mi * 128 + r8 * 16;
  uint4 v[7];
#pragma unroll
  for (int i = 0; i < 7; i++) v[i] = ldg128(src + i * 64);
#pragma unroll
  for (int i = 0; i < 7; i++) stg128(dst + i * 512 + ((i * 4 + mi) / 14) * (HU_T * BT - 1792), v[i].x, v[i].y, v[i].z, v[i].w);
  publish(scr, C_WO);
}

struct Params {
  const unsigned char *wo, *w1, *b1, *w2, *b2;
  unsigned char *out, *scr;
};

__global__ void __launch_bounds__(NTHREADS, 1)
fused_kernel(const __grid_constant__ CUtensorMap m_x, const __grid_constant__ CUtensorMap m_wkv, const __grid_constant__ CUtensorMap m_wq,
             const __grid_constant__ CUtensorMap m_w1, const __grid_constant__ CUtensorMap m_w2, const __grid_constant__ CUtensorMap m_res, const Params p) {
  extern __shared__ __align__(1024) unsigned char smem_raw[];
  constexpr uint32_t base = 1024, bars = base + OFF_BAR;
  const int tid = threadIdx.x, lane = tid & 31, b = blockIdx.x;
  const int rb = (b >> 2) & 15, hp = ((b >> 6) << 2) | (b & 3);
  const int wcol = hp * 56 - (hp & 1) * 8;
  auto load_kv = [&](int s) { mbar_expect_tx(bars + B_KV + s * 8, 16384); tma3d(base + s * 16384, &m_wkv, wcol, s * 64, 1, bars + B_KV + s * 8); };
  if (tid < 32) {
    if (elect()) {
#pragma unroll
      for (int i = 0; i < 7; i++) mbar_init(bars + B_X + i * 8, 1);
      asm volatile("fence.mbarrier_init.release.cluster;" ::: "memory");
#pragma unroll
      for (int i = 0; i < 7; i++) { mbar_expect_tx(bars + B_X + i * 8, 16384); tma3d(base + OFF_X + i * 16384, &m_x, i * 64, rb * 128, 0, bars + B_X + i * 8); }
#pragma unroll
      for (int i = 0; i < 7; i++) mbar_init(bars + B_KV + i * 8, 1);
      asm volatile("fence.mbarrier_init.release.cluster;" ::: "memory");
#pragma unroll 1
      for (int i = 0; i < NW0; i++) load_kv(i);
    }
  }
  const int warp = __shfl_sync(0xffffffffu, tid >> 5, 0);
  if (warp == 1) {
    if (elect()) {
#pragma unroll
      for (int i = 0; i < 16; i++) mbar_init(bars + i * 8, 2);
#pragma unroll
      for (int i = 0; i < 7; i++) mbar_init(bars + B_WQ + i * 8, 1);
      asm volatile("fence.mbarrier_init.release.cluster;" ::: "memory");
      if (smem_u32(smem_raw) != base) asm volatile("trap;");
    }
  }
  const int dt = b & 3, mt = b >> 2;
  const bool g1 = (b & 15) < 14;
  const int a1 = b - 2 * (b >> 4), ft = a1 >> 2, d1 = a1 & 3;
  const int g = lane >> 2, t = lane & 3, r8 = lane & 7, mi = lane >> 3;
  OBSG(FREQ && tid == 160, 128, 160);
  __syncthreads();
  if (warp >= 8) {
    asm volatile("setmaxnreg.dec.sync.aligned.u32 40;");
    const int pw = warp - 8;
    unsigned char* scr = p.scr;
    if (NW0 < 7 && pw == 3) {
      mbar_wait(bars + B_X, 0);
      if (elect()) {
#pragma unroll 1
        for (int i = NW0; i < 7; i++) load_kv(i);
      }
      __syncwarp();
    }
    {
      const int c0 = pw * 14 + (mi >> 1);
      unsigned char* dst = scr + (pw * HU_T + rb * 2 + (hp >> 2)) * BT + ((hp & 3) * 2 + (mi & 1)) * 1792 + (mi >> 1) * 128 + r8 * 16;
      const uint32_t xs = base + OFF_X + (hp * 16 + (lane & 15)) * 128;
      uint4 H[7];
      named_sync(9, 160);
#pragma unroll
      for (int i = 0; i < 7; i++) H[i] = lds128(xs + ((c0 + 2 * i) >> 3) * 16384 + ((((c0 + 2 * i) & 7) ^ r8) << 4));
      asm volatile("" :: "r"(H[6].w), "r"(H[0].x) : "memory");
      if (pw != 3) named_arrive(8, 384);
      else {
        named_sync(8, 384);
        if (elect()) {
          mbar_expect_tx(bars + B_WQ, 57344);
          tma3d(base + OFF_WQ, &m_wq, wcol, 0, 0, bars + B_WQ); tma3d(base + OFF_WQ + 28672, &m_wq, wcol, 224, 0, bars + B_WQ);
        }
        __syncwarp();
      }
      const uint2 st = lds64(base + OFF_LN + (lane & 15) * 8);
      const float sum = __uint_as_float(st.x), mean = sum * (1.0f / D_), var = ln_var(mean, __uint_as_float(st.y));
      const float m = rbf(mean), r = ln_rstd(var), r2 = ln_rstd(var * r * r);
      const float nc = fmaf(m, (float)D_, -sum) * (1.0f / D_) * (r * r2);
      const uint32_t m2 = pack2(m, m), r2x = pack2(r * r2, r * r2), nc2 = pack2(nc, nc);
      auto f = [&](uint32_t v) { return hfma2(hsub2(v, m2), r2x, nc2); };
#pragma unroll
      for (int i = 0; i < 7; i++) stg128(dst + i * 256, f(H[i].x), f(H[i].y), f(H[i].z), f(H[i].w));
      if (pw != 1) named_arrive(4, 128);
      else { named_sync(4, 128); publish(scr, C_H + (b & 3)); }
      OBS(tid == 288, 4);
    }
    const int lane = lane_id();
    if (pw == 0) {
      if (elect()) {
        asm volatile("prefetch.tensormap [%0];" :: "l"(&m_w1) : "memory");
        asm volatile("prefetch.tensormap [%0];" :: "l"(&m_w2) : "memory");
        asm volatile("prefetch.tensormap [%0];" :: "l"(&m_res) : "memory");
      }
      if (g1) produce_box<0>(base, 0, 32, &m_w1, ft * 64, 0);
      mbar_wait(bars + B_ATT, 0);
      if (elect()) { mbar_expect_tx(bars + B_RES, BT); tma3d(base + OFF_Q, &m_res, dt * 112, mt * 64, 0, bars + B_RES); }
      spin_ge(scr, C_WO, 112);
      produce_lin<0>(base, 0, 7, scr + (dt * HU_T + 60) * BT, BT);
      if (MU) {
        produce_box<0>(base, 7, 15, &m_w2, mt * 64, 0);
        mbar_wait(bars + 56, 0);
        produce_box<P2>(base, 15, 35, &m_w2, mt * 64, 512, lds64(bars + B_T0).x + MU);
      } else produce_box<0>(base, 7, 35, &m_w2, mt * 64, 0);
    } else if (pw == 1) {
      if (g1) {
        spin_ge(scr, C_H + (lane & 3), 32);
        OBS(lane == 0, 16);
        if (HP) { produce_lin<HP>(base, 0, 8, scr + d1 * HU_T * BT, BT, clock()); produce_lin<0>(base, 8, 32, scr + (d1 * HU_T + 8) * BT, BT); }
        else produce_lin<0>(base, 0, 32, scr + d1 * HU_T * BT, BT);
      }
      spin_ge(scr, C_O + (mt >> 1), 8);
      OBS(lane == 0, 17);
      produce_lin<OPP>(base, 0, 7, scr + O_OFF + mt * 57344, 8192, clock());
      const unsigned char* us = scr + (dt * HU_T + 32) * BT;
      mbar_wait(bars + B_EMPTY + 56, 0);
      if (elect()) mbar_expect_tx(bars + 56, BT);
      __syncwarp();
      spin_ge(scr, C_U + dt, 28);
      if (elect()) bulk_g2s(base + 7 * SLOT + 8192, us, BT, bars + 56);
      const uint32_t tu = clock();
      if (MU) sts32(bars + B_T0, __uint_as_float(tu));
      OBS(lane == 0, 18);
      produce_lin<UP>(base, 8, 15, us + BT, BT, tu + UP);
      produce_lin<(MU ? P2 : 0)>(base, 15, 35, us + 8 * BT, BT, tu + MU);
      unsigned tk = 0;
      if (lane == 0) tk = atomicAdd((unsigned*)(scr + CNT_OFF + C_TK * 128), 1u);
      if (__shfl_sync(0xffffffffu, tk, 0) == 127) {
#pragma unroll 1
        for (int i = lane; i < 160; i += 32) *(unsigned*)(scr + CNT_OFF + i * 128) = 0;
      }
    } else if (pw == 2) {
      uint32_t tn = clock() + PACE0 + b * STAG;
      const unsigned char* src = p.w1 + b * 4096 + lane * 128;
#pragma unroll 1
      for (int i = 0; i < 28 + FREQ * 2; i++) {
        while ((int)(clock() - tn) < 0) __nanosleep(20);
        if (i == 14) src = p.w2 + b * 4096 + lane * 128;
        if (i < 28) asm volatile("prefetch.global.L2 [%0];" :: "l"(src) : "memory");
        OBSG(FREQ && lane == 0, 129 + i, 161 + i);
        src += 128 * 4096;
        tn += i < 14 ? PACE1 : PACE2;
      }
    } else {
      if (!WOP && b < 112) retile_wo(p.wo, scr, b, lane_id());
      const int lane = lane_id();
      unsigned char* hg = scr + HALO_OFF + (rb * 8 + hp) * 3584 + lane * 16;
      named_sync(1, 64);
      if (rb < 15) {
        uint4 v[7];
#pragma unroll
        for (int i = 0; i < 7; i++) v[i] = lds128(base + OFF_K + 8 * 3584 + i * 512 + lane * 16);
#pragma unroll
        for (int i = 0; i < 7; i++) stg128(hg + i * 512, v[i].x, v[i].y, v[i].z, v[i].w);
        publish(scr, C_HALO + rb * 8 + hp);
      }
      OBS(lane == 0, 29);
      if (rb > 0) {
        spin_ge(scr, C_HALO + (rb - 1) * 8 + hp, 1);
        OBS(lane == 0, 12);
        if (elect()) { mbar_expect_tx(bars + B_HALO, 3584); bulk_g2s(base + OFF_K, scr + HALO_OFF + ((rb - 1) * 8 + hp) * 3584, 3584, bars + B_HALO); }
      } else {
#pragma unroll
        for (int i = 0; i < 7; i++) sts128(base + OFF_K + i * 512 + lane * 16, 0, 0, 0, 0);
        smem_fence();
        __syncwarp();
        if (lane == 0) mbar_arrive(bars + B_HALO);
      }
    }
  } else {
    asm volatile("setmaxnreg.inc.sync.aligned.u32 232;");
    const int wg = warp >> 2, w4 = warp & 3, th = wg ^ 1;
    const bool rel = (tid & 127) < 2;
    unsigned char* scr = p.scr;
    uint32_t X[28][4];
    float aq[28];
    const uint32_t dlo = (base >> 4) + (512u << 16) + (hp & 1), dlq = dlo + (OFF_WQ >> 4);
    {
      uint32_t xa[4];
#pragma unroll
      for (int k = 0; k < 4; k++) xa[k] = base + OFF_X + (th * 64 + w4 * 16 + (mi >> 1) * 8 + r8) * 128 + (((2 * k + (mi & 1)) ^ r8) << 4);
      float c0[2][4] = {}, c1[2][4] = {};
      uint32_t one[8];
#pragma unroll
      for (int j = 0; j < 8; j++) asm volatile("{\n.reg .u32 y;\nmov.u32 y, %%tid.y;\nmad.lo.u32 %0, y, %1, 0x3f803f80;\n}" : "=r"(one[j]) : "r"(lane + j));
      asm volatile("" : "+l"(scr));
      uint32_t ok = 0;
      if (HEAT) {
#pragma unroll 1
        for (int n = 0; n < 64 && !ok; n++) { mma16816(c0[0], 0, 0, 0, 0, 0, 0); ok = mbar_try(bars + B_X, 0); }
      }
#pragma unroll
      for (int i = 0; i < 8; i++) {
        if (i < 7) {
          if (!ok) mbar_wait(bars + B_X + i * 8, 0);
          OBS(tid == 64 && i == 0, 0); OBS(tid == 64 && i == 6, 15);
#pragma unroll
          for (int k = 0; k < 4; k++) ldsm4(X[i * 4 + k], xa[k] + i * 16384);
          if (i < 6) ok = mbar_try(bars + B_X + i * 8 + 8, 0);
        }
        if (i > 0) {
#pragma unroll
          for (int k = i * 4 - 4; k < i * 4; k++) {
            mma16816(c0[k & 1], X[k][0], one[(k & 1) * 4], X[k][1], one[(k & 1) * 4 + 1], X[k][0], X[k][1]);
            mma16816(c1[k & 1], X[k][2], one[(k & 1) * 4 + 2], X[k][3], one[(k & 1) * 4 + 3], X[k][2], X[k][3]);
          }
        }
      }
      float st[4];
#pragma unroll
      for (int j = 0; j < 2; j++) {
        st[j] = __shfl_sync(0xffffffffu, (g & 1) ? c0[0][2 * j + 1] + c0[1][2 * j + 1] : c0[0][2 * j] + c0[1][2 * j], (lane & 28) | (g >> 1));
        st[2 + j] = __shfl_sync(0xffffffffu, (g & 1) ? c1[0][2 * j + 1] + c1[1][2 * j + 1] : c1[0][2 * j] + c1[1][2 * j], (lane & 28) | (g >> 1));
      }
      named_arrive(8, 384);
      asm volatile("{\n.reg .pred q;\nsetp.ne.u32 q, %3, 0;\n@q st.shared.v2.f32 [%0], {%1,%2};\n@q bar.arrive 9, 160;\n}"
                   :: "r"(base + OFF_LN + ((t & 1) * 8 + g) * 8), "f"((t & 1) ? st[3] : st[1]), "f"((t & 1) ? st[2] : st[0]), "r"((uint32_t)((warp ^ 4) == hp)) : "memory");
      ok = mbar_try(bars + B_KV, 0);
      LnC l0, l1;
      float eps = 1e-5f;
#pragma unroll 1
      do {
        l0 = ln_consts(st[1], st[0], eps); l1 = ln_consts(st[3], st[2], eps);
#pragma unroll
        for (int k = 0; k < PRE * 16; k++) X[k >> 2][k & 3] = hsub2(X[k >> 2][k & 3], k & 2 ? l1.m : l0.m);
        eps += eps;
      } while ((l0.rl ^ l1.rl) == 4);
      OBS(tid == 32, 1);
      float ak[60], *av = ak + 32;
      const int pp_in = wg ? 6 : 0, pp_out = wg ? 0 : 6;
#pragma unroll
      for (int s = 0; s < 7; s++) {
#pragma unroll
        for (int k = s * 4; k < s * 4 + 4; k++) {
          if (s < PRE) {
            auto f = [&](uint32_t d, const LnC& l) { return hfma2(d, l.rh, hmul2(d, l.rl)); };
            const uint32_t y = f(X[k][1], l0);
            X[k][0] = f(X[k][0], l0); X[k][1] = f(X[k][2], l1); X[k][2] = y; X[k][3] = f(X[k][3], l1);
          } else {
            const uint32_t y = ln_apply(X[k][1], l0);
            X[k][0] = ln_apply(X[k][0], l0); X[k][1] = ln_apply(X[k][2], l1); X[k][2] = y; X[k][3] = ln_apply(X[k][3], l1);
          }
        }
        if (__builtin_expect(!ok, 0)) { mbar_wait(bars + B_KV + s * 8, 0); if (s == 6) mbar_wait(bars + B_WQ, 0); }
        if (s == 0) fresh(ak);
        if (s == 6) { wg_wait<0>(); if ((tid & 127) == 0) mbar_arrive(bars + B_EMPTY + 3 * 8); }
        OBS(KOBS && (tid & 127) == 0, 40 + wg * 32 + s);
        if (wg || s) named_sync(pp_in, 256);
        OBS(KOBS && (tid & 127) == 32, 48 + wg * 32 + s);
        OBS(tid == 64 && s == 0, 2);
        wg_fence();
#pragma unroll
        for (int k = 0; k < 4; k++) {
          if (s < 6 && k == PPE) named_arrive(pp_out, 256);
          wgmma_rs_n120<1>(ak, X[s * 4 + k], mkdesc(HI_SW128, dlo + s * 1024 + k * 128), (s | k) != 0);
        }
        wg_commit();
        if (s == 6) {
          fresh(aq);
#pragma unroll
          for (int k = 0; k < 4 * QA; k++) {
            if (k == 4 * QA - PQE) named_arrive(pp_out, 256);
            wgmma_rs_n56<1>(aq, X[k], mkdesc(HI_SW128, dlq + k * 128), k);
          }
          wg_commit();
        }
        if (s < 6 ? PPE == 4 : PQE == 0) named_arrive(pp_out, 256);
        fence_code(s);
        OBS(KOBS && (tid & 127) == 64, 56 + wg * 32 + s);
        if (s < 6) ok = mbar_try(bars + B_KV + s * 8 + 8, 0);
        if (s == 5) ok &= mbar_try(bars + B_WQ, 0);
        OBS(tid == 64 && s == 1, 28); OBS(tid == 64 && s == 5, 31);
        if (s > 0) wg_wait<1>();
        OBS(KOBS && (tid & 127) == 96, 64 + wg * 32 + s);
        if ((s == 2 || s == 3 || s == 5) && (tid & 127) == 0) mbar_arrive(bars + B_EMPTY + (s == 5 ? 2 : s - 2) * 8);
      }
      if ((tid & 127) == 0) mbar_arrive(bars + B_EMPTY + 4 * 8);
      OBS(tid == 32, 3);
      {
        const uint32_t kst = base + OFF_K + (2 + (warp ^ 4) * 2 + (mi & 1)) * 1792 + (mi >> 1) * 896 + r8 * 16;
#pragma unroll
        for (int n = 0; n < 7; n++)
          stsm4(kst + n * 128, pack2(ak[n * 4], ak[n * 4 + 1]), pack2(ak[n * 4 + 2], ak[n * 4 + 3]), pack2(av[n * 4], av[n * 4 + 1]), pack2(av[n * 4 + 2], av[n * 4 + 3]));
        named_arrive_if(warp == 3, 1, 64);
      }
      OBS(tid == 96, 32); OBS(tid == 224, 34);
      wg_wait<0>();
      if ((tid & 127) == 0) mbar_arrive(bars + B_EMPTY + 5 * 8);
    }
    const unsigned short *bp1 = (const unsigned short*)p.b1 + (g1 ? ft * 64 : 0) + w4 * 16 + g, *bp2 = (const unsigned short*)p.b2 + mt * 64 + w4 * 16 + g;
    const uint32_t braw[4] = {__ldg(bp1), __ldg(bp1 + 8), __ldg(bp2), __ldg(bp2 + 8)};
    auto q_rest = [&]() {
      wg_fence();
#pragma unroll
      for (int s = QA; s < 7; s++) {
#pragma unroll
        for (int k = s * 4; k < s * 4 + 4; k++) wgmma_rs_n56<1>(aq, X[k], mkdesc(HI_SW128, dlq + k * 128), 1);
        wg_commit();
        if (s == 5) { wg_wait<2>(); if ((tid & 127) == 0) mbar_arrive(bars + B_EMPTY + 6 * 8); }
      }
    };
    uint32_t Q[4][4];
    auto q_pack = [&]() {
#pragma unroll
      for (int n = 0; n < 14; n++) { const int m = n + 2 * (n > 7); Q[m >> 2][m & 3] = pack2(aq[n * 2], aq[n * 2 + 1]); }
#pragma unroll
      for (int h = 0; h < 2; h++) { Q[2][h] = t < 2 ? 0u : Q[1][2 + h]; Q[1][2 + h] = t < 2 ? Q[1][2 + h] : 0u; }
    };
    float acc[56];
    auto ai = [](int p) { return p < 4 ? 48 + (p & 1) * 4 + (p & 2) : (p - 4) * 4; };
    uint32_t xch, ts, tl;
    unsigned char *ug, *uc, *outp, *outq;
    auto setup_u = [&]() {
      xch = pin(base + OFF_K + (tid & 127) * 16);
      ug = pin(scr + (d1 * HU_T + 32 + ft) * BT + w4 * 3584 + lane * 4 + wg * 1792);
      uc = pin(scr + d1 * 128);
    };
    auto setup_out = [&]() {
      const uint32_t tb = base + OFF_K + 6144 + warp * 2560;
      ts = pin(tb + mi * 160 + r8 * 16); tl = pin(tb + t * 160 + g * 16);
      unsigned char* o = p.out + (mt * 64 + w4 * 16 + g) * 896 + dt * 224;
      outp = pin(o + th * 7168 + t * 16); outq = pin(o + (t >> 1) * 7168 + 192 + (t & 1) * 16);
    };
    auto give = [&](const float (&a)[56], int id) {
#pragma unroll
      for (int i = 0; i < 48; i += 16) sts128(xch + i * 128, pack2(a[i + 2], a[i + 3]), pack2(a[i + 6], a[i + 7]), pack2(a[i + 10], a[i + 11]), pack2(a[i + 14], a[i + 15]));
      named_arrive(id, 256);
    };
    auto take = [&](uint32_t (&r)[12], int id) {
      named_sync(id, 256);
#pragma unroll
      for (int i = 0; i < 3; i++) { const uint4 v = lds128(xch + i * 2048); r[i * 4] = v.x; r[i * 4 + 1] = v.y; r[i * 4 + 2] = v.z; r[i * 4 + 3] = v.w; }
    };
    float hv[32];
    auto keep_h = [&](int i) {
      const float hb0 = 0.5f * bf_lo(braw[i]), hb1 = 0.5f * bf_lo(braw[i + 1]);
#pragma unroll
      for (int j = 0; j < 32; j++) hv[j] = fmaf(acc[ai(j >> 1) + (j & 1)], 0.5f, j >= 4 && j < 8 ? hb1 : hb0);
    };
    auto take_h = [&](int i) {
      const float hb1 = 0.5f * bf_lo(braw[i + 1]);
      uint32_t r[12];
      take(r, 5);
#pragma unroll
      for (int j = 0; j < 12; j++) { hv[8 + 2 * j] = fmaf(bf_lo(r[j]), 0.5f, hb1); hv[9 + 2 * j] = fmaf(bf_hi(r[j]), 0.5f, hb1); }
    };
    uint4 Xr[4];
    auto get_x = [&]() {
      const uint32_t xr = base + OFF_Q + (w4 * 16 + g) * 224;
      mbar_wait(bars + B_RES, 0);
      Xr[0] = lds128(xr + (t >> 1) * 1792 + 192 + (t & 1) * 16);
#pragma unroll
      for (int i = 1; i < 4; i++) Xr[i] = lds128(xr + th * 1792 + t * 16 + (i - 1) * 64);
    };
    auto gelu = [&](int j) {
      const float h0 = hv[2 * j], h1 = hv[2 * j + 1];
      const float t0 = tanh_fast(h0 * fmaf(h0 * h0, 0.2854192648f, 1.5957691216f)), t1 = tanh_fast(h1 * fmaf(h1 * h1, 0.2854192648f, 1.5957691216f));
      stg32(ug + (ai(j) & 2) * 896 + (ai(j) >> 2) * 128, pack2(fmaf(h0, t0, h0), fmaf(h1, t1, h1)));
    };
    if (wg == 0) {
      named_sync(0, 256);
      OBS(tid == 96, 14);
      q_rest();
      named_arrive(6, 256);
      wg_wait<0>();
      if (tid == 0) mbar_arrive(bars + B_EMPTY + 7 * 8);
      q_pack();
      const uint32_t qst = base + OFF_Q + 8192 + (mi >> 1) * 1024 + (w4 * 16 + (mi & 1) * 8 + r8) * 16;
#pragma unroll
      for (int n = 0; n < 4; n++) stsm4(qst + n * 2048, Q[n][0], Q[n][1], Q[n][2], Q[n][3]);
      smem_fence();
      named_arrive(7, 256);
      OBS(tid == 32, 5);
      fresh(acc);
      setup_u();
      if (g1) {
        mbar_wait(bars, 0); mbar_wait(bars + 8, 0);
        named_sync(0, 256);
        gemm_issue<1>(acc, base >> 4, 0);
        OBS(tid == 0, 20);
        gemm_loop<1>(acc, base, 1, 32, rel, 40, 1, tid == 32 ? J1 : tid == 64 ? J2 : tid == 96 ? J3 : -1, bars + B_GATE - 8 + w4 * 8);
        wg_wait<0>();
        OBS(tid == 0, 21);
        give(acc, 5);
        mbar_arrive_if(rel, bars + B_EMPTY + 7 * 8);
        fence_code(30);
        keep_h(0);
#pragma unroll
        for (int j = 0; j < 4; j++) gelu(j);
      } else {
        if (lane == 0 && w4) mbar_arrive(bars + B_GATE - 8 + w4 * 8);
      }
      if (!g1 && WOP) {
        if (WOP == 2) mbar_wait(bars + B_ATT, 0);
#pragma unroll 1
        for (int n = w4; n < 7; n += 4) retile_wo(p.wo, scr, ((b >> 4) * 2 + (b & 1)) * 7 + n, lane);
      }
    } else {
      const uint32_t dq = ((base + OFF_Q) >> 4) + (64u << 16), dk = (base + OFF_K) >> 4;
      const bool odd = g & 1, early = 2 * t + (g & 1) > g;
      uint32_t selA[5], selB[4];
#pragma unroll
      for (int j = 0; j < 5; j++) selA[j] = j == w4 + (early ? 0 : 1) ? (odd ? 0x1044u : 0x4410u) : 0x4444u;
#pragma unroll
      for (int j = 0; j < 4; j++) selB[j] = j == w4 ? (odd ? 0x3244u : 0x4432u) : 0x4444u;
      float Sc[2][40], Op[2][2][16];
      uint32_t A[2][5][4];
      auto scores = [&](int T) {
        fresh(Sc[0]); fresh(Sc[1]);
#pragma unroll
        for (int k = 0; k < 2; k++) {
#pragma unroll
          for (int hh = 0; hh < 2; hh++)
            if (T) wgmma_n80<0, 0>(Sc[hh], mkdesc(8, dq + 512 + hh * 256 + k * 128), mkdesc(112, dk + (8u << 16) + 896 + hh * 24 + k * 16), k);
            else wgmma_rs_n80<0>(Sc[hh], Q[hh * 2 + k], mkdesc(112, dk + (8u << 16) + hh * 24 + k * 16), k);
        }
      };
      auto softmax = [&](int T) {
#pragma unroll
        for (int hh = 0; hh < 2; hh++) {
          uint32_t pp[2];
#pragma unroll
          for (int h = 0; h < 2; h++) {
            float c[3];
#pragma unroll
            for (int n = 0; n < 3; n++) {
              const float* q = Sc[hh] + (h + n) * 4 + 2 * h;
              asm("{\n.reg .pred p, a, b, c;\nsetp.ne.u32 p, %9, 0;\nsetp.eq.u32 a, %10, 1;\nsetp.eq.u32 b, %10, 2;\nsetp.eq.u32 c, %10, 3;\n"
                  "selp.f32 %0, %2, %1, p;\n@a selp.f32 %0, %4, %3, p;\n@b selp.f32 %0, %6, %5, p;\n@c selp.f32 %0, %8, %7, p;\n}"
                  : "=&f"(c[n]) : "f"(q[0]), "f"(q[1]), "f"(q[8]), "f"(q[9]), "f"(q[16]), "f"(q[17]), "f"(q[24]), "f"(q[25]), "r"((uint32_t)odd), "r"((tid >> 5) & 3));
            }
            uint32_t pk = pack2(early ? c[0] : c[2], c[1]);
            pk = pack2(bf_lo(pk) * SCALE, bf_hi(pk) * SCALE);
            float l0 = bf_lo(pk), l1 = bf_hi(pk);
            if (T == 0 && w4 == 0 && rb == 0) { if (early) l0 = -1e9f; if (h == 0) l1 = -1e9f; }
            float mx = fmaxf(l0, l1);
            mx = fmaxf(mx, __shfl_xor_sync(0xffffffffu, mx, 1));
            mx = fmaxf(mx, __shfl_xor_sync(0xffffffffu, mx, 2));
            float p0 = ex2_fast((l0 - mx) * LOG2E), p1 = ex2_fast((l1 - mx) * LOG2E);
            float sm = p0 + p1;
            sm += __shfl_xor_sync(0xffffffffu, sm, 1);
            sm += __shfl_xor_sync(0xffffffffu, sm, 2);
            const float inv = rcp_fast(sm);
            pp[h] = pack2(p0 * inv, p1 * inv);
          }
#pragma unroll
          for (int j = 0; j < 5; j++) {
            A[hh][j][0] = __byte_perm(pp[0], 0, selA[j]); A[hh][j][1] = j ? __byte_perm(pp[1], 0, selB[j ? j - 1 : 0]) : 0u;
            A[hh][j][2] = j < 4 ? __byte_perm(pp[0], 0, selB[j & 3]) : 0u; A[hh][j][3] = __byte_perm(pp[1], 0, selA[j]);
          }
        }
      };
      auto values = [&](int T) {
        fresh(Op[T][0]); fresh(Op[T][1]);
#pragma unroll
        for (int j = 0; j < 5; j++)
#pragma unroll
          for (int hh = 0; hh < 2; hh++) {
            wgmma_rs_n32<1>(Op[T][hh], A[hh][j], mkdesc(8, dk + (112u << 16) + 56 + T * 896 + hh * 24 + j * 224), j);
          }
        wg_commit();
      };
      uint32_t Ob[2][14];
      auto pack = [&](int T) {
        const float (&O)[2][16] = Op[T];
#pragma unroll
        for (int n = 0; n < 7; n++)
#pragma unroll
          for (int h = 0; h < 2; h++) {
            if (n < 3) Ob[T][n * 2 + h] = pack2(O[0][n * 4 + 2 * h], O[0][n * 4 + 2 * h + 1]);
            else if (n == 3) Ob[T][n * 2 + h] = pack2(t < 2 ? O[0][12 + 2 * h] : O[1][2 * h], t < 2 ? O[0][13 + 2 * h] : O[1][2 * h + 1]);
            else Ob[T][n * 2 + h] = pack2(O[1][(n - 3) * 4 + 2 * h], O[1][(n - 3) * 4 + 2 * h + 1]);
          }
      };
      smem_fence();
      named_sync(6, 256);
      OBS(tid == 224, 26);
      q_rest();
      named_sync(7, 256);
      wg_fence();
      scores(1);
      wg_commit();
      named_arrive_if(g1, 0, 256);
      wg_wait<2>();
      if (tid == 128) mbar_arrive(bars + B_EMPTY + 7 * 8);
      wg_wait<0>();
      q_pack();
      OBS(tid == 160, 10);
      softmax(1);
      OBS(tid == 160, 30);
      mbar_wait(bars + B_HALO, 0);
      OBS(tid == 160, 7);
      mbar_wait(bars + B_GATE, 0);
      wg_fence();
      scores(0);
      values(1);
      wg_wait<0>();
      OBS(tid == 160, 33);
      unsigned char* og = scr + O_OFF + rb * 2 * 57344 + hp * 7168 + w4 * 256 + lane * 4;
      auto put = [&](int T) {
#pragma unroll
        for (int n = 0; n < 14; n++) { stg32(og + T * 57344 + (n >> 1) * 1024 + (n & 1) * 128, Ob[T][n]); if (OSLEEP && n % OGRP == OGRP - 1) __nanosleep(OSLEEP); }
      };
      if (OMODE == 1) { pack(1); put(1); }
      softmax(0);
      if (OMODE == 2) { pack(1); put(1); }
      mbar_wait(bars + B_GATE + 8, 0);
      wg_fence();
      values(0);
      if (OMODE == 3) { pack(1); put(1); }
      wg_wait<0>();
      OBS(tid == 160, 35);
      named_sync(11, 128);
      if (tid == 160) mbar_arrive(bars + B_ATT);
      if (OMODE == 0) pack(1);
      pack(0);
      if (J3 > J2) mbar_wait(bars + B_GATE + 16, 0);
      if (OMODE == 0) put(1);
      put(0);
      named_sync(11, 128);
      if (warp == 4) publish(scr, C_O + rb);
      OBS(tid == 160, 8);
      setup_u(); setup_out();
      if (g1) take_h(0);
    }
    if (g1) {
#pragma unroll
      for (int j = 4; j < 16; j++) { gelu(j); if (GCH && j < 15 && (j - 3) % (GCH ? GCH : 1) == 0) fence_code(8 + j); }
      if (warp == 0) { named_sync(2, 256); publish(uc, C_U); OBS(tid == 0, 9); }
      else if (OPW && wg) named_sync(2, 256);
      else named_arrive(2, 256);
    }
    uint32_t Sv[16];
    auto gate = [&](int i) {
      uint32_t R[4];
#pragma unroll
      for (int q = 0; q < 4; q++) {
        const int j = i * 4 + q;
        const float h0 = hv[2 * j], h1 = hv[2 * j + 1];
        R[q] = hmul2(Sv[j], pack2(fmaf(h0, tanh_fast(h0), h0), fmaf(h1, tanh_fast(h1), h1)));
      }
      stsm4(ts + i * 640, R[0], R[1], R[2], R[3]);
    };
    auto leave = [&](int i) {
      __syncwarp();
      const uint4 v = lds128(tl + i * 640), x = Xr[i];
      stg128(i ? outp + (i - 1) * 64 : outq, hadd2(x.x, v.x), hadd2(x.y, v.y), hadd2(x.z, v.z), hadd2(x.w, v.w));
    };
    if (wg == 1) {
      float as[56];
      fresh(as);
      gemm_stage<0>(as, base, 0, 0);
      OBS(tid == 128, 22);
      gemm_loop<0>(as, base, 1, 7, rel, 104);
      wg_wait<0>();
      OBS(tid == 128, 23);
      if (rel) mbar_arrive(bars + B_EMPTY + 6 * 8);
      fresh(acc);
      if (SEARLY) { give(as, 3); get_x(); }
      gemm_stage<1>(acc, base, 7, 0);
      OBS(tid == 128, 24);
      if (!SEARLY) { give(as, 3); get_x(); }
#pragma unroll
      for (int j = 0; j < 16; j++) Sv[j] = pack2(as[ai(j)], as[ai(j) + 1]);
      gemm_loop<1>(acc, base, 8, 35, rel, 65);
      named_sync(10, 256);
      wg_wait<0>();
      OBS(tid == 128, 25);
      give(acc, 5);
      fence_code(31);
      keep_h(2);
      gate(0); leave(0);
    } else {
      setup_out();
      get_x();
      uint32_t r[12];
      take(r, 3);
#pragma unroll
      for (int j = 0; j < 16; j++) Sv[j] = r[j < 4 ? 0 : j - 4];
      asm volatile("" :: "r"(r[0]), "r"(r[11]) : "memory");
      named_arrive(10, 256);
      take_h(2);
    }
    {
#pragma unroll
      for (int i = 1; i < 4; i++) { gate(i); leave(i); }
      OBS(tid == 128, 27);
    }
  }
}

typedef CUresult (*EncFn)(CUtensorMap*, CUtensorMapDataType, cuuint32_t, void*, const cuuint64_t*, const cuuint64_t*, const cuuint32_t*,
                          const cuuint32_t*, CUtensorMapInterleave, CUtensorMapSwizzle, CUtensorMapL2promotion, CUtensorMapFloatOOBfill);
void enc(EncFn f, CUtensorMap* m, const void* ptr, cuuint64_t d0, cuuint64_t d1, cuuint64_t d2, cuuint64_t s1, cuuint64_t s2, cuuint32_t b1, cuuint32_t b2, cuuint32_t b0 = 64) {
  const cuuint64_t gd[3] = {d0, d1, d2}, gs[2] = {s1 * 2, s2 * 2};
  const cuuint32_t bx[3] = {b0, b1, b2}, es[3] = {1, 1, 1};
  f(m, CU_TENSOR_MAP_DATA_TYPE_BFLOAT16, 3, (void*)ptr, gd, gs, bx, es, CU_TENSOR_MAP_INTERLEAVE_NONE, b0 == 64 ? CU_TENSOR_MAP_SWIZZLE_128B : CU_TENSOR_MAP_SWIZZLE_NONE,
    CU_TENSOR_MAP_L2_PROMOTION_L2_128B, CU_TENSOR_MAP_FLOAT_OOB_FILL_NONE);
}
}

extern "C" void kernel_launch(void* const* d_in, const int* in_sizes, int n_in, void* d_out, int out_size) {
  (void)in_sizes; (void)n_in; (void)out_size;
  void* fp = nullptr;
  cudaDriverEntryPointQueryResult qr;
  cudaGetDriverEntryPoint("cuTensorMapEncodeTiled", &fp, cudaEnableDefault, &qr);
  EncFn f = (EncFn)fp;
  CUtensorMap m_x, m_wkv, m_wq, m_w1, m_w2, m_res;
  void* scr = nullptr;
  cudaGetSymbolAddress(&scr, g_scr);
  enc(f, &m_x, d_in[0], D_, S_, 1, D_, D_, 128, 1);
  enc(f, &m_wkv, d_in[1], D_, D_, 3, 3 * D_, D_, 64, 2);
  enc(f, &m_wq, d_in[1], D_, D_, 3, 3 * D_, D_, 224, 1);
  enc(f, &m_w1, d_in[4], F_, S_, 1, F_, F_, 64, 1);
  enc(f, &m_w2, d_in[6], S_, F_, 1, S_, S_, 64, 1);
  enc(f, &m_res, d_in[0], D_, S_, 1, D_, D_, 64, 1, 112);
  Params p;
  p.wo = (const unsigned char*)d_in[2];
  p.w1 = (const unsigned char*)d_in[4]; p.b1 = (const unsigned char*)d_in[5];
  p.w2 = (const unsigned char*)d_in[6]; p.b2 = (const unsigned char*)d_in[7];
  p.out = (unsigned char*)d_out; p.scr = (unsigned char*)scr;
  cudaFuncSetAttribute(fused_kernel, cudaFuncAttributeMaxDynamicSharedMemorySize, SMEM_BYTES);
  fused_kernel<<<128, NTHREADS, SMEM_BYTES, cudaStreamPerThread>>>(m_x, m_wkv, m_wq, m_w1, m_w2, m_res, p);
}
```

```cpp
#include <cuda_runtime.h>
#include <cuda.h>
#include <cuda_bf16.h>
#include <stdint.h>

template<int TA, int TB> __device__ __forceinline__ void wgmma_n112(float (&d)[56], uint64_t da, uint64_t db, int sc) {
  asm volatile("{\n.reg .pred p;\nsetp.ne.b32 p, %58, 0;\n"
    "wgmma.mma_async.sync.aligned.m64n112k16.f32.bf16.bf16 {%0, %1, %2, %3, %4, %5, %6, %7, %8, %9, %10, %11, %12, %13, %14, %15, %16, %17, %18, %19, %20, %21, %22, %23, %24, %25, %26, %27, %28, %29, %30, %31, %32, %33, %34, %35, %36, %37, %38, %39, %40, %41, %42, %43, %44, %45, %46, %47, %48, %49, %50, %51, %52, %53, %54, %55}, %56, %57, p, 1, 1, %59, %60;\n}\n"
    : "+f"(d[0]), "+f"(d[1]), "+f"(d[2]), "+f"(d[3]), "+f"(d[4]), "+f"(d[5]), "+f"(d[6]), "+f"(d[7]), "+f"(d[8]), "+f"(d[9]), "+f"(d[10]), "+f"(d[11]), "+f"(d[12]), "+f"(d[13]), "+f"(d[14]), "+f"(d[15]), "+f"(d[16]), "+f"(d[17]), "+f"(d[18]), "+f"(d[19]), "+f"(d[20]), "+f"(d[21]), "+f"(d[22]), "+f"(d[23]), "+f"(d[24]), "+f"(d[25]), "+f"(d[26]), "+f"(d[27]), "+f"(d[28]), "+f"(d[29]), "+f"(d[30]), "+f"(d[31]), "+f"(d[32]), "+f"(d[33]), "+f"(d[34]), "+f"(d[35]), "+f"(d[36]), "+f"(d[37]), "+f"(d[38]), "+f"(d[39]), "+f"(d[40]), "+f"(d[41]), "+f"(d[42]), "+f"(d[43]), "+f"(d[44]), "+f"(d[45]), "+f"(d[46]), "+f"(d[47]), "+f"(d[48]), "+f"(d[49]), "+f"(d[50]), "+f"(d[51]), "+f"(d[52]), "+f"(d[53]), "+f"(d[54]), "+f"(d[55])
    : "l"(da), "l"(db), "r"(sc), "n"(TA), "n"(TB));
}

template<int TA, int TB> __device__ __forceinline__ void wgmma_n80(float (&d)[40], uint64_t da, uint64_t db, int sc) {
  asm volatile("{\n.reg .pred p;\nsetp.ne.b32 p, %42, 0;\n"
    "wgmma.mma_async.sync.aligned.m64n80k16.f32.bf16.bf16 {%0, %1, %2, %3, %4, %5, %6, %7, %8, %9, %10, %11, %12, %13, %14, %15, %16, %17, %18, %19, %20, %21, %22, %23, %24, %25, %26, %27, %28, %29, %30, %31, %32, %33, %34, %35, %36, %37, %38, %39}, %40, %41, p, 1, 1, %43, %44;\n}\n"
    : "+f"(d[0]), "+f"(d[1]), "+f"(d[2]), "+f"(d[3]), "+f"(d[4]), "+f"(d[5]), "+f"(d[6]), "+f"(d[7]), "+f"(d[8]), "+f"(d[9]), "+f"(d[10]), "+f"(d[11]), "+f"(d[12]), "+f"(d[13]), "+f"(d[14]), "+f"(d[15]), "+f"(d[16]), "+f"(d[17]), "+f"(d[18]), "+f"(d[19]), "+f"(d[20]), "+f"(d[21]), "+f"(d[22]), "+f"(d[23]), "+f"(d[24]), "+f"(d[25]), "+f"(d[26]), "+f"(d[27]), "+f"(d[28]), "+f"(d[29]), "+f"(d[30]), "+f"(d[31]), "+f"(d[32]), "+f"(d[33]), "+f"(d[34]), "+f"(d[35]), "+f"(d[36]), "+f"(d[37]), "+f"(d[38]), "+f"(d[39])
    : "l"(da), "l"(db), "r"(sc), "n"(TA), "n"(TB));
}

template<int TB> __device__ __forceinline__ void wgmma_rs_n120(float (&d)[60], const uint32_t (&a)[4], uint64_t db, int sc) {
  asm volatile("{\n.reg .pred p;\nsetp.ne.b32 p, %65, 0;\n"
    "wgmma.mma_async.sync.aligned.m64n120k16.f32.bf16.bf16 {%0, %1, %2, %3, %4, %5, %6, %7, %8, %9, %10, %11, %12, %13, %14, %15, %16, %17, %18, %19, %20, %21, %22, %23, %24, %25, %26, %27, %28, %29, %30, %31, %32, %33, %34, %35, %36, %37, %38, %39, %40, %41, %42, %43, %44, %45, %46, %47, %48, %49, %50, %51, %52, %53, %54, %55, %56, %57, %58, %59}, {%60, %61, %62, %63}, %64, p, 1, 1, %66;\n}\n"
    : "+f"(d[0]), "+f"(d[1]), "+f"(d[2]), "+f"(d[3]), "+f"(d[4]), "+f"(d[5]), "+f"(d[6]), "+f"(d[7]), "+f"(d[8]), "+f"(d[9]), "+f"(d[10]), "+f"(d[11]), "+f"(d[12]), "+f"(d[13]), "+f"(d[14]), "+f"(d[15]), "+f"(d[16]), "+f"(d[17]), "+f"(d[18]), "+f"(d[19]), "+f"(d[20]), "+f"(d[21]), "+f"(d[22]), "+f"(d[23]), "+f"(d[24]), "+f"(d[25]), "+f"(d[26]), "+f"(d[27]), "+f"(d[28]), "+f"(d[29]), "+f"(d[30]), "+f"(d[31]), "+f"(d[32]), "+f"(d[33]), "+f"(d[34]), "+f"(d[35]), "+f"(d[36]), "+f"(d[37]), "+f"(d[38]), "+f"(d[39]), "+f"(d[40]), "+f"(d[41]), "+f"(d[42]), "+f"(d[43]), "+f"(d[44]), "+f"(d[45]), "+f"(d[46]), "+f"(d[47]), "+f"(d[48]), "+f"(d[49]), "+f"(d[50]), "+f"(d[51]), "+f"(d[52]), "+f"(d[53]), "+f"(d[54]), "+f"(d[55]), "+f"(d[56]), "+f"(d[57]), "+f"(d[58]), "+f"(d[59])
    : "r"(a[0]), "r"(a[1]), "r"(a[2]), "r"(a[3]), "l"(db), "r"(sc), "n"(TB));
}

template<int TB> __device__ __forceinline__ void wgmma_rs_n56(float (&d)[28], const uint32_t (&a)[4], uint64_t db, int sc) {
  asm volatile("{\n.reg .pred p;\nsetp.ne.b32 p, %33, 0;\n"
    "wgmma.mma_async.sync.aligned.m64n56k16.f32.bf16.bf16 {%0, %1, %2, %3, %4, %5, %6, %7, %8, %9, %10, %11, %12, %13, %14, %15, %16, %17, %18, %19, %20, %21, %22, %23, %24, %25, %26, %27}, {%28, %29, %30, %31}, %32, p, 1, 1, %34;\n}\n"
    : "+f"(d[0]), "+f"(d[1]), "+f"(d[2]), "+f"(d[3]), "+f"(d[4]), "+f"(d[5]), "+f"(d[6]), "+f"(d[7]), "+f"(d[8]), "+f"(d[9]), "+f"(d[10]), "+f"(d[11]), "+f"(d[12]), "+f"(d[13]), "+f"(d[14]), "+f"(d[15]), "+f"(d[16]), "+f"(d[17]), "+f"(d[18]), "+f"(d[19]), "+f"(d[20]), "+f"(d[21]), "+f"(d[22]), "+f"(d[23]), "+f"(d[24]), "+f"(d[25]), "+f"(d[26]), "+f"(d[27])
    : "r"(a[0]), "r"(a[1]), "r"(a[2]), "r"(a[3]), "l"(db), "r"(sc), "n"(TB));
}

template<int TB> __device__ __forceinline__ void wgmma_rs_n32(float (&d)[16], const uint32_t (&a)[4], uint64_t db, int sc) {
  asm volatile("{\n.reg .pred p;\nsetp.ne.b32 p, %21, 0;\n"
    "wgmma.mma_async.sync.aligned.m64n32k16.f32.bf16.bf16 {%0, %1, %2, %3, %4, %5, %6, %7, %8, %9, %10, %11, %12, %13, %14, %15}, {%16, %17, %18, %19}, %20, p, 1, 1, %22;\n}\n"
    : "+f"(d[0]), "+f"(d[1]), "+f"(d[2]), "+f"(d[3]), "+f"(d[4]), "+f"(d[5]), "+f"(d[6]), "+f"(d[7]), "+f"(d[8]), "+f"(d[9]), "+f"(d[10]), "+f"(d[11]), "+f"(d[12]), "+f"(d[13]), "+f"(d[14]), "+f"(d[15])
    : "r"(a[0]), "r"(a[1]), "r"(a[2]), "r"(a[3]), "l"(db), "r"(sc), "n"(TB));
}

template<int TB> __device__ __forceinline__ void wgmma_rs_n80(float (&d)[40], const uint32_t (&a)[4], uint64_t db, int sc) {
  asm volatile("{\n.reg .pred p;\nsetp.ne.b32 p, %45, 0;\n"
    "wgmma.mma_async.sync.aligned.m64n80k16.f32.bf16.bf16 {%0, %1, %2, %3, %4, %5, %6, %7, %8, %9, %10, %11, %12, %13, %14, %15, %16, %17, %18, %19, %20, %21, %22, %23, %24, %25, %26, %27, %28, %29, %30, %31, %32, %33, %34, %35, %36, %37, %38, %39}, {%40, %41, %42, %43}, %44, p, 1, 1, %46;\n}\n"
    : "+f"(d[0]), "+f"(d[1]), "+f"(d[2]), "+f"(d[3]), "+f"(d[4]), "+f"(d[5]), "+f"(d[6]), "+f"(d[7]), "+f"(d[8]), "+f"(d[9]), "+f"(d[10]), "+f"(d[11]), "+f"(d[12]), "+f"(d[13]), "+f"(d[14]), "+f"(d[15]), "+f"(d[16]), "+f"(d[17]), "+f"(d[18]), "+f"(d[19]), "+f"(d[20]), "+f"(d[21]), "+f"(d[22]), "+f"(d[23]), "+f"(d[24]), "+f"(d[25]), "+f"(d[26]), "+f"(d[27]), "+f"(d[28]), "+f"(d[29]), "+f"(d[30]), "+f"(d[31]), "+f"(d[32]), "+f"(d[33]), "+f"(d[34]), "+f"(d[35]), "+f"(d[36]), "+f"(d[37]), "+f"(d[38]), "+f"(d[39])
    : "r"(a[0]), "r"(a[1]), "r"(a[2]), "r"(a[3]), "l"(db), "r"(sc), "n"(TB));
}

namespace {
constexpr int S_ = 2048, D_ = 448, F_ = 1792;
constexpr int NSLOT = 8, SLOT = 22528;
constexpr int OFF_X = 7 * 16384;
constexpr int OFF_WQ = 8 * 16384;
constexpr int OFF_Q = NSLOT * SLOT;
constexpr int OFF_K = OFF_Q + 16384;
constexpr int OFF_XW = OFF_K + 6144;
constexpr int OFF_BAR = 14 * 16384;
constexpr int OFF_LN = OFF_BAR + 512;
constexpr int OFF_OBS = OFF_BAR + 640;
constexpr int SMEM_BYTES = OFF_OBS + 1024;
#define PACE0 0
#define PACE1 540
#define PACE2 650
#define WARM 3
#define NW0 2
#define HEAT 1
#define T0 0
#define TP 250
#define J3 0
#define J1 9
#define J2 14
#define EARLY 4
#define PPE 4
#define PQE 2
#define LANDOBS 0
#define TRUNC 0
#define KOBS 0
#define PRE 1
#define QA 2
#define HEARLY 0
#define OSLEEP 20
#define PROBE 1
#define WOP 0
#define OGRP 2
#define OMODE 3
#define GCH 4
#define GLAG 2
#define GSLOW 0
#define RH 32
#define NOST 0
#define GOBS 0
#define HP 0
#define OPP 0
#define STAG 0
#define RESP 0
#define XE 1
#define NX 0
#define XS 15
#define XT 9
#define NPRE 1
#define U0 0
#define ALL4 0
#define UREP 1
#define TS 0
#define PPM 1
#define WPF 1
#define XSPLIT 1
#define XK 1
#define MU 0
#define P2 224
#define UP 170
#define POLL "relaxed"
#define OPJ 16
#define SEARLY 1
#define EXACT 0
#define SOBS 0
#define FREQ 0
#define OBS(c, i) do {} while (0)
#define OBSG(c, i, j) do {} while (0)
constexpr int NTHREADS = 384;
constexpr float SCALE = 0.18898223650461361f, LOG2E = 1.4426950408889634f;
constexpr int BT = 14336;

constexpr int HU_T = 67;
constexpr int O_OFF = 4 * HU_T * BT;
constexpr int HALO_OFF = O_OFF + 32 * 7 * 8192;
constexpr int CNT_OFF = HALO_OFF + 128 * 3584;
constexpr int SCR_BYTES = CNT_OFF + 192 * 128;
constexpr int C_WO = 0, C_TK = 1, C_U = 160, C_O = 8, C_H = 24, C_HALO = 32;
__device__ __align__(1024) unsigned char g_scr[SCR_BYTES];

__device__ __forceinline__ uint32_t smem_u32(const void* p) { return (uint32_t)__cvta_generic_to_shared(p); }
__device__ __forceinline__ void mbar_init(uint32_t bar, uint32_t cnt) { asm volatile("mbarrier.init.shared::cta.b64 [%0], %1;" :: "r"(bar), "r"(cnt)); }
__device__ __forceinline__ void mbar_expect_tx(uint32_t bar, uint32_t bytes) { asm volatile("mbarrier.arrive.expect_tx.shared::cta.b64 _, [%0], %1;" :: "r"(bar), "r"(bytes) : "memory"); }
__device__ __forceinline__ void mbar_arrive_if(uint32_t c, uint32_t bar) { asm volatile("{\n.reg .pred q;\nsetp.ne.u32 q, %1, 0;\n@q mbarrier.arrive.shared::cta.b64 _, [%0];\n}" :: "r"(bar), "r"(c) : "memory"); }
__device__ __forceinline__ void mbar_arrive(uint32_t bar) { asm volatile("mbarrier.arrive.shared::cta.b64 _, [%0];" :: "r"(bar) : "memory"); }
__device__ __forceinline__ void mbar_wait(uint32_t bar, uint32_t parity) {
  asm volatile("{\n.reg .pred p;\n.reg .u32 n;\nmov.u32 n, 0;\nLAB_WAIT:\n"
               "mbarrier.try_wait.parity.shared::cta.b64 p, [%0], %1;\n@p bra DONE;\n"
               "add.u32 n, n, 1;\nsetp.lt.u32 p, n, 400000;\n@p bra LAB_WAIT;\ntrap;\nDONE:\n}" :: "r"(bar), "r"(parity) : "memory");
}
__device__ __forceinline__ uint32_t mbar_try(uint32_t bar, uint32_t parity) {
  uint32_t ok;
  asm volatile("{\n.reg .pred p;\nmbarrier.test_wait.parity.shared::cta.b64 p, [%1], %2;\nselp.u32 %0, 1, 0, p;\n}" : "=r"(ok) : "r"(bar), "r"(parity) : "memory");
  return ok;
}
__device__ __forceinline__ void tma3d(uint32_t dst, const CUtensorMap* m, int c0, int c1, int c2, uint32_t bar) {
  asm volatile("cp.async.bulk.tensor.3d.shared::cluster.global.mbarrier::complete_tx::bytes [%0], [%1, {%3, %4, %5}], [%2];"
               :: "r"(dst), "l"(m), "r"(bar), "r"(c0), "r"(c1), "r"(c2) : "memory");
}
__device__ __forceinline__ void bulk_g2s(uint32_t dst, const void* src, uint32_t bytes, uint32_t bar) {
  asm volatile("cp.async.bulk.shared::cluster.global.mbarrier::complete_tx::bytes [%0], [%1], %2, [%3];" :: "r"(dst), "l"(src), "r"(bytes), "r"(bar) : "memory");
}
__device__ __forceinline__ void wg_fence() { asm volatile("wgmma.fence.sync.aligned;" ::: "memory"); }
__device__ __forceinline__ void wg_commit() { asm volatile("wgmma.commit_group.sync.aligned;" ::: "memory"); }
template <int N> __device__ __forceinline__ void wg_wait() { asm volatile("wgmma.wait_group.sync.aligned %0;" :: "n"(N) : "memory"); }
__device__ __forceinline__ void smem_fence() { asm volatile("fence.proxy.async.shared::cta;" ::: "memory"); }
__device__ __forceinline__ void stg128(void* p, uint32_t a, uint32_t b, uint32_t c, uint32_t d) { asm volatile("st.global.v4.u32 [%0], {%1,%2,%3,%4};" :: "l"(p), "r"(a), "r"(b), "r"(c), "r"(d) : "memory"); }
__device__ __forceinline__ void stg32(void* p, uint32_t v) { asm volatile("st.global.u32 [%0], %1;" :: "l"(p), "r"(v) : "memory"); }
__device__ __forceinline__ uint4 ldg128(const void* p) { uint4 v; asm volatile("ld.global.nc.L1::no_allocate.v4.u32 {%0,%1,%2,%3}, [%4];" : "=r"(v.x), "=r"(v.y), "=r"(v.z), "=r"(v.w) : "l"(p)); return v; }
__device__ __forceinline__ void publish(unsigned char* scr, int i) {
  asm volatile("{\n.reg .pred q;\nelect.sync _|q, 0xffffffff;\n@q red.relaxed.gpu.global.inc.u32 [%0], 0xffffffff;\n}" :: "l"(scr + CNT_OFF + i * 128) : "memory");
}
__device__ __forceinline__ void spin_ge(unsigned char* scr, int i, unsigned target) {
  asm volatile("{\n.reg .pred p;\n.reg .u32 n, v;\nmov.u32 n, 0;\nLAB_SPIN:\n"
               "ld." POLL ".gpu.global.u32 v, [%0];\nsetp.ge.u32 p, v, %1;\nvote.sync.all.pred p, p, 0xffffffff;\n@p bra DONE;\n"
               "add.u32 n, n, 1;\nsetp.lt.u32 p, n, 4000000;\n@p bra LAB_SPIN;\ntrap;\nDONE:\n}" :: "l"(scr + CNT_OFF + i * 128), "r"(target) : "memory");
}
__device__ __forceinline__ int lane_id() { int l; asm volatile("mov.u32 %0, %%laneid;" : "=r"(l)); return l; }
__device__ __forceinline__ uint32_t pin(uint32_t v) { return __shfl_xor_sync(0xffffffffu, v, blockIdx.y); }
__device__ __forceinline__ unsigned char* pin(unsigned char* p) { return (unsigned char*)(((uint64_t)pin((uint32_t)((uint64_t)p >> 32)) << 32) | pin((uint32_t)(uint64_t)p)); }
__device__ __forceinline__ bool elect() {
  uint32_t r; asm volatile("{\n.reg .pred p;\nelect.sync _|p, 0xffffffff;\nselp.u32 %0, 1, 0, p;\n}" : "=r"(r)); return r != 0;
}
__device__ __forceinline__ uint4 lds128(uint32_t a) { uint4 v; asm volatile("ld.shared.v4.u32 {%0,%1,%2,%3}, [%4];" : "=r"(v.x), "=r"(v.y), "=r"(v.z), "=r"(v.w) : "r"(a) : "memory"); return v; }
__device__ __forceinline__ uint2 lds64(uint32_t a) { uint2 v; asm volatile("ld.shared.v2.u32 {%0,%1}, [%2];" : "=r"(v.x), "=r"(v.y) : "r"(a) : "memory"); return v; }
__device__ __forceinline__ void sts128(uint32_t p, uint32_t a, uint32_t b, uint32_t c, uint32_t d) { asm volatile("st.shared.v4.u32 [%0], {%1,%2,%3,%4};" :: "r"(p), "r"(a), "r"(b), "r"(c), "r"(d) : "memory"); }
__device__ __forceinline__ void sts32(uint32_t a, float v) { asm volatile("st.shared.f32 [%0], %1;" :: "r"(a), "f"(v) : "memory"); }
__device__ __forceinline__ void named_sync(int id, int n) { asm volatile("bar.sync %0, %1;" :: "r"(id), "r"(n) : "memory"); }
__device__ __forceinline__ void named_arrive(int id, int n) { asm volatile("bar.arrive %0, %1;" :: "r"(id), "r"(n) : "memory"); }
__device__ __forceinline__ void named_arrive_if(uint32_t c, int id, int n) { asm volatile("{\n.reg .pred q;\nsetp.ne.u32 q, %2, 0;\n@q bar.arrive %0, %1;\n}" :: "r"(id), "r"(n), "r"(c) : "memory"); }
__device__ __forceinline__ uint64_t mkdesc(uint32_t hi, uint32_t lo) { return ((uint64_t)hi << 32) | lo; }
constexpr uint32_t HI_SW128 = 0x40000040u;
__device__ __forceinline__ uint32_t pack2(float lo, float hi) { uint32_t r; asm("cvt.rn.bf16x2.f32 %0, %1, %2;" : "=r"(r) : "f"(hi), "f"(lo)); return r; }
__device__ __forceinline__ float bf_lo(uint32_t v) { return __uint_as_float(v << 16); }
__device__ __forceinline__ float bf_hi(uint32_t v) { return __uint_as_float(v & 0xffff0000u); }
__device__ __forceinline__ float rbf(float x) { return bf_lo(pack2(x, 0.f)); }
__device__ __forceinline__ uint32_t hsub2(uint32_t a, uint32_t b) { uint32_t r; asm("sub.rn.bf16x2 %0, %1, %2;" : "=r"(r) : "r"(a), "r"(b)); return r; }
__device__ __forceinline__ uint32_t hadd2(uint32_t a, uint32_t b) { uint32_t r; asm("add.rn.bf16x2 %0, %1, %2;" : "=r"(r) : "r"(a), "r"(b)); return r; }
__device__ __forceinline__ uint32_t hmul2(uint32_t a, uint32_t b) { uint32_t r; asm("mul.rn.bf16x2 %0, %1, %2;" : "=r"(r) : "r"(a), "r"(b)); return r; }
__device__ __forceinline__ uint32_t hfma2(uint32_t a, uint32_t b, uint32_t c) { uint32_t r; asm("fma.rn.bf16x2 %0, %1, %2, %3;" : "=r"(r) : "r"(a), "r"(b), "r"(c)); return r; }
__device__ __forceinline__ float tanh_fast(float x) { float r; asm("tanh.approx.f32 %0, %1;" : "=f"(r) : "f"(x)); return r; }
__device__ __forceinline__ float rcp_fast(float x) { float r; asm("rcp.approx.ftz.f32 %0, %1;" : "=f"(r) : "f"(x)); return r; }
__device__ __forceinline__ float ex2_fast(float x) { float r; asm("ex2.approx.ftz.f32 %0, %1;" : "=f"(r) : "f"(x)); return r; }
__device__ __forceinline__ void mma16816(float (&c)[4], uint32_t a0, uint32_t a1, uint32_t a2, uint32_t a3, uint32_t b0, uint32_t b1) {
  asm volatile("mma.sync.aligned.m16n8k16.row.col.f32.bf16.bf16.f32 {%0,%1,%2,%3}, {%4,%5,%6,%7}, {%8,%9}, {%0,%1,%2,%3};"
               : "+f"(c[0]), "+f"(c[1]), "+f"(c[2]), "+f"(c[3]) : "r"(a0), "r"(a1), "r"(a2), "r"(a3), "r"(b0), "r"(b1));
}
__device__ __forceinline__ void ldsm4(uint32_t (&r)[4], uint32_t addr) {
  asm volatile("ldmatrix.sync.aligned.m8n8.x4.shared.b16 {%0,%1,%2,%3}, [%4];" : "=r"(r[0]), "=r"(r[1]), "=r"(r[2]), "=r"(r[3]) : "r"(addr) : "memory");
}
__device__ __forceinline__ void stsm4(uint32_t addr, uint32_t a, uint32_t b, uint32_t c, uint32_t d) {
  asm volatile("stmatrix.sync.aligned.m8n8.x4.shared.b16 [%0], {%1,%2,%3,%4};" :: "r"(addr), "r"(a), "r"(b), "r"(c), "r"(d) : "memory");
}

__device__ __forceinline__ float ln_rstd(float var, float eps = 1e-5f) {
  float sd;
  asm("sqrt.approx.ftz.f32 %0, %1;" : "=f"(sd) : "f"(rbf(rbf(var) + eps)));
  return rcp_fast(rbf(sd));
}
__device__ __forceinline__ float ln_var(float mean, float sq) { return fmaxf(fmaf(-mean, mean, sq * (1.0f / D_)), 0.f); }
struct LnC { uint32_t m, rh, rl; };
__device__ __forceinline__ LnC ln_consts(float sum, float sq, float eps) {
  const float mean = sum * (1.0f / D_), r = ln_rstd(ln_var(mean, sq), eps), rh = rbf(r);
  LnC c; c.m = pack2(mean, mean); c.rh = pack2(rh, rh); c.rl = pack2(r - rh, r - rh);
  return c;
}
__device__ __forceinline__ uint32_t ln_apply(uint32_t x, const LnC& c) {
  uint32_t d = hsub2(x, c.m);
  return hfma2(d, c.rh, hmul2(d, c.rl));
}

__device__ __forceinline__ void fence_code(int id) {
  asm volatile("{\n.reg .pred q;\nLAB_F:\nsetp.eq.u32 q, %0, %1;\n@q st.volatile.shared.u32 [%2], %2;\n@q bra LAB_F;\n}" :: "r"(blockIdx.x), "r"(0x70000000 + id), "r"(0) : "memory");
}
template <int N> __device__ __forceinline__ void fresh(float (&a)[N]) {
#pragma unroll
  for (int i = 0; i < N; i++) asm volatile("" : "=f"(a[i]));
}
constexpr int B_EMPTY = 64, B_X = 384, B_KV = 192, B_WQ = 248, B_HALO = 256, B_RES = 264, B_ATT = 272, B_GATE = 280, B_WO = 304, B_O = 312, B_XW = 320, B_WQ2 = 328, B_T0 = 336;

template <int TA>
__device__ __forceinline__ void gemm_issue(float (&acc)[56], uint32_t la, uint32_t lo, int sc) {
  wg_fence();
#pragma unroll
  for (int k = 0; k < 4; k++)
    wgmma_n112<TA, 1>(acc, mkdesc(TA ? HI_SW128 : 8, la + (TA ? 512u << 16 : 64u << 16) + k * 128), mkdesc(8, lo + (112u << 16) + 512 + k * 224), sc | k);
  wg_commit();
}
template <int TA>
__device__ __forceinline__ void gemm_stage(float (&acc)[56], uint32_t base, int it, int sc) {
  mbar_wait(base + OFF_BAR + (it & 7) * 8, (it >> 3) & 1);
  const uint32_t lo = (base >> 4) + (it & 7) * (SLOT >> 4);
  gemm_issue<TA>(acc, lo, lo, sc);
}
template <int TA, int EXTRA = 0>
__device__ __forceinline__ void gemm_loop(float (&acc)[56], uint32_t base, int it, int end, bool rel, int oi, uint32_t ok = 0, int gate_it = -1, uint32_t gate = 0) {
#pragma unroll 1
  for (; it < end;) {
    if (__builtin_expect(!ok, 0)) mbar_wait(base + OFF_BAR + (it & 7) * 8, (it >> 3) & 1);
    const uint32_t lo = (base >> 4) + (it & 7) * (SLOT >> 4);
    gemm_issue<TA>(acc, (unsigned)(it - XS) < EXTRA ? ((base + OFF_XW) >> 4) + (it - XS) * 512 : lo, lo, 1);
    OBS(SOBS && rel, oi + it);
    it++;
    ok = mbar_try(base + OFF_BAR + (it & 7) * 8, (it >> 3) & 1);
    wg_wait<1>();
    if (rel || it == gate_it) mbar_arrive(rel ? base + OFF_BAR + B_EMPTY + ((it - 2) & 7) * 8 : gate);
  }
}
template <int PER>
__device__ __forceinline__ void produce_box(uint32_t base, int it, int end, const CUtensorMap* mp, int c0, int c1, uint32_t tn = 0) {
#pragma unroll 1
  for (; it < end; it++) {
    const uint32_t fb = base + OFF_BAR + (it & 7) * 8;
    mbar_wait(fb + B_EMPTY, (it >> 3) & 1);
    if (PER) { while ((int)(clock() - tn) < 0); tn += PER; }
    if (elect()) { mbar_expect_tx(fb, 8192); tma3d(base + (it & 7) * SLOT, mp, c0, c1, 0, fb); }
    c1 += 64;
  }
}
template <int PER>
__device__ __forceinline__ void produce_lin(uint32_t base, int it, int end, const unsigned char* src, uint32_t bytes, uint32_t tn = 0) {
#pragma unroll 1
  for (; it < end; it++) {
    const uint32_t fb = base + OFF_BAR + (it & 7) * 8;
    mbar_wait(fb + B_EMPTY, (it >> 3) & 1);
    if (PER) { while ((int)(clock() - tn) < 0); tn += PER; }
    if (elect()) { mbar_expect_tx(fb, bytes); bulk_g2s(base + (it & 7) * SLOT + (bytes & 2048) * 4, src, bytes, fb); }
    src += bytes;
  }
}

__device__ __forceinline__ void retile_wo(const unsigned char* wo, unsigned char* scr, int u, int lane) {
  const int r8 = lane & 7, mi = lane >> 3;
  const unsigned char* src = wo + ((u >> 1) * 8 + r8) * 896 + ((u & 1) * 28 + mi) * 16;
  unsigned char* dst = scr + ((u & 1) * 2 * HU_T + 60 + (u >> 4)) * BT + ((u >> 1) & 7) * 1792 + mi * 128 + r8 * 16;
  uint4 v[7];
#pragma unroll
  for (int i = 0; i < 7; i++) v[i] = ldg128(src + i * 64);
#pragma unroll
  for (int i = 0; i < 7; i++) stg128(dst + i * 512 + ((i * 4 + mi) / 14) * (HU_T * BT - 1792), v[i].x, v[i].y, v[i].z, v[i].w);
  publish(scr, C_WO);
}

struct Params {
  const unsigned char *wqkv, *wo, *w1, *b1, *w2, *b2;
  unsigned char *out, *scr;
};

__global__ void __launch_bounds__(NTHREADS, 1)
fused_kernel(const __grid_constant__ CUtensorMap m_x, const __grid_constant__ CUtensorMap m_wkv, const __grid_constant__ CUtensorMap m_wq,
             const __grid_constant__ CUtensorMap m_w1, const __grid_constant__ CUtensorMap m_w2, const __grid_constant__ CUtensorMap m_res, const Params p) {
  extern __shared__ __align__(1024) unsigned char smem_raw[];
  constexpr uint32_t base = 1024, bars = base + OFF_BAR;
  const int tid = threadIdx.x, lane = tid & 31, b = blockIdx.x;
  const int rb = (b >> 2) & 15, hp = ((b >> 6) << 2) | (b & 3);
  const int wcol = hp * 56 - (hp & 1) * 8;
  auto load_kv = [&](int s) { mbar_expect_tx(bars + B_KV + s * 8, 16384); tma3d(base + s * 16384, &m_wkv, wcol, s * 64, 1, bars + B_KV + s * 8); };
  if (tid < 32) {
    if (elect()) {
#pragma unroll
      for (int i = 0; i < 7; i++) mbar_init(bars + B_X + i * 8, 1);
      asm volatile("fence.mbarrier_init.release.cluster;" ::: "memory");
#pragma unroll
      for (int i = 0; i < 7; i++) { mbar_expect_tx(bars + B_X + i * 8, 16384 >> XSPLIT); tma3d(base + OFF_X + i * 16384 + XSPLIT * 8192, &m_x, i * 64, rb * 128 + XSPLIT * 64, 0, bars + B_X + i * 8); }
#pragma unroll
      for (int i = 0; i < 7; i++) { mbar_init(bars + B_KV + i * 8, 1); if (XSPLIT) mbar_init(bars + B_X + 64 + i * 8, 1); }
      asm volatile("fence.mbarrier_init.release.cluster;" ::: "memory");
      if (XSPLIT) {
#pragma unroll
        for (int i = 0; i < XK; i++) load_kv(i);
#pragma unroll
        for (int i = 0; i < 7; i++) { mbar_expect_tx(bars + B_X + 64 + i * 8, 8192); tma3d(base + OFF_X + i * 16384, &m_x, i * 64, rb * 128, 0, bars + B_X + 64 + i * 8); }
      }
#pragma unroll 1
      for (int i = XSPLIT * XK; i < NW0; i++) load_kv(i);
    }
  }
  const int warp = __shfl_sync(0xffffffffu, tid >> 5, 0);
  if (TS && tid == 64) sts32(bars + B_T0, __uint_as_float(clock() + TS));
  if (warp == 1) {
    if (elect()) {
#pragma unroll
      for (int i = 0; i < 16; i++) mbar_init(bars + i * 8, 2);
#pragma unroll
      for (int i = 0; i < 11; i++) mbar_init(bars + B_WQ + i * 8, 1);
      asm volatile("fence.mbarrier_init.release.cluster;" ::: "memory");
      if (smem_u32(smem_raw) != base) asm volatile("trap;");
    }
  }
  const int dt = b & 3, mt = b >> 2;
  const bool g1 = (b & 15) < 14;
  const int a1 = b - 2 * (b >> 4), ft = a1 >> 2, d1 = a1 & 3;
  const int g = lane >> 2, t = lane & 3, r8 = lane & 7, mi = lane >> 3;
  OBSG(FREQ && tid == 160, 128, 160);
  __syncthreads();
  if (warp >= 8) {
    asm volatile("setmaxnreg.dec.sync.aligned.u32 40;");
    const int pw = warp - 8;
    unsigned char* scr = p.scr;
    if (WPF && pw == 2) {
      mbar_wait(bars + B_X + (WPF - 1) * 8, 0);
      if (b < 112 && lane < 28) asm volatile("prefetch.global.L2 [%0];" :: "l"(p.wqkv + (b * 4 + lane / 7) * 2688 + (lane % 7) * 128) : "memory");
      if (lane == 31) asm volatile("prefetch.tensormap [%0];" :: "l"(&m_wq) : "memory");
      __syncwarp();
    }
    if (NW0 < 7 && pw == 3) {
      mbar_wait(bars + B_X, 0);
      if (elect()) {
#pragma unroll 1
        for (int i = NW0; i < 7; i++) load_kv(i);
      }
      __syncwarp();
    }
    {
      const int c0 = pw * 14 + (mi >> 1);
      unsigned char* dst = scr + (pw * HU_T + rb * 2 + (hp >> 2)) * BT + ((hp & 3) * 2 + (mi & 1)) * 1792 + (mi >> 1) * 128 + r8 * 16;
      const uint32_t xs = base + OFF_X + (hp * 16 + (lane & 15)) * 128;
      uint4 H[7];
      named_sync(9, 160);
#pragma unroll
      for (int i = 0; i < 7; i++) H[i] = lds128(xs + ((c0 + 2 * i) >> 3) * 16384 + ((((c0 + 2 * i) & 7) ^ r8) << 4));
      asm volatile("" :: "r"(H[6].w), "r"(H[0].x) : "memory");
      if (pw != 3) named_arrive(8, 384);
      else {
        named_sync(8, 384);
        if (elect()) {
          mbar_expect_tx(bars + B_WQ, 28672); tma3d(base + OFF_WQ, &m_wq, wcol, 0, 0, bars + B_WQ);
          mbar_expect_tx(bars + B_WQ2, 28672); tma3d(base + OFF_WQ + 28672, &m_wq, wcol, 224, 0, bars + B_WQ2);
        }
        __syncwarp();
      }
      const uint2 st = lds64(base + OFF_LN + (lane & 15) * 8);
      const float sum = __uint_as_float(st.x), mean = sum * (1.0f / D_), var = ln_var(mean, __uint_as_float(st.y));
      const float m = rbf(mean), r = ln_rstd(var), r2 = ln_rstd(var * r * r);
      const float nc = fmaf(m, (float)D_, -sum) * (1.0f / D_) * (r * r2);
      const uint32_t m2 = pack2(m, m), r2x = pack2(r * r2, r * r2), nc2 = pack2(nc, nc);
      auto f = [&](uint32_t v) { return hfma2(hsub2(v, m2), r2x, nc2); };
#pragma unroll
      for (int i = 0; i < 7; i++) stg128(dst + i * 256, f(H[i].x), f(H[i].y), f(H[i].z), f(H[i].w));
      if (pw != 1) named_arrive(4, 128);
      else { named_sync(4, 128); publish(scr, C_H + (b & 3)); }
      OBS(tid == 288, 4);
    }
    const int lane = lane_id();
    if (pw == 0) {
      if (elect()) {
        asm volatile("prefetch.tensormap [%0];" :: "l"(&m_w1) : "memory");
        asm volatile("prefetch.tensormap [%0];" :: "l"(&m_w2) : "memory");
        asm volatile("prefetch.tensormap [%0];" :: "l"(&m_res) : "memory");
      }
      if (g1) produce_box<0>(base, 0, 32, &m_w1, ft * 64, 0);
      auto load_res = [&]() { if (elect()) { mbar_expect_tx(bars + B_RES, BT); tma3d(base + OFF_Q, &m_res, dt * 112, mt * 64, 0, bars + B_RES); } };
      if (RESP == 0) { mbar_wait(bars + B_ATT, 0); load_res(); }
      mbar_wait(bars + B_WO, 0);
      produce_lin<0>(base, 0, 7, scr + (dt * HU_T + 60) * BT, BT);
      if (NX) {
        produce_box<0>(base, 7, XT, &m_w2, mt * 64, 0);
        if (elect()) {
          mbar_expect_tx(bars + B_XW, NX * 8192);
#pragma unroll 1
          for (int i = 0; i < NX; i++) tma3d(base + OFF_XW + i * 8192, &m_w2, mt * 64, (XS - 7 + i) * 64, 0, bars + B_XW);
        }
        __syncwarp();
        produce_box<0>(base, XT, XS, &m_w2, mt * 64, (XT - 7) * 64);
        mbar_wait(bars + B_XW, 0);
#pragma unroll 1
        for (int it = XS; it < XS + NX; it++) { mbar_wait(bars + B_EMPTY + (it & 7) * 8, (it >> 3) & 1); if (lane == 0) mbar_arrive(bars + (it & 7) * 8); }
        __syncwarp();
        produce_box<0>(base, XS + NX, 35, &m_w2, mt * 64, (XS + NX - 7) * 64);
      } else produce_box<0>(base, 7, 35, &m_w2, mt * 64, 0);
      if (RESP) load_res();
    } else if (pw == 1) {
      if (g1) {
        spin_ge(scr, C_H + (lane & 3), 32);
        OBS(lane == 0, 16);
        if (HP) { produce_lin<HP>(base, 0, 8, scr + d1 * HU_T * BT, BT, clock()); produce_lin<0>(base, 8, 32, scr + (d1 * HU_T + 8) * BT, BT); }
        else produce_lin<0>(base, 0, 32, scr + d1 * HU_T * BT, BT);
      }
      mbar_wait(bars + B_O, 0);
      produce_lin<OPP>(base, 0, 7, scr + O_OFF + mt * 57344, 8192, clock());
      const unsigned char* us = scr + (dt * HU_T + 32) * BT;
#pragma unroll
      for (int i = 0; i < NPRE; i++) {
        mbar_wait(bars + B_EMPTY + ((7 + i) & 7) * 8, i > 0);
        if (elect()) mbar_expect_tx(bars + ((7 + i) & 7) * 8, BT);
        __syncwarp();
      }
      spin_ge(scr, C_U + (ALL4 ? lane & 3 : dt) + (mt & (UREP - 1)) * 4, 28);
      if (elect()) {
#pragma unroll
        for (int i = 0; i < NPRE; i++) bulk_g2s(base + ((7 + i) & 7) * SLOT + 8192, us + i * BT, BT, bars + ((7 + i) & 7) * 8);
      }
      const uint32_t tu = clock();
      OBS(lane == 0, 18);
      produce_lin<UP>(base, 7 + NPRE, 15, us + NPRE * BT, BT, tu + NPRE * UP - U0);
      produce_lin<0>(base, 15, 35, us + 8 * BT, BT);
      unsigned tk = 0;
      if (lane == 0) tk = atomicAdd((unsigned*)(scr + CNT_OFF + C_TK * 128), 1u);
      if (__shfl_sync(0xffffffffu, tk, 0) == 127) {
#pragma unroll 1
        for (int i = lane; i < 192; i += 32) *(unsigned*)(scr + CNT_OFF + i * 128) = 0;
      }
    } else if (pw == 2) {
      uint32_t tn = clock() + PACE0 + b * STAG;
      const unsigned char* src = p.w1 + b * 4096 + lane * 128;
#pragma unroll 1
      for (int i = 0; i < 28 + FREQ * 2; i++) {
        while ((int)(clock() - tn) < 0) __nanosleep(20);
        if (i == 14) src = p.w2 + b * 4096 + lane * 128;
        if (i < 28) asm volatile("prefetch.global.L2 [%0];" :: "l"(src) : "memory");
        OBSG(FREQ && lane == 0, 129 + i, 161 + i);
        src += 128 * 4096;
        tn += i < 14 ? PACE1 : PACE2;
      }
    } else {
      if (b < 112) retile_wo(p.wo, scr, b, lane_id());
      const int lane = lane_id();
      unsigned char* hg = scr + HALO_OFF + (rb * 8 + hp) * 3584 + lane * 16;
      named_sync(1, 64);
      if (rb < 15) {
        uint4 v[7];
#pragma unroll
        for (int i = 0; i < 7; i++) v[i] = lds128(base + OFF_K + 8 * 3584 + i * 512 + lane * 16);
#pragma unroll
        for (int i = 0; i < 7; i++) stg128(hg + i * 512, v[i].x, v[i].y, v[i].z, v[i].w);
        publish(scr, C_HALO + rb * 8 + hp);
      }
      OBS(lane == 0, 29);
      if (rb > 0) {
        spin_ge(scr, C_HALO + (rb - 1) * 8 + hp, 1);
        OBS(lane == 0, 12);
        if (elect()) { mbar_expect_tx(bars + B_HALO, 3584); bulk_g2s(base + OFF_K, scr + HALO_OFF + ((rb - 1) * 8 + hp) * 3584, 3584, bars + B_HALO); }
      } else {
#pragma unroll
        for (int i = 0; i < 7; i++) sts128(base + OFF_K + i * 512 + lane * 16, 0, 0, 0, 0);
        smem_fence();
        __syncwarp();
        if (lane == 0) mbar_arrive(bars + B_HALO);
      }
      __syncwarp();
      spin_ge(scr, C_WO, 112);
      if (lane == 0) mbar_arrive(bars + B_WO);
      mbar_wait(bars + B_ATT, 0);
      spin_ge(scr, C_O + (mt >> 1), 8);
      OBS(lane == 0, 17);
      if (lane == 0) mbar_arrive(bars + B_O);
    }
  } else {
    asm volatile("setmaxnreg.inc.sync.aligned.u32 232;");
    const int wg = warp >> 2, w4 = warp & 3, th = wg ^ 1;
    const bool rel = (tid & 127) < 2;
    unsigned char* scr = p.scr;
    uint32_t X[28][4];
    float aq[28];
    const uint32_t dlo = (base >> 4) + (512u << 16) + (hp & 1), dlq = dlo + (OFF_WQ >> 4);
    {
      uint32_t xa[4];
#pragma unroll
      for (int k = 0; k < 4; k++) xa[k] = base + OFF_X + (th * 64 + w4 * 16 + (mi >> 1) * 8 + r8) * 128 + (((2 * k + (mi & 1)) ^ r8) << 4);
      float c0[2][4] = {}, c1[2][4] = {};
      uint32_t one[8];
#pragma unroll
      for (int j = 0; j < 8; j++) asm volatile("{\n.reg .u32 y;\nmov.u32 y, %%tid.y;\nmad.lo.u32 %0, y, %1, 0x3f803f80;\n}" : "=r"(one[j]) : "r"(lane + j));
      asm volatile("" : "+l"(scr));
      uint32_t ok = 0;
      const uint32_t bx = bars + B_X + XSPLIT * wg * 64;
      if (HEAT) {
#pragma unroll 1
        for (int n = 0; n < 64 && !ok; n++) { mma16816(c0[0], 0, 0, 0, 0, 0, 0); ok = mbar_try(bars + B_X, 0); }
        if (XSPLIT && wg) ok = 0;
      }
#pragma unroll
      for (int i = 0; i < 8; i++) {
        if (i < 7) {
          if (!ok) mbar_wait(bx + i * 8, 0);
          OBS(tid == 64 && i == 0, 0); OBS(tid == 64 && i == 6, 15);
#pragma unroll
          for (int k = 0; k < 4; k++) ldsm4(X[i * 4 + k], xa[k] + i * 16384);
          if (i < 6) ok = mbar_try(bx + i * 8 + 8, 0);
        }
        if (i > 0) {
#pragma unroll
          for (int k = i * 4 - 4; k < i * 4; k++) {
            mma16816(c0[k & 1], X[k][0], one[(k & 1) * 4], X[k][1], one[(k & 1) * 4 + 1], X[k][0], X[k][1]);
            mma16816(c1[k & 1], X[k][2], one[(k & 1) * 4 + 2], X[k][3], one[(k & 1) * 4 + 3], X[k][2], X[k][3]);
          }
        }
      }
      float st[4];
#pragma unroll
      for (int j = 0; j < 2; j++) {
        st[j] = __shfl_sync(0xffffffffu, (g & 1) ? c0[0][2 * j + 1] + c0[1][2 * j + 1] : c0[0][2 * j] + c0[1][2 * j], (lane & 28) | (g >> 1));
        st[2 + j] = __shfl_sync(0xffffffffu, (g & 1) ? c1[0][2 * j + 1] + c1[1][2 * j + 1] : c1[0][2 * j] + c1[1][2 * j], (lane & 28) | (g >> 1));
      }
      named_arrive(8, 384);
      asm volatile("{\n.reg .pred q;\nsetp.ne.u32 q, %3, 0;\n@q st.shared.v2.f32 [%0], {%1,%2};\n@q bar.arrive 9, 160;\n}"
                   :: "r"(base + OFF_LN + ((t & 1) * 8 + g) * 8), "f"((t & 1) ? st[3] : st[1]), "f"((t & 1) ? st[2] : st[0]), "r"((uint32_t)((warp ^ 4) == hp)) : "memory");
      ok = mbar_try(bars + B_KV, 0);
      LnC l0, l1;
      float eps = 1e-5f;
#pragma unroll 1
      do {
        l0 = ln_consts(st[1], st[0], eps); l1 = ln_consts(st[3], st[2], eps);
#pragma unroll
        for (int k = 0; k < PRE * 16; k++) X[k >> 2][k & 3] = hsub2(X[k >> 2][k & 3], k & 2 ? l1.m : l0.m);
        eps += eps;
      } while ((l0.rl ^ l1.rl) == 4);
      OBS(tid == 32, 1);
      float ak[60], *av = ak + 32;
      const int pp_in = wg ? 6 : 0, pp_out = wg ? 0 : 6;
#pragma unroll
      for (int s = 0; s < 7; s++) {
#pragma unroll
        for (int k = s * 4; k < s * 4 + 4; k++) {
          if (s < PRE) {
            auto f = [&](uint32_t d, const LnC& l) { return hfma2(d, l.rh, hmul2(d, l.rl)); };
            const uint32_t y = f(X[k][1], l0);
            X[k][0] = f(X[k][0], l0); X[k][1] = f(X[k][2], l1); X[k][2] = y; X[k][3] = f(X[k][3], l1);
          } else {
            const uint32_t y = ln_apply(X[k][1], l0);
            X[k][0] = ln_apply(X[k][0], l0); X[k][1] = ln_apply(X[k][2], l1); X[k][2] = y; X[k][3] = ln_apply(X[k][3], l1);
          }
        }
        if (__builtin_expect(!ok, 0)) { mbar_wait(bars + B_KV + s * 8, 0); if (s == 6) mbar_wait(bars + B_WQ, 0); }
        if (s == 0) fresh(ak);
        if (s == 6) { wg_wait<0>(); if ((tid & 127) == 0) mbar_arrive(bars + B_EMPTY + 3 * 8); }
        OBS(KOBS && (tid & 127) == 0, 40 + wg * 32 + s);
        if (PPM == 2 ? (wg ? s < 6 : s > 1) : (wg || s)) named_sync(pp_in, 256);
        OBS(KOBS && (tid & 127) == 32, 48 + wg * 32 + s);
        OBS(tid == 64 && s == 0, 2);
        wg_fence();
#pragma unroll
        for (int k = 0; k < 4; k++) {
          wgmma_rs_n120<1>(ak, X[s * 4 + k], mkdesc(HI_SW128, dlo + s * 1024 + k * 128), (s | k) != 0);
        }
        wg_commit();
        if (s == 6) {
          fresh(aq);
#pragma unroll
          for (int k = 0; k < 4 * QA; k++) {
            if (k == 4 * QA - PQE) named_arrive(pp_out, 256);
            wgmma_rs_n56<1>(aq, X[k], mkdesc(HI_SW128, dlq + k * 128), k);
          }
          wg_commit();
        }
        if (s < 6 || PQE == 0) named_arrive_if(PPM != 2 || (wg ? s != 5 : s != 0), pp_out, 256);
        fence_code(s);
        OBS(KOBS && (tid & 127) == 64, 56 + wg * 32 + s);
        if (s < 6) ok = mbar_try(bars + B_KV + s * 8 + 8, 0);
        if (s == 5) ok &= mbar_try(bars + B_WQ, 0);
        OBS(tid == 64 && s == 1, 28); OBS(tid == 64 && s == 5, 31);
        if (s > 0) wg_wait<1>();
        OBS(KOBS && (tid & 127) == 96, 64 + wg * 32 + s);
        if ((s == 2 || s == 3 || s == 5) && (tid & 127) == 0) mbar_arrive(bars + B_EMPTY + (s == 5 ? 2 : s - 2) * 8);
      }
      if ((tid & 127) == 0) mbar_arrive(bars + B_EMPTY + 4 * 8);
      OBS(tid == 32, 3);
      {
        const uint32_t kst = base + OFF_K + (2 + (warp ^ 4) * 2 + (mi & 1)) * 1792 + (mi >> 1) * 896 + r8 * 16;
#pragma unroll
        for (int n = 0; n < 7; n++)
          stsm4(kst + n * 128, pack2(ak[n * 4], ak[n * 4 + 1]), pack2(ak[n * 4 + 2], ak[n * 4 + 3]), pack2(av[n * 4], av[n * 4 + 1]), pack2(av[n * 4 + 2], av[n * 4 + 3]));
        named_arrive_if(warp == 3, 1, 64);
      }
      OBS(tid == 96, 32); OBS(tid == 224, 34);
      wg_wait<0>();
      if ((tid & 127) == 0) mbar_arrive(bars + B_EMPTY + 5 * 8);
      mbar_wait(bars + B_WQ2, 0);
    }
    const unsigned short *bp1 = (const unsigned short*)p.b1 + (g1 ? ft * 64 : 0) + w4 * 16 + g, *bp2 = (const unsigned short*)p.b2 + mt * 64 + w4 * 16 + g;
    const uint32_t braw[4] = {__ldg(bp1), __ldg(bp1 + 8), __ldg(bp2), __ldg(bp2 + 8)};
    auto q_rest = [&]() {
      wg_fence();
#pragma unroll
      for (int s = QA; s < 7; s++) {
#pragma unroll
        for (int k = s * 4; k < s * 4 + 4; k++) wgmma_rs_n56<1>(aq, X[k], mkdesc(HI_SW128, dlq + k * 128), 1);
        wg_commit();
        if (s == 5) { wg_wait<2>(); if ((tid & 127) == 0) mbar_arrive(bars + B_EMPTY + 6 * 8); }
      }
    };
    uint32_t Q[4][4];
    auto q_pack = [&]() {
#pragma unroll
      for (int n = 0; n < 14; n++) { const int m = n + 2 * (n > 7); Q[m >> 2][m & 3] = pack2(aq[n * 2], aq[n * 2 + 1]); }
#pragma unroll
      for (int h = 0; h < 2; h++) { Q[2][h] = t < 2 ? 0u : Q[1][2 + h]; Q[1][2 + h] = t < 2 ? Q[1][2 + h] : 0u; }
    };
    float acc[56];
    auto ai = [](int p) { return p < 4 ? 48 + (p & 1) * 4 + (p & 2) : (p - 4) * 4; };
    uint32_t xch, ts, tl;
    unsigned char *ug, *uc, *outp, *outq;
    auto setup_u = [&]() {
      xch = pin(base + OFF_K + (tid & 127) * 16);
      ug = pin(scr + (d1 * HU_T + 32 + ft) * BT + w4 * 3584 + lane * 4 + wg * 1792);
      uc = pin(scr + CNT_OFF + (C_U + d1 + (lane & (UREP - 1)) * 4) * 128);
    };
    auto setup_out = [&]() {
      const uint32_t tb = base + OFF_K + 6144 + warp * 2560;
      ts = pin(tb + mi * 160 + r8 * 16); tl = pin(tb + t * 160 + g * 16);
      unsigned char* o = p.out + (mt * 64 + w4 * 16 + g) * 896 + dt * 224;
      outp = pin(o + th * 7168 + t * 16); outq = pin(o + (t >> 1) * 7168 + 192 + (t & 1) * 16);
    };
    auto give = [&](const float (&a)[56], int id) {
#pragma unroll
      for (int i = 0; i < 48; i += 16) sts128(xch + i * 128, pack2(a[i + 2], a[i + 3]), pack2(a[i + 6], a[i + 7]), pack2(a[i + 10], a[i + 11]), pack2(a[i + 14], a[i + 15]));
      named_arrive(id, 256);
    };
    auto take = [&](uint32_t (&r)[12], int id) {
      named_sync(id, 256);
#pragma unroll
      for (int i = 0; i < 3; i++) { const uint4 v = lds128(xch + i * 2048); r[i * 4] = v.x; r[i * 4 + 1] = v.y; r[i * 4 + 2] = v.z; r[i * 4 + 3] = v.w; }
    };
    float hv[32];
    auto keep_h = [&](int i) {
      const float hb0 = 0.5f * bf_lo(braw[i]), hb1 = 0.5f * bf_lo(braw[i + 1]);
#pragma unroll
      for (int j = 0; j < 32; j++) hv[j] = fmaf(acc[ai(j >> 1) + (j & 1)], 0.5f, j >= 4 && j < 8 ? hb1 : hb0);
    };
    auto take_h = [&](int i) {
      const float hb1 = 0.5f * bf_lo(braw[i + 1]);
      uint32_t r[12];
      take(r, 5);
#pragma unroll
      for (int j = 0; j < 12; j++) { hv[8 + 2 * j] = fmaf(bf_lo(r[j]), 0.5f, hb1); hv[9 + 2 * j] = fmaf(bf_hi(r[j]), 0.5f, hb1); }
    };
    uint4 Xr[4];
    auto get_x = [&]() {
      const uint32_t xr = base + OFF_Q + (w4 * 16 + g) * 224;
      mbar_wait(bars + B_RES, 0);
      Xr[0] = lds128(xr + (t >> 1) * 1792 + 192 + (t & 1) * 16);
#pragma unroll
      for (int i = 1; i < 4; i++) Xr[i] = lds128(xr + th * 1792 + t * 16 + (i - 1) * 64);
    };
    auto gelu = [&](int j) {
      const float h0 = hv[2 * j], h1 = hv[2 * j + 1];
      const float t0 = tanh_fast(h0 * fmaf(h0 * h0, 0.2854192648f, 1.5957691216f)), t1 = tanh_fast(h1 * fmaf(h1 * h1, 0.2854192648f, 1.5957691216f));
      stg32(ug + (ai(j) & 2) * 896 + (ai(j) >> 2) * 128, pack2(fmaf(h0, t0, h0), fmaf(h1, t1, h1)));
    };
    uint32_t Sv[16];
    auto gate = [&](int i) {
      uint32_t R[4];
#pragma unroll
      for (int q = 0; q < 4; q++) {
        const int j = i * 4 + q;
        const float h0 = hv[2 * j], h1 = hv[2 * j + 1];
        R[q] = hmul2(Sv[j], pack2(fmaf(h0, tanh_fast(h0), h0), fmaf(h1, tanh_fast(h1), h1)));
      }
      stsm4(ts + i * 640, R[0], R[1], R[2], R[3]);
    };
    auto leave = [&](int i) {
      __syncwarp();
      const uint4 v = lds128(tl + i * 640), x = Xr[i];
      stg128(i ? outp + (i - 1) * 64 : outq, hadd2(x.x, v.x), hadd2(x.y, v.y), hadd2(x.z, v.z), hadd2(x.w, v.w));
    };
    if (wg == 0) {
      named_sync(0, 256);
      OBS(tid == 96, 14);
      q_rest();
      named_arrive(6, 256);
      wg_wait<0>();
      if (tid == 0) mbar_arrive(bars + B_EMPTY + 7 * 8);
      q_pack();
      const uint32_t qst = base + OFF_Q + 8192 + (mi >> 1) * 1024 + (w4 * 16 + (mi & 1) * 8 + r8) * 16;
#pragma unroll
      for (int n = 0; n < 4; n++) stsm4(qst + n * 2048, Q[n][0], Q[n][1], Q[n][2], Q[n][3]);
      smem_fence();
      named_arrive(7, 256);
      OBS(tid == 32, 5);
      fresh(acc);
      setup_u();
      if (g1) {
        mbar_wait(bars, 0); mbar_wait(bars + 8, 0);
        if (TS) {
          const uint32_t tg = lds64(bars + B_T0).x;
          while ((int)(clock() - tg) < 0);
        }
        named_sync(0, 256);
        gemm_issue<1>(acc, base >> 4, base >> 4, 0);
        OBS(tid == 0, 20);
        gemm_loop<1>(acc, base, 1, 32, rel, 40, 1, tid == 32 ? J1 : tid == 64 ? J2 : tid == 96 ? J3 : -1, bars + B_GATE - 8 + w4 * 8);
        wg_wait<0>();
        OBS(tid == 0, 21);
        give(acc, 5);
        mbar_arrive_if(rel, bars + B_EMPTY + 7 * 8);
        fence_code(30);
        keep_h(0);
#pragma unroll
        for (int j = 0; j < 16; j++) { gelu(j); if (j % GCH == GCH - 1 && j < 15) fence_code(8 + j); }
        if (w4) named_arrive(2, 256);
        else { named_sync(2, 256); asm volatile("{\n.reg .pred q;\nsetp.lt.u32 q, %1, %2;\n@q red.relaxed.gpu.global.add.u32 [%0], 1;\n}" :: "l"(uc), "r"(lane), "n"(UREP) : "memory"); OBS(tid == 0, 9); }
      } else {
        if (lane == 0 && w4) mbar_arrive(bars + B_GATE - 8 + w4 * 8);
      }
      setup_out();
      if (!RESP) get_x();
      uint32_t r[12];
      take(r, 3);
#pragma unroll
      for (int j = 0; j < 16; j++) Sv[j] = r[j < 4 ? 0 : j - 4];
      asm volatile("" :: "r"(r[0]), "r"(r[11]) : "memory");
      named_arrive(10, 256);
      if (RESP) get_x();
      take_h(2);
    } else {
      const uint32_t dq = ((base + OFF_Q) >> 4) + (64u << 16), dk = (base + OFF_K) >> 4;
      const bool odd = g & 1, early = 2 * t + (g & 1) > g;
      uint32_t selA[5], selB[4];
#pragma unroll
      for (int j = 0; j < 5; j++) selA[j] = j == w4 + (early ? 0 : 1) ? (odd ? 0x1044u : 0x4410u) : 0x4444u;
#pragma unroll
      for (int j = 0; j < 4; j++) selB[j] = j == w4 ? (odd ? 0x3244u : 0x4432u) : 0x4444u;
      float Sc[2][40], Op[2][2][16];
      uint32_t A[2][5][4];
      auto scores = [&](int T) {
        fresh(Sc[0]); fresh(Sc[1]);
#pragma unroll
        for (int k = 0; k < 2; k++) {
#pragma unroll
          for (int hh = 0; hh < 2; hh++)
            if (T) wgmma_n80<0, 0>(Sc[hh], mkdesc(8, dq + 512 + hh * 256 + k * 128), mkdesc(112, dk + (8u << 16) + 896 + hh * 24 + k * 16), k);
            else wgmma_rs_n80<0>(Sc[hh], Q[hh * 2 + k], mkdesc(112, dk + (8u << 16) + hh * 24 + k * 16), k);
        }
      };
      auto softmax = [&](int T) {
#pragma unroll
        for (int hh = 0; hh < 2; hh++) {
          uint32_t pp[2];
#pragma unroll
          for (int h = 0; h < 2; h++) {
            float c[3];
#pragma unroll
            for (int n = 0; n < 3; n++) {
              const float* q = Sc[hh] + (h + n) * 4 + 2 * h;
              asm("{\n.reg .pred p, a, b, c;\nsetp.ne.u32 p, %9, 0;\nsetp.eq.u32 a, %10, 1;\nsetp.eq.u32 b, %10, 2;\nsetp.eq.u32 c, %10, 3;\n"
                  "selp.f32 %0, %2, %1, p;\n@a selp.f32 %0, %4, %3, p;\n@b selp.f32 %0, %6, %5, p;\n@c selp.f32 %0, %8, %7, p;\n}"
                  : "=&f"(c[n]) : "f"(q[0]), "f"(q[1]), "f"(q[8]), "f"(q[9]), "f"(q[16]), "f"(q[17]), "f"(q[24]), "f"(q[25]), "r"((uint32_t)odd), "r"((tid >> 5) & 3));
            }
            uint32_t pk = pack2(early ? c[0] : c[2], c[1]);
            pk = pack2(bf_lo(pk) * SCALE, bf_hi(pk) * SCALE);
            float l0 = bf_lo(pk), l1 = bf_hi(pk);
            if (T == 0 && w4 == 0 && rb == 0) { if (early) l0 = -1e9f; if (h == 0) l1 = -1e9f; }
            float mx = fmaxf(l0, l1);
            mx = fmaxf(mx, __shfl_xor_sync(0xffffffffu, mx, 1));
            mx = fmaxf(mx, __shfl_xor_sync(0xffffffffu, mx, 2));
            float p0 = ex2_fast((l0 - mx) * LOG2E), p1 = ex2_fast((l1 - mx) * LOG2E);
            float sm = p0 + p1;
            sm += __shfl_xor_sync(0xffffffffu, sm, 1);
            sm += __shfl_xor_sync(0xffffffffu, sm, 2);
            const float inv = rcp_fast(sm);
            pp[h] = pack2(p0 * inv, p1 * inv);
          }
#pragma unroll
          for (int j = 0; j < 5; j++) {
            A[hh][j][0] = __byte_perm(pp[0], 0, selA[j]); A[hh][j][1] = j ? __byte_perm(pp[1], 0, selB[j ? j - 1 : 0]) : 0u;
            A[hh][j][2] = j < 4 ? __byte_perm(pp[0], 0, selB[j & 3]) : 0u; A[hh][j][3] = __byte_perm(pp[1], 0, selA[j]);
          }
        }
      };
      auto values = [&](int T) {
        fresh(Op[T][0]); fresh(Op[T][1]);
#pragma unroll
        for (int j = 0; j < 5; j++)
#pragma unroll
          for (int hh = 0; hh < 2; hh++) {
            wgmma_rs_n32<1>(Op[T][hh], A[hh][j], mkdesc(8, dk + (112u << 16) + 56 + T * 896 + hh * 24 + j * 224), j);
          }
        wg_commit();
      };
      uint32_t Ob[2][14];
      auto pack = [&](int T) {
        const float (&O)[2][16] = Op[T];
#pragma unroll
        for (int n = 0; n < 7; n++)
#pragma unroll
          for (int h = 0; h < 2; h++) {
            if (n < 3) Ob[T][n * 2 + h] = pack2(O[0][n * 4 + 2 * h], O[0][n * 4 + 2 * h + 1]);
            else if (n == 3) Ob[T][n * 2 + h] = pack2(t < 2 ? O[0][12 + 2 * h] : O[1][2 * h], t < 2 ? O[0][13 + 2 * h] : O[1][2 * h + 1]);
            else Ob[T][n * 2 + h] = pack2(O[1][(n - 3) * 4 + 2 * h], O[1][(n - 3) * 4 + 2 * h + 1]);
          }
      };
      smem_fence();
      named_sync(6, 256);
      OBS(tid == 224, 26);
      q_rest();
      named_sync(7, 256);
      wg_fence();
      scores(1);
      wg_commit();
      named_arrive_if(g1, 0, 256);
      wg_wait<2>();
      if (tid == 128) mbar_arrive(bars + B_EMPTY + 7 * 8);
      wg_wait<0>();
      q_pack();
      OBS(tid == 160, 10);
      softmax(1);
      OBS(tid == 160, 30);
      mbar_wait(bars + B_HALO, 0);
      OBS(tid == 160, 7);
      mbar_wait(bars + B_GATE, 0);
      wg_fence();
      scores(0);
      values(1);
      wg_wait<0>();
      OBS(tid == 160, 33);
      unsigned char* og = scr + O_OFF + rb * 2 * 57344 + hp * 7168 + w4 * 256 + lane * 4;
      auto put = [&](int T) {
#pragma unroll
        for (int n = 0; n < 14; n++) { stg32(og + T * 57344 + (n >> 1) * 1024 + (n & 1) * 128, Ob[T][n]); if (OSLEEP && n % OGRP == OGRP - 1) __nanosleep(OSLEEP); }
      };
      if (OMODE == 1) { pack(1); put(1); }
      softmax(0);
      if (OMODE == 2) { pack(1); put(1); }
      mbar_wait(bars + B_GATE + 8, 0);
      wg_fence();
      values(0);
      if (OMODE == 3) { pack(1); put(1); }
      wg_wait<0>();
      OBS(tid == 160, 35);
      named_sync(11, 128);
      if (tid == 160) mbar_arrive(bars + B_ATT);
      if (OMODE == 0) pack(1);
      pack(0);
      if (J3 > J2) mbar_wait(bars + B_GATE + 16, 0);
      if (OMODE == 0) put(1);
      put(0);
      named_sync(11, 128);
      if (warp == 4) publish(scr, C_O + rb);
      OBS(tid == 160, 8);
      setup_u(); setup_out();
      float as[56];
      if (g1) {
        take_h(0);
        if (!RESP && XE) get_x();
#pragma unroll
        for (int j = 4; j < OPJ; j++) { gelu(j); if (j % GCH == GCH - 1 && j < OPJ - 1) fence_code(40 + j); }
        if (OPJ == 16) named_arrive(2, 256);
      } else if (!RESP && XE) get_x();
      fresh(as);
      gemm_stage<0>(as, base, 0, 0);
      OBS(tid == 128, 22);
      if (OPJ < 16 && g1) {
#pragma unroll
        for (int j = OPJ; j < 16; j++) gelu(j);
        named_arrive(2, 256);
      }
      gemm_loop<0>(as, base, 1, 7, rel, 104);
      fresh(acc);
      if (SEARLY) { wg_wait<0>(); mbar_arrive_if(rel, bars + B_EMPTY + 6 * 8); give(as, 3); if (!RESP && !XE) get_x(); }
      gemm_stage<1>(acc, base, 7, 0);
      OBS(tid == 128, 24);
      if (!SEARLY) { wg_wait<1>(); mbar_arrive_if(rel, bars + B_EMPTY + 6 * 8); give(as, 3); }
#pragma unroll
      for (int j = 0; j < 16; j++) Sv[j] = pack2(as[ai(j)], as[ai(j) + 1]);
      gemm_loop<1, NX>(acc, base, 8, 35, rel, 65);
      if (RESP) get_x();
      named_sync(10, 256);
      wg_wait<0>();
      OBS(tid == 128, 25);
      give(acc, 5);
      fence_code(31);
      keep_h(2);
      gate(0); leave(0);
    }
    {
#pragma unroll
      for (int i = 1; i < 4; i++) { gate(i); leave(i); }
      OBS(tid == 128, 27);
    }
  }
}

typedef CUresult (*EncFn)(CUtensorMap*, CUtensorMapDataType, cuuint32_t, void*, const cuuint64_t*, const cuuint64_t*, const cuuint32_t*,
                          const cuuint32_t*, CUtensorMapInterleave, CUtensorMapSwizzle, CUtensorMapL2promotion, CUtensorMapFloatOOBfill);
void enc(EncFn f, CUtensorMap* m, const void* ptr, cuuint64_t d0, cuuint64_t d1, cuuint64_t d2, cuuint64_t s1, cuuint64_t s2, cuuint32_t b1, cuuint32_t b2, cuuint32_t b0 = 64) {
  const cuuint64_t gd[3] = {d0, d1, d2}, gs[2] = {s1 * 2, s2 * 2};
  const cuuint32_t bx[3] = {b0, b1, b2}, es[3] = {1, 1, 1};
  f(m, CU_TENSOR_MAP_DATA_TYPE_BFLOAT16, 3, (void*)ptr, gd, gs, bx, es, CU_TENSOR_MAP_INTERLEAVE_NONE, b0 == 64 ? CU_TENSOR_MAP_SWIZZLE_128B : CU_TENSOR_MAP_SWIZZLE_NONE,
    CU_TENSOR_MAP_L2_PROMOTION_L2_128B, CU_TENSOR_MAP_FLOAT_OOB_FILL_NONE);
}
}

extern "C" void kernel_launch(void* const* d_in, const int* in_sizes, int n_in, void* d_out, int out_size) {
  (void)in_sizes; (void)n_in; (void)out_size;
  void* fp = nullptr;
  cudaDriverEntryPointQueryResult qr;
  cudaGetDriverEntryPoint("cuTensorMapEncodeTiled", &fp, cudaEnableDefault, &qr);
  EncFn f = (EncFn)fp;
  CUtensorMap m_x, m_wkv, m_wq, m_w1, m_w2, m_res;
  void* scr = nullptr;
  cudaGetSymbolAddress(&scr, g_scr);
  enc(f, &m_x, d_in[0], D_, S_, 1, D_, D_, 128 >> XSPLIT, 1);
  enc(f, &m_wkv, d_in[1], D_, D_, 3, 3 * D_, D_, 64, 2);
  enc(f, &m_wq, d_in[1], D_, D_, 3, 3 * D_, D_, 224, 1);
  enc(f, &m_w1, d_in[4], F_, S_, 1, F_, F_, 64, 1);
  enc(f, &m_w2, d_in[6], S_, F_, 1, S_, S_, 64, 1);
  enc(f, &m_res, d_in[0], D_, S_, 1, D_, D_, 64, 1, 112);
  Params p;
  p.wqkv = (const unsigned char*)d_in[1]; p.wo = (const unsigned char*)d_in[2];
  p.w1 = (const unsigned char*)d_in[4]; p.b1 = (const unsigned char*)d_in[5];
  p.w2 = (const unsigned char*)d_in[6]; p.b2 = (const unsigned char*)d_in[7];
  p.out = (unsigned char*)d_out; p.scr = (unsigned char*)scr;
  cudaFuncSetAttribute(fused_kernel, cudaFuncAttributeMaxDynamicSharedMemorySize, SMEM_BYTES);
  fused_kernel<<<128, NTHREADS, SMEM_BYTES, cudaStreamPerThread>>>(m_x, m_wkv, m_wq, m_w1, m_w2, m_res, p);
}
```

```cpp
#include <cuda_runtime.h>
#include <cuda.h>
#include <cuda_bf16.h>
#include <stdint.h>

template<int TA, int TB> __device__ __forceinline__ void wgmma_n112(float (&d)[56], uint64_t da, uint64_t db, int sc) {
  asm volatile("{\n.reg .pred p;\nsetp.ne.b32 p, %58, 0;\n"
    "wgmma.mma_async.sync.aligned.m64n112k16.f32.bf16.bf16 {%0, %1, %2, %3, %4, %5, %6, %7, %8, %9, %10, %11, %12, %13, %14, %15, %16, %17, %18, %19, %20, %21, %22, %23, %24, %25, %26, %27, %28, %29, %30, %31, %32, %33, %34, %35, %36, %37, %38, %39, %40, %41, %42, %43, %44, %45, %46, %47, %48, %49, %50, %51, %52, %53, %54, %55}, %56, %57, p, 1, 1, %59, %60;\n}\n"
    : "+f"(d[0]), "+f"(d[1]), "+f"(d[2]), "+f"(d[3]), "+f"(d[4]), "+f"(d[5]), "+f"(d[6]), "+f"(d[7]), "+f"(d[8]), "+f"(d[9]), "+f"(d[10]), "+f"(d[11]), "+f"(d[12]), "+f"(d[13]), "+f"(d[14]), "+f"(d[15]), "+f"(d[16]), "+f"(d[17]), "+f"(d[18]), "+f"(d[19]), "+f"(d[20]), "+f"(d[21]), "+f"(d[22]), "+f"(d[23]), "+f"(d[24]), "+f"(d[25]), "+f"(d[26]), "+f"(d[27]), "+f"(d[28]), "+f"(d[29]), "+f"(d[30]), "+f"(d[31]), "+f"(d[32]), "+f"(d[33]), "+f"(d[34]), "+f"(d[35]), "+f"(d[36]), "+f"(d[37]), "+f"(d[38]), "+f"(d[39]), "+f"(d[40]), "+f"(d[41]), "+f"(d[42]), "+f"(d[43]), "+f"(d[44]), "+f"(d[45]), "+f"(d[46]), "+f"(d[47]), "+f"(d[48]), "+f"(d[49]), "+f"(d[50]), "+f"(d[51]), "+f"(d[52]), "+f"(d[53]), "+f"(d[54]), "+f"(d[55])
    : "l"(da), "l"(db), "r"(sc), "n"(TA), "n"(TB));
}

template<int TA, int TB> __device__ __forceinline__ void wgmma_n80(float (&d)[40], uint64_t da, uint64_t db, int sc) {
  asm volatile("{\n.reg .pred p;\nsetp.ne.b32 p, %42, 0;\n"
    "wgmma.mma_async.sync.aligned.m64n80k16.f32.bf16.bf16 {%0, %1, %2, %3, %4, %5, %6, %7, %8, %9, %10, %11, %12, %13, %14, %15, %16, %17, %18, %19, %20, %21, %22, %23, %24, %25, %26, %27, %28, %29, %30, %31, %32, %33, %34, %35, %36, %37, %38, %39}, %40, %41, p, 1, 1, %43, %44;\n}\n"
    : "+f"(d[0]), "+f"(d[1]), "+f"(d[2]), "+f"(d[3]), "+f"(d[4]), "+f"(d[5]), "+f"(d[6]), "+f"(d[7]), "+f"(d[8]), "+f"(d[9]), "+f"(d[10]), "+f"(d[11]), "+f"(d[12]), "+f"(d[13]), "+f"(d[14]), "+f"(d[15]), "+f"(d[16]), "+f"(d[17]), "+f"(d[18]), "+f"(d[19]), "+f"(d[20]), "+f"(d[21]), "+f"(d[22]), "+f"(d[23]), "+f"(d[24]), "+f"(d[25]), "+f"(d[26]), "+f"(d[27]), "+f"(d[28]), "+f"(d[29]), "+f"(d[30]), "+f"(d[31]), "+f"(d[32]), "+f"(d[33]), "+f"(d[34]), "+f"(d[35]), "+f"(d[36]), "+f"(d[37]), "+f"(d[38]), "+f"(d[39])
    : "l"(da), "l"(db), "r"(sc), "n"(TA), "n"(TB));
}

template<int TB> __device__ __forceinline__ void wgmma_rs_n120(float (&d)[60], const uint32_t (&a)[4], uint64_t db, int sc) {
  asm volatile("{\n.reg .pred p;\nsetp.ne.b32 p, %65, 0;\n"
    "wgmma.mma_async.sync.aligned.m64n120k16.f32.bf16.bf16 {%0, %1, %2, %3, %4, %5, %6, %7, %8, %9, %10, %11, %12, %13, %14, %15, %16, %17, %18, %19, %20, %21, %22, %23, %24, %25, %26, %27, %28, %29, %30, %31, %32, %33, %34, %35, %36, %37, %38, %39, %40, %41, %42, %43, %44, %45, %46, %47, %48, %49, %50, %51, %52, %53, %54, %55, %56, %57, %58, %59}, {%60, %61, %62, %63}, %64, p, 1, 1, %66;\n}\n"
    : "+f"(d[0]), "+f"(d[1]), "+f"(d[2]), "+f"(d[3]), "+f"(d[4]), "+f"(d[5]), "+f"(d[6]), "+f"(d[7]), "+f"(d[8]), "+f"(d[9]), "+f"(d[10]), "+f"(d[11]), "+f"(d[12]), "+f"(d[13]), "+f"(d[14]), "+f"(d[15]), "+f"(d[16]), "+f"(d[17]), "+f"(d[18]), "+f"(d[19]), "+f"(d[20]), "+f"(d[21]), "+f"(d[22]), "+f"(d[23]), "+f"(d[24]), "+f"(d[25]), "+f"(d[26]), "+f"(d[27]), "+f"(d[28]), "+f"(d[29]), "+f"(d[30]), "+f"(d[31]), "+f"(d[32]), "+f"(d[33]), "+f"(d[34]), "+f"(d[35]), "+f"(d[36]), "+f"(d[37]), "+f"(d[38]), "+f"(d[39]), "+f"(d[40]), "+f"(d[41]), "+f"(d[42]), "+f"(d[43]), "+f"(d[44]), "+f"(d[45]), "+f"(d[46]), "+f"(d[47]), "+f"(d[48]), "+f"(d[49]), "+f"(d[50]), "+f"(d[51]), "+f"(d[52]), "+f"(d[53]), "+f"(d[54]), "+f"(d[55]), "+f"(d[56]), "+f"(d[57]), "+f"(d[58]), "+f"(d[59])
    : "r"(a[0]), "r"(a[1]), "r"(a[2]), "r"(a[3]), "l"(db), "r"(sc), "n"(TB));
}

template<int TB> __device__ __forceinline__ void wgmma_rs_n56(float (&d)[28], const uint32_t (&a)[4], uint64_t db, int sc) {
  asm volatile("{\n.reg .pred p;\nsetp.ne.b32 p, %33, 0;\n"
    "wgmma.mma_async.sync.aligned.m64n56k16.f32.bf16.bf16 {%0, %1, %2, %3, %4, %5, %6, %7, %8, %9, %10, %11, %12, %13, %14, %15, %16, %17, %18, %19, %20, %21, %22, %23, %24, %25, %26, %27}, {%28, %29, %30, %31}, %32, p, 1, 1, %34;\n}\n"
    : "+f"(d[0]), "+f"(d[1]), "+f"(d[2]), "+f"(d[3]), "+f"(d[4]), "+f"(d[5]), "+f"(d[6]), "+f"(d[7]), "+f"(d[8]), "+f"(d[9]), "+f"(d[10]), "+f"(d[11]), "+f"(d[12]), "+f"(d[13]), "+f"(d[14]), "+f"(d[15]), "+f"(d[16]), "+f"(d[17]), "+f"(d[18]), "+f"(d[19]), "+f"(d[20]), "+f"(d[21]), "+f"(d[22]), "+f"(d[23]), "+f"(d[24]), "+f"(d[25]), "+f"(d[26]), "+f"(d[27])
    : "r"(a[0]), "r"(a[1]), "r"(a[2]), "r"(a[3]), "l"(db), "r"(sc), "n"(TB));
}

template<int TB> __device__ __forceinline__ void wgmma_rs_n32(float (&d)[16], const uint32_t (&a)[4], uint64_t db, int sc) {
  asm volatile("{\n.reg .pred p;\nsetp.ne.b32 p, %21, 0;\n"
    "wgmma.mma_async.sync.aligned.m64n32k16.f32.bf16.bf16 {%0, %1, %2, %3, %4, %5, %6, %7, %8, %9, %10, %11, %12, %13, %14, %15}, {%16, %17, %18, %19}, %20, p, 1, 1, %22;\n}\n"
    : "+f"(d[0]), "+f"(d[1]), "+f"(d[2]), "+f"(d[3]), "+f"(d[4]), "+f"(d[5]), "+f"(d[6]), "+f"(d[7]), "+f"(d[8]), "+f"(d[9]), "+f"(d[10]), "+f"(d[11]), "+f"(d[12]), "+f"(d[13]), "+f"(d[14]), "+f"(d[15])
    : "r"(a[0]), "r"(a[1]), "r"(a[2]), "r"(a[3]), "l"(db), "r"(sc), "n"(TB));
}

template<int TB> __device__ __forceinline__ void wgmma_rs_n80(float (&d)[40], const uint32_t (&a)[4], uint64_t db, int sc) {
  asm volatile("{\n.reg .pred p;\nsetp.ne.b32 p, %45, 0;\n"
    "wgmma.mma_async.sync.aligned.m64n80k16.f32.bf16.bf16 {%0, %1, %2, %3, %4, %5, %6, %7, %8, %9, %10, %11, %12, %13, %14, %15, %16, %17, %18, %19, %20, %21, %22, %23, %24, %25, %26, %27, %28, %29, %30, %31, %32, %33, %34, %35, %36, %37, %38, %39}, {%40, %41, %42, %43}, %44, p, 1, 1, %46;\n}\n"
    : "+f"(d[0]), "+f"(d[1]), "+f"(d[2]), "+f"(d[3]), "+f"(d[4]), "+f"(d[5]), "+f"(d[6]), "+f"(d[7]), "+f"(d[8]), "+f"(d[9]), "+f"(d[10]), "+f"(d[11]), "+f"(d[12]), "+f"(d[13]), "+f"(d[14]), "+f"(d[15]), "+f"(d[16]), "+f"(d[17]), "+f"(d[18]), "+f"(d[19]), "+f"(d[20]), "+f"(d[21]), "+f"(d[22]), "+f"(d[23]), "+f"(d[24]), "+f"(d[25]), "+f"(d[26]), "+f"(d[27]), "+f"(d[28]), "+f"(d[29]), "+f"(d[30]), "+f"(d[31]), "+f"(d[32]), "+f"(d[33]), "+f"(d[34]), "+f"(d[35]), "+f"(d[36]), "+f"(d[37]), "+f"(d[38]), "+f"(d[39])
    : "r"(a[0]), "r"(a[1]), "r"(a[2]), "r"(a[3]), "l"(db), "r"(sc), "n"(TB));
}

namespace {
constexpr int S_ = 2048, D_ = 448, F_ = 1792;
constexpr int NSLOT = 8, SLOT = 22528;
constexpr int OFF_X = 7 * 16384;
constexpr int OFF_WQ = 8 * 16384;
constexpr int OFF_Q = NSLOT * SLOT;
constexpr int OFF_K = OFF_Q + 16384;
constexpr int OFF_XW = OFF_K + 6144;
constexpr int OFF_BAR = 14 * 16384;
constexpr int OFF_LN = OFF_BAR + 512;
constexpr int OFF_OBS = OFF_BAR + 640;
constexpr int SMEM_BYTES = OFF_OBS + 1024;
#define PACE0 0
#define PACE1 540
#define PACE2 650
#define WARM 3
#define NW0 2
#define HEAT 1
#define T0 0
#define TP 250
#define J3 0
#define J1 9
#define J2 14
#define EARLY 4
#define PPE 4
#define PQE 2
#define LANDOBS 0
#define TRUNC 0
#define KOBS 0
#define PRE 1
#define QA 2
#define HEARLY 0
#define OSLEEP 20
#define PROBE 1
#define WOP 0
#define OGRP 2
#define OMODE 3
#define GCH 4
#define GLAG 2
#define GSLOW 0
#define RH 32
#define NOST 0
#define GOBS 0
#define HP 0
#define OPP 0
#define STAG 0
#define RESP 0
#define XE 1
#define NX 0
#define XS 15
#define XT 9
#define NPRE 1
#define U0 0
#define ALL4 0
#define UREP 1
#define TS 0
#define PPM 1
#define WPF 0
#define XSPLIT 1
#define XK 1
#define FAKE 8
#define MU 0
#define P2 224
#define UP 170
#define POLL "relaxed"
#define OPJ 16
#define SEARLY 1
#define EXACT 0
#define SOBS 0
#define FREQ 0
#define OBS(c, i) do {} while (0)
#define OBSG(c, i, j) do {} while (0)
constexpr int NTHREADS = 384;
constexpr float SCALE = 0.18898223650461361f, LOG2E = 1.4426950408889634f;
constexpr int BT = 14336;

constexpr int HU_T = 67;
constexpr int O_OFF = 4 * HU_T * BT;
constexpr int HALO_OFF = O_OFF + 32 * 7 * 8192;
constexpr int CNT_OFF = HALO_OFF + 128 * 3584;
constexpr int SCR_BYTES = CNT_OFF + 192 * 128;
constexpr int C_WO = 0, C_TK = 1, C_U = 160, C_O = 8, C_H = 24, C_HALO = 32;
__device__ __align__(1024) unsigned char g_scr[SCR_BYTES];

__device__ __forceinline__ uint32_t smem_u32(const void* p) { return (uint32_t)__cvta_generic_to_shared(p); }
__device__ __forceinline__ void mbar_init(uint32_t bar, uint32_t cnt) { asm volatile("mbarrier.init.shared::cta.b64 [%0], %1;" :: "r"(bar), "r"(cnt)); }
__device__ __forceinline__ void mbar_expect_tx(uint32_t bar, uint32_t bytes) { asm volatile("mbarrier.arrive.expect_tx.shared::cta.b64 _, [%0], %1;" :: "r"(bar), "r"(bytes) : "memory"); }
__device__ __forceinline__ void mbar_arrive_if(uint32_t c, uint32_t bar) { asm volatile("{\n.reg .pred q;\nsetp.ne.u32 q, %1, 0;\n@q mbarrier.arrive.shared::cta.b64 _, [%0];\n}" :: "r"(bar), "r"(c) : "memory"); }
__device__ __forceinline__ void mbar_arrive(uint32_t bar) { asm volatile("mbarrier.arrive.shared::cta.b64 _, [%0];" :: "r"(bar) : "memory"); }
__device__ __forceinline__ void mbar_wait(uint32_t bar, uint32_t parity) {
  asm volatile("{\n.reg .pred p;\n.reg .u32 n;\nmov.u32 n, 0;\nLAB_WAIT:\n"
               "mbarrier.try_wait.parity.shared::cta.b64 p, [%0], %1;\n@p bra DONE;\n"
               "add.u32 n, n, 1;\nsetp.lt.u32 p, n, 400000;\n@p bra LAB_WAIT;\ntrap;\nDONE:\n}" :: "r"(bar), "r"(parity) : "memory");
}
__device__ __forceinline__ uint32_t mbar_try(uint32_t bar, uint32_t parity) {
  uint32_t ok;
  asm volatile("{\n.reg .pred p;\nmbarrier.test_wait.parity.shared::cta.b64 p, [%1], %2;\nselp.u32 %0, 1, 0, p;\n}" : "=r"(ok) : "r"(bar), "r"(parity) : "memory");
  return ok;
}
__device__ __forceinline__ void tma3d(uint32_t dst, const CUtensorMap* m, int c0, int c1, int c2, uint32_t bar) {
  asm volatile("cp.async.bulk.tensor.3d.shared::cluster.global.mbarrier::complete_tx::bytes [%0], [%1, {%3, %4, %5}], [%2];"
               :: "r"(dst), "l"(m), "r"(bar), "r"(c0), "r"(c1), "r"(c2) : "memory");
}
__device__ __forceinline__ void bulk_g2s(uint32_t dst, const void* src, uint32_t bytes, uint32_t bar) {
  asm volatile("cp.async.bulk.shared::cluster.global.mbarrier::complete_tx::bytes [%0], [%1], %2, [%3];" :: "r"(dst), "l"(src), "r"(bytes), "r"(bar) : "memory");
}
__device__ __forceinline__ void wg_fence() { asm volatile("wgmma.fence.sync.aligned;" ::: "memory"); }
__device__ __forceinline__ void wg_commit() { asm volatile("wgmma.commit_group.sync.aligned;" ::: "memory"); }
template <int N> __device__ __forceinline__ void wg_wait() { asm volatile("wgmma.wait_group.sync.aligned %0;" :: "n"(N) : "memory"); }
__device__ __forceinline__ void smem_fence() { asm volatile("fence.proxy.async.shared::cta;" ::: "memory"); }
__device__ __forceinline__ void stg128(void* p, uint32_t a, uint32_t b, uint32_t c, uint32_t d) { asm volatile("st.global.v4.u32 [%0], {%1,%2,%3,%4};" :: "l"(p), "r"(a), "r"(b), "r"(c), "r"(d) : "memory"); }
__device__ __forceinline__ void stg32(void* p, uint32_t v) { asm volatile("st.global.u32 [%0], %1;" :: "l"(p), "r"(v) : "memory"); }
__device__ __forceinline__ uint4 ldg128(const void* p) { uint4 v; asm volatile("ld.global.nc.L1::no_allocate.v4.u32 {%0,%1,%2,%3}, [%4];" : "=r"(v.x), "=r"(v.y), "=r"(v.z), "=r"(v.w) : "l"(p)); return v; }
__device__ __forceinline__ void publish(unsigned char* scr, int i) {
  asm volatile("{\n.reg .pred q;\nelect.sync _|q, 0xffffffff;\n@q red.relaxed.gpu.global.inc.u32 [%0], 0xffffffff;\n}" :: "l"(scr + CNT_OFF + i * 128) : "memory");
}
__device__ __forceinline__ void spin_ge(unsigned char* scr, int i, unsigned target) {
  asm volatile("{\n.reg .pred p;\n.reg .u32 n, v;\nmov.u32 n, 0;\nLAB_SPIN:\n"
               "ld." POLL ".gpu.global.u32 v, [%0];\nsetp.ge.u32 p, v, %1;\nvote.sync.all.pred p, p, 0xffffffff;\n@p bra DONE;\n"
               "add.u32 n, n, 1;\nsetp.lt.u32 p, n, 4000000;\n@p bra LAB_SPIN;\ntrap;\nDONE:\n}" :: "l"(scr + CNT_OFF + i * 128), "r"(target) : "memory");
}
__device__ __forceinline__ int lane_id() { int l; asm volatile("mov.u32 %0, %%laneid;" : "=r"(l)); return l; }
__device__ __forceinline__ uint32_t pin(uint32_t v) { return __shfl_xor_sync(0xffffffffu, v, blockIdx.y); }
__device__ __forceinline__ unsigned char* pin(unsigned char* p) { return (unsigned char*)(((uint64_t)pin((uint32_t)((uint64_t)p >> 32)) << 32) | pin((uint32_t)(uint64_t)p)); }
__device__ __forceinline__ bool elect() {
  uint32_t r; asm volatile("{\n.reg .pred p;\nelect.sync _|p, 0xffffffff;\nselp.u32 %0, 1, 0, p;\n}" : "=r"(r)); return r != 0;
}
__device__ __forceinline__ uint4 lds128(uint32_t a) { uint4 v; asm volatile("ld.shared.v4.u32 {%0,%1,%2,%3}, [%4];" : "=r"(v.x), "=r"(v.y), "=r"(v.z), "=r"(v.w) : "r"(a) : "memory"); return v; }
__device__ __forceinline__ uint2 lds64(uint32_t a) { uint2 v; asm volatile("ld.shared.v2.u32 {%0,%1}, [%2];" : "=r"(v.x), "=r"(v.y) : "r"(a) : "memory"); return v; }
__device__ __forceinline__ void sts128(uint32_t p, uint32_t a, uint32_t b, uint32_t c, uint32_t d) { asm volatile("st.shared.v4.u32 [%0], {%1,%2,%3,%4};" :: "r"(p), "r"(a), "r"(b), "r"(c), "r"(d) : "memory"); }
__device__ __forceinline__ void sts32(uint32_t a, float v) { asm volatile("st.shared.f32 [%0], %1;" :: "r"(a), "f"(v) : "memory"); }
__device__ __forceinline__ void named_sync(int id, int n) { asm volatile("bar.sync %0, %1;" :: "r"(id), "r"(n) : "memory"); }
__device__ __forceinline__ void named_arrive(int id, int n) { asm volatile("bar.arrive %0, %1;" :: "r"(id), "r"(n) : "memory"); }
__device__ __forceinline__ void named_arrive_if(uint32_t c, int id, int n) { asm volatile("{\n.reg .pred q;\nsetp.ne.u32 q, %2, 0;\n@q bar.arrive %0, %1;\n}" :: "r"(id), "r"(n), "r"(c) : "memory"); }
__device__ __forceinline__ uint64_t mkdesc(uint32_t hi, uint32_t lo) { return ((uint64_t)hi << 32) | lo; }
constexpr uint32_t HI_SW128 = 0x40000040u;
__device__ __forceinline__ uint32_t pack2(float lo, float hi) { uint32_t r; asm("cvt.rn.bf16x2.f32 %0, %1, %2;" : "=r"(r) : "f"(hi), "f"(lo)); return r; }
__device__ __forceinline__ float bf_lo(uint32_t v) { return __uint_as_float(v << 16); }
__device__ __forceinline__ float bf_hi(uint32_t v) { return __uint_as_float(v & 0xffff0000u); }
__device__ __forceinline__ float rbf(float x) { return bf_lo(pack2(x, 0.f)); }
__device__ __forceinline__ uint32_t hsub2(uint32_t a, uint32_t b) { uint32_t r; asm("sub.rn.bf16x2 %0, %1, %2;" : "=r"(r) : "r"(a), "r"(b)); return r; }
__device__ __forceinline__ uint32_t hadd2(uint32_t a, uint32_t b) { uint32_t r; asm("add.rn.bf16x2 %0, %1, %2;" : "=r"(r) : "r"(a), "r"(b)); return r; }
__device__ __forceinline__ uint32_t hmul2(uint32_t a, uint32_t b) { uint32_t r; asm("mul.rn.bf16x2 %0, %1, %2;" : "=r"(r) : "r"(a), "r"(b)); return r; }
__device__ __forceinline__ uint32_t hfma2(uint32_t a, uint32_t b, uint32_t c) { uint32_t r; asm("fma.rn.bf16x2 %0, %1, %2, %3;" : "=r"(r) : "r"(a), "r"(b), "r"(c)); return r; }
__device__ __forceinline__ float tanh_fast(float x) { float r; asm("tanh.approx.f32 %0, %1;" : "=f"(r) : "f"(x)); return r; }
__device__ __forceinline__ float rcp_fast(float x) { float r; asm("rcp.approx.ftz.f32 %0, %1;" : "=f"(r) : "f"(x)); return r; }
__device__ __forceinline__ float ex2_fast(float x) { float r; asm("ex2.approx.ftz.f32 %0, %1;" : "=f"(r) : "f"(x)); return r; }
__device__ __forceinline__ void mma16816(float (&c)[4], uint32_t a0, uint32_t a1, uint32_t a2, uint32_t a3, uint32_t b0, uint32_t b1) {
  asm volatile("mma.sync.aligned.m16n8k16.row.col.f32.bf16.bf16.f32 {%0,%1,%2,%3}, {%4,%5,%6,%7}, {%8,%9}, {%0,%1,%2,%3};"
               : "+f"(c[0]), "+f"(c[1]), "+f"(c[2]), "+f"(c[3]) : "r"(a0), "r"(a1), "r"(a2), "r"(a3), "r"(b0), "r"(b1));
}
__device__ __forceinline__ void ldsm4(uint32_t (&r)[4], uint32_t addr) {
  asm volatile("ldmatrix.sync.aligned.m8n8.x4.shared.b16 {%0,%1,%2,%3}, [%4];" : "=r"(r[0]), "=r"(r[1]), "=r"(r[2]), "=r"(r[3]) : "r"(addr) : "memory");
}
__device__ __forceinline__ void stsm4(uint32_t addr, uint32_t a, uint32_t b, uint32_t c, uint32_t d) {
  asm volatile("stmatrix.sync.aligned.m8n8.x4.shared.b16 [%0], {%1,%2,%3,%4};" :: "r"(addr), "r"(a), "r"(b), "r"(c), "r"(d) : "memory");
}

__device__ __forceinline__ float ln_rstd(float var, float eps = 1e-5f) {
  float sd;
  asm("sqrt.approx.ftz.f32 %0, %1;" : "=f"(sd) : "f"(rbf(rbf(var) + eps)));
  return rcp_fast(rbf(sd));
}
__device__ __forceinline__ float ln_var(float mean, float sq) { return fmaxf(fmaf(-mean, mean, sq * (1.0f / D_)), 0.f); }
struct LnC { uint32_t m, rh, rl; };
__device__ __forceinline__ LnC ln_consts(float sum, float sq, float eps) {
  const float mean = sum * (1.0f / D_), r = ln_rstd(ln_var(mean, sq), eps), rh = rbf(r);
  LnC c; c.m = pack2(mean, mean); c.rh = pack2(rh, rh); c.rl = pack2(r - rh, r - rh);
  return c;
}
__device__ __forceinline__ uint32_t ln_apply(uint32_t x, const LnC& c) {
  uint32_t d = hsub2(x, c.m);
  return hfma2(d, c.rh, hmul2(d, c.rl));
}

__device__ __forceinline__ void fence_code(int id) {
  asm volatile("{\n.reg .pred q;\nLAB_F:\nsetp.eq.u32 q, %0, %1;\n@q st.volatile.shared.u32 [%2], %2;\n@q bra LAB_F;\n}" :: "r"(blockIdx.x), "r"(0x70000000 + id), "r"(0) : "memory");
}
template <int N> __device__ __forceinline__ void fresh(float (&a)[N]) {
#pragma unroll
  for (int i = 0; i < N; i++) asm volatile("" : "=f"(a[i]));
}
constexpr int B_EMPTY = 64, B_X = 384, B_KV = 192, B_WQ = 248, B_HALO = 256, B_RES = 264, B_ATT = 272, B_GATE = 280, B_WO = 304, B_O = 312, B_XW = 320, B_WQ2 = 328, B_T0 = 336;

template <int TA>
__device__ __forceinline__ void gemm_issue(float (&acc)[56], uint32_t la, uint32_t lo, int sc) {
  wg_fence();
#pragma unroll
  for (int k = 0; k < 4; k++)
    wgmma_n112<TA, 1>(acc, mkdesc(TA ? HI_SW128 : 8, la + (TA ? 512u << 16 : 64u << 16) + k * 128), mkdesc(8, lo + (112u << 16) + 512 + k * 224), sc | k);
  wg_commit();
}
template <int TA>
__device__ __forceinline__ void gemm_stage(float (&acc)[56], uint32_t base, int it, int sc) {
  mbar_wait(base + OFF_BAR + (it & 7) * 8, (it >> 3) & 1);
  const uint32_t lo = (base >> 4) + (it & 7) * (SLOT >> 4);
  gemm_issue<TA>(acc, lo, lo, sc);
}
template <int TA, int EXTRA = 0>
__device__ __forceinline__ void gemm_loop(float (&acc)[56], uint32_t base, int it, int end, bool rel, int oi, uint32_t ok = 0, int gate_it = -1, uint32_t gate = 0) {
#pragma unroll 1
  for (; it < end;) {
    if (__builtin_expect(!ok, 0)) mbar_wait(base + OFF_BAR + (it & 7) * 8, (it >> 3) & 1);
    const uint32_t lo = (base >> 4) + (it & 7) * (SLOT >> 4);
    gemm_issue<TA>(acc, (unsigned)(it - XS) < EXTRA ? ((base + OFF_XW) >> 4) + (it - XS) * 512 : lo, lo, 1);
    OBS(SOBS && rel, oi + it);
    it++;
    ok = mbar_try(base + OFF_BAR + (it & 7) * 8, (it >> 3) & 1);
    wg_wait<1>();
    if (rel || it == gate_it) mbar_arrive(rel ? base + OFF_BAR + B_EMPTY + ((it - 2) & 7) * 8 : gate);
  }
}
template <int PER>
__device__ __forceinline__ void produce_box(uint32_t base, int it, int end, const CUtensorMap* mp, int c0, int c1, uint32_t tn = 0) {
#pragma unroll 1
  for (; it < end; it++) {
    const uint32_t fb = base + OFF_BAR + (it & 7) * 8;
    mbar_wait(fb + B_EMPTY, (it >> 3) & 1);
    if (PER) { while ((int)(clock() - tn) < 0); tn += PER; }
    if (elect()) { mbar_expect_tx(fb, 8192); tma3d(base + (it & 7) * SLOT, mp, c0, c1, 0, fb); }
    c1 += 64;
  }
}
template <int PER>
__device__ __forceinline__ void produce_lin(uint32_t base, int it, int end, const unsigned char* src, uint32_t bytes, uint32_t tn = 0) {
#pragma unroll 1
  for (; it < end; it++) {
    const uint32_t fb = base + OFF_BAR + (it & 7) * 8;
    mbar_wait(fb + B_EMPTY, (it >> 3) & 1);
    if (PER) { while ((int)(clock() - tn) < 0); tn += PER; }
    if (elect()) { mbar_expect_tx(fb, bytes); bulk_g2s(base + (it & 7) * SLOT + (bytes & 2048) * 4, src, bytes, fb); }
    src += bytes;
  }
}

__device__ __forceinline__ void retile_wo(const unsigned char* wo, unsigned char* scr, int u, int lane) {
  const int r8 = lane & 7, mi = lane >> 3;
  const unsigned char* src = wo + ((u >> 1) * 8 + r8) * 896 + ((u & 1) * 28 + mi) * 16;
  unsigned char* dst = scr + ((u & 1) * 2 * HU_T + 60 + (u >> 4)) * BT + ((u >> 1) & 7) * 1792 + mi * 128 + r8 * 16;
  uint4 v[7];
#pragma unroll
  for (int i = 0; i < 7; i++) v[i] = ldg128(src + i * 64);
#pragma unroll
  for (int i = 0; i < 7; i++) stg128(dst + i * 512 + ((i * 4 + mi) / 14) * (HU_T * BT - 1792), v[i].x, v[i].y, v[i].z, v[i].w);
  publish(scr, C_WO);
}

struct Params {
  const unsigned char *wqkv, *wo, *w1, *b1, *w2, *b2;
  unsigned char *out, *scr;
};

__global__ void __launch_bounds__(NTHREADS, 1)
fused_kernel(const __grid_constant__ CUtensorMap m_x, const __grid_constant__ CUtensorMap m_wkv, const __grid_constant__ CUtensorMap m_wq,
             const __grid_constant__ CUtensorMap m_w1, const __grid_constant__ CUtensorMap m_w2, const __grid_constant__ CUtensorMap m_res, const Params p) {
  extern __shared__ __align__(1024) unsigned char smem_raw[];
  constexpr uint32_t base = 1024, bars = base + OFF_BAR;
  const int tid = threadIdx.x, lane = tid & 31, b = blockIdx.x;
  const int rb = (b >> 2) & 15, hp = ((b >> 6) << 2) | (b & 3);
  const int wcol = hp * 56 - (hp & 1) * 8;
  auto load_kv = [&](int s) { mbar_expect_tx(bars + B_KV + s * 8, 16384); tma3d(base + s * 16384, &m_wkv, s >= FAKE ? wcol & ~63 : wcol, s * 64, 1, bars + B_KV + s * 8); };
  if (tid < 32) {
    if (elect()) {
#pragma unroll
      for (int i = 0; i < 7; i++) mbar_init(bars + B_X + i * 8, 1);
      asm volatile("fence.mbarrier_init.release.cluster;" ::: "memory");
#pragma unroll
      for (int i = 0; i < 7; i++) { mbar_expect_tx(bars + B_X + i * 8, 16384 >> XSPLIT); tma3d(base + OFF_X + i * 16384 + XSPLIT * 8192, &m_x, i * 64, rb * 128 + XSPLIT * 64, 0, bars + B_X + i * 8); }
#pragma unroll
      for (int i = 0; i < 7; i++) { mbar_init(bars + B_KV + i * 8, 1); if (XSPLIT) mbar_init(bars + B_X + 64 + i * 8, 1); }
      asm volatile("fence.mbarrier_init.release.cluster;" ::: "memory");
      if (XSPLIT) {
#pragma unroll
        for (int i = 0; i < XK; i++) load_kv(i);
#pragma unroll
        for (int i = 0; i < 7; i++) { mbar_expect_tx(bars + B_X + 64 + i * 8, 8192); tma3d(base + OFF_X + i * 16384, &m_x, i * 64, rb * 128, 0, bars + B_X + 64 + i * 8); }
      }
#pragma unroll 1
      for (int i = XSPLIT * XK; i < NW0; i++) load_kv(i);
    }
  }
  const int warp = __shfl_sync(0xffffffffu, tid >> 5, 0);
  if (TS && tid == 64) sts32(bars + B_T0, __uint_as_float(clock() + TS));
  if (warp == 1) {
    if (elect()) {
#pragma unroll
      for (int i = 0; i < 16; i++) mbar_init(bars + i * 8, 2);
#pragma unroll
      for (int i = 0; i < 11; i++) mbar_init(bars + B_WQ + i * 8, 1);
      asm volatile("fence.mbarrier_init.release.cluster;" ::: "memory");
      if (smem_u32(smem_raw) != base) asm volatile("trap;");
    }
  }
  const int dt = b & 3, mt = b >> 2;
  const bool g1 = (b & 15) < 14;
  const int a1 = b - 2 * (b >> 4), ft = a1 >> 2, d1 = a1 & 3;
  const int g = lane >> 2, t = lane & 3, r8 = lane & 7, mi = lane >> 3;
  OBSG(FREQ && tid == 160, 128, 160);
  __syncthreads();
  if (warp >= 8) {
    asm volatile("setmaxnreg.dec.sync.aligned.u32 40;");
    const int pw = warp - 8;
    unsigned char* scr = p.scr;
    if (WPF && pw == 2) {
      mbar_wait(bars + B_X + (WPF - 1) * 8, 0);
      if (b < 112 && lane < 28) asm volatile("prefetch.global.L2 [%0];" :: "l"(p.wqkv + (b * 4 + lane / 7) * 2688 + (lane % 7) * 128) : "memory");
      if (lane == 31) asm volatile("prefetch.tensormap [%0];" :: "l"(&m_wq) : "memory");
      __syncwarp();
    }
    if (NW0 < 7 && pw == 3) {
      mbar_wait(bars + B_X, 0);
      if (elect()) {
#pragma unroll 1
        for (int i = NW0; i < 7; i++) load_kv(i);
      }
      __syncwarp();
    }
    {
      const int c0 = pw * 14 + (mi >> 1);
      unsigned char* dst = scr + (pw * HU_T + rb * 2 + (hp >> 2)) * BT + ((hp & 3) * 2 + (mi & 1)) * 1792 + (mi >> 1) * 128 + r8 * 16;
      const uint32_t xs = base + OFF_X + (hp * 16 + (lane & 15)) * 128;
      uint4 H[7];
      named_sync(9, 160);
#pragma unroll
      for (int i = 0; i < 7; i++) H[i] = lds128(xs + ((c0 + 2 * i) >> 3) * 16384 + ((((c0 + 2 * i) & 7) ^ r8) << 4));
      asm volatile("" :: "r"(H[6].w), "r"(H[0].x) : "memory");
      if (pw != 3) named_arrive(8, 384);
      else {
        named_sync(8, 384);
        if (elect()) {
          mbar_expect_tx(bars + B_WQ, 28672); tma3d(base + OFF_WQ, &m_wq, FAKE < 8 ? wcol & ~63 : wcol, 0, 0, bars + B_WQ);
          mbar_expect_tx(bars + B_WQ2, 28672); tma3d(base + OFF_WQ + 28672, &m_wq, FAKE < 8 ? wcol & ~63 : wcol, 224, 0, bars + B_WQ2);
        }
        __syncwarp();
      }
      const uint2 st = lds64(base + OFF_LN + (lane & 15) * 8);
      const float sum = __uint_as_float(st.x), mean = sum * (1.0f / D_), var = ln_var(mean, __uint_as_float(st.y));
      const float m = rbf(mean), r = ln_rstd(var), r2 = ln_rstd(var * r * r);
      const float nc = fmaf(m, (float)D_, -sum) * (1.0f / D_) * (r * r2);
      const uint32_t m2 = pack2(m, m), r2x = pack2(r * r2, r * r2), nc2 = pack2(nc, nc);
      auto f = [&](uint32_t v) { return hfma2(hsub2(v, m2), r2x, nc2); };
#pragma unroll
      for (int i = 0; i < 7; i++) stg128(dst + i * 256, f(H[i].x), f(H[i].y), f(H[i].z), f(H[i].w));
      if (pw != 1) named_arrive(4, 128);
      else { named_sync(4, 128); publish(scr, C_H + (b & 3)); }
      OBS(tid == 288, 4);
    }
    const int lane = lane_id();
    if (pw == 0) {
      if (elect()) {
        asm volatile("prefetch.tensormap [%0];" :: "l"(&m_w1) : "memory");
        asm volatile("prefetch.tensormap [%0];" :: "l"(&m_w2) : "memory");
        asm volatile("prefetch.tensormap [%0];" :: "l"(&m_res) : "memory");
      }
      if (g1) produce_box<0>(base, 0, 32, &m_w1, ft * 64, 0);
      auto load_res = [&]() { if (elect()) { mbar_expect_tx(bars + B_RES, BT); tma3d(base + OFF_Q, &m_res, dt * 112, mt * 64, 0, bars + B_RES); } };
      if (RESP == 0) { mbar_wait(bars + B_ATT, 0); load_res(); }
      mbar_wait(bars + B_WO, 0);
      produce_lin<0>(base, 0, 7, scr + (dt * HU_T + 60) * BT, BT);
      if (NX) {
        produce_box<0>(base, 7, XT, &m_w2, mt * 64, 0);
        if (elect()) {
          mbar_expect_tx(bars + B_XW, NX * 8192);
#pragma unroll 1
          for (int i = 0; i < NX; i++) tma3d(base + OFF_XW + i * 8192, &m_w2, mt * 64, (XS - 7 + i) * 64, 0, bars + B_XW);
        }
        __syncwarp();
        produce_box<0>(base, XT, XS, &m_w2, mt * 64, (XT - 7) * 64);
        mbar_wait(bars + B_XW, 0);
#pragma unroll 1
        for (int it = XS; it < XS + NX; it++) { mbar_wait(bars + B_EMPTY + (it & 7) * 8, (it >> 3) & 1); if (lane == 0) mbar_arrive(bars + (it & 7) * 8); }
        __syncwarp();
        produce_box<0>(base, XS + NX, 35, &m_w2, mt * 64, (XS + NX - 7) * 64);
      } else produce_box<0>(base, 7, 35, &m_w2, mt * 64, 0);
      if (RESP) load_res();
    } else if (pw == 1) {
      if (g1) {
        spin_ge(scr, C_H + (lane & 3), 32);
        OBS(lane == 0, 16);
        if (HP) { produce_lin<HP>(base, 0, 8, scr + d1 * HU_T * BT, BT, clock()); produce_lin<0>(base, 8, 32, scr + (d1 * HU_T + 8) * BT, BT); }
        else produce_lin<0>(base, 0, 32, scr + d1 * HU_T * BT, BT);
      }
      mbar_wait(bars + B_O, 0);
      produce_lin<OPP>(base, 0, 7, scr + O_OFF + mt * 57344, 8192, clock());
      const unsigned char* us = scr + (dt * HU_T + 32) * BT;
#pragma unroll
      for (int i = 0; i < NPRE; i++) {
        mbar_wait(bars + B_EMPTY + ((7 + i) & 7) * 8, i > 0);
        if (elect()) mbar_expect_tx(bars + ((7 + i) & 7) * 8, BT);
        __syncwarp();
      }
      spin_ge(scr, C_U + (ALL4 ? lane & 3 : dt) + (mt & (UREP - 1)) * 4, 28);
      if (elect()) {
#pragma unroll
        for (int i = 0; i < NPRE; i++) bulk_g2s(base + ((7 + i) & 7) * SLOT + 8192, us + i * BT, BT, bars + ((7 + i) & 7) * 8);
      }
      const uint32_t tu = clock();
      OBS(lane == 0, 18);
      produce_lin<UP>(base, 7 + NPRE, 15, us + NPRE * BT, BT, tu + NPRE * UP - U0);
      produce_lin<0>(base, 15, 35, us + 8 * BT, BT);
      unsigned tk = 0;
      if (lane == 0) tk = atomicAdd((unsigned*)(scr + CNT_OFF + C_TK * 128), 1u);
      if (__shfl_sync(0xffffffffu, tk, 0) == 127) {
#pragma unroll 1
        for (int i = lane; i < 192; i += 32) *(unsigned*)(scr + CNT_OFF + i * 128) = 0;
      }
    } else if (pw == 2) {
      uint32_t tn = clock() + PACE0 + b * STAG;
      const unsigned char* src = p.w1 + b * 4096 + lane * 128;
#pragma unroll 1
      for (int i = 0; i < 28 + FREQ * 2; i++) {
        while ((int)(clock() - tn) < 0) __nanosleep(20);
        if (i == 14) src = p.w2 + b * 4096 + lane * 128;
        if (i < 28) asm volatile("prefetch.global.L2 [%0];" :: "l"(src) : "memory");
        OBSG(FREQ && lane == 0, 129 + i, 161 + i);
        src += 128 * 4096;
        tn += i < 14 ? PACE1 : PACE2;
      }
    } else {
      if (b < 112) retile_wo(p.wo, scr, b, lane_id());
      const int lane = lane_id();
      unsigned char* hg = scr + HALO_OFF + (rb * 8 + hp) * 3584 + lane * 16;
      named_sync(1, 64);
      if (rb < 15) {
        uint4 v[7];
#pragma unroll
        for (int i = 0; i < 7; i++) v[i] = lds128(base + OFF_K + 8 * 3584 + i * 512 + lane * 16);
#pragma unroll
        for (int i = 0; i < 7; i++) stg128(hg + i * 512, v[i].x, v[i].y, v[i].z, v[i].w);
        publish(scr, C_HALO + rb * 8 + hp);
      }
      OBS(lane == 0, 29);
      if (rb > 0) {
        spin_ge(scr, C_HALO + (rb - 1) * 8 + hp, 1);
        OBS(lane == 0, 12);
        if (elect()) { mbar_expect_tx(bars + B_HALO, 3584); bulk_g2s(base + OFF_K, scr + HALO_OFF + ((rb - 1) * 8 + hp) * 3584, 3584, bars + B_HALO); }
      } else {
#pragma unroll
        for (int i = 0; i < 7; i++) sts128(base + OFF_K + i * 512 + lane * 16, 0, 0, 0, 0);
        smem_fence();
        __syncwarp();
        if (lane == 0) mbar_arrive(bars + B_HALO);
      }
      __syncwarp();
      spin_ge(scr, C_WO, 112);
      if (lane == 0) mbar_arrive(bars + B_WO);
      mbar_wait(bars + B_ATT, 0);
      spin_ge(scr, C_O + (mt >> 1), 8);
      OBS(lane == 0, 17);
      if (lane == 0) mbar_arrive(bars + B_O);
    }
  } else {
    asm volatile("setmaxnreg.inc.sync.aligned.u32 232;");
    const int wg = warp >> 2, w4 = warp & 3, th = wg ^ 1;
    const bool rel = (tid & 127) < 2;
    unsigned char* scr = p.scr;
    uint32_t X[28][4];
    float aq[28];
    const uint32_t dlo = (base >> 4) + (512u << 16) + (hp & 1), dlq = dlo + (OFF_WQ >> 4);
    {
      uint32_t xa[4];
#pragma unroll
      for (int k = 0; k < 4; k++) xa[k] = base + OFF_X + (th * 64 + w4 * 16 + (mi >> 1) * 8 + r8) * 128 + (((2 * k + (mi & 1)) ^ r8) << 4);
      float c0[2][4] = {}, c1[2][4] = {};
      uint32_t one[8];
#pragma unroll
      for (int j = 0; j < 8; j++) asm volatile("{\n.reg .u32 y;\nmov.u32 y, %%tid.y;\nmad.lo.u32 %0, y, %1, 0x3f803f80;\n}" : "=r"(one[j]) : "r"(lane + j));
      asm volatile("" : "+l"(scr));
      uint32_t ok = 0;
      const uint32_t bx = bars + B_X + XSPLIT * wg * 64;
      if (HEAT) {
#pragma unroll 1
        for (int n = 0; n < 64 && !ok; n++) { mma16816(c0[0], 0, 0, 0, 0, 0, 0); ok = mbar_try(bars + B_X, 0); }
        if (XSPLIT && wg) ok = 0;
      }
#pragma unroll
      for (int i = 0; i < 8; i++) {
        if (i < 7) {
          if (!ok) mbar_wait(bx + i * 8, 0);
          OBS(tid == 64 && i == 0, 0); OBS(tid == 64 && i == 6, 15);
#pragma unroll
          for (int k = 0; k < 4; k++) ldsm4(X[i * 4 + k], xa[k] + i * 16384);
          if (i < 6) ok = mbar_try(bx + i * 8 + 8, 0);
        }
        if (i > 0) {
#pragma unroll
          for (int k = i * 4 - 4; k < i * 4; k++) {
            mma16816(c0[k & 1], X[k][0], one[(k & 1) * 4], X[k][1], one[(k & 1) * 4 + 1], X[k][0], X[k][1]);
            mma16816(c1[k & 1], X[k][2], one[(k & 1) * 4 + 2], X[k][3], one[(k & 1) * 4 + 3], X[k][2], X[k][3]);
          }
        }
      }
      float st[4];
#pragma unroll
      for (int j = 0; j < 2; j++) {
        st[j] = __shfl_sync(0xffffffffu, (g & 1) ? c0[0][2 * j + 1] + c0[1][2 * j + 1] : c0[0][2 * j] + c0[1][2 * j], (lane & 28) | (g >> 1));
        st[2 + j] = __shfl_sync(0xffffffffu, (g & 1) ? c1[0][2 * j + 1] + c1[1][2 * j + 1] : c1[0][2 * j] + c1[1][2 * j], (lane & 28) | (g >> 1));
      }
      named_arrive(8, 384);
      asm volatile("{\n.reg .pred q;\nsetp.ne.u32 q, %3, 0;\n@q st.shared.v2.f32 [%0], {%1,%2};\n@q bar.arrive 9, 160;\n}"
                   :: "r"(base + OFF_LN + ((t & 1) * 8 + g) * 8), "f"((t & 1) ? st[3] : st[1]), "f"((t & 1) ? st[2] : st[0]), "r"((uint32_t)((warp ^ 4) == hp)) : "memory");
      ok = mbar_try(bars + B_KV, 0);
      LnC l0, l1;
      float eps = 1e-5f;
#pragma unroll 1
      do {
        l0 = ln_consts(st[1], st[0], eps); l1 = ln_consts(st[3], st[2], eps);
#pragma unroll
        for (int k = 0; k < PRE * 16; k++) X[k >> 2][k & 3] = hsub2(X[k >> 2][k & 3], k & 2 ? l1.m : l0.m);
        eps += eps;
      } while ((l0.rl ^ l1.rl) == 4);
      OBS(tid == 32, 1);
      float ak[60], *av = ak + 32;
      const int pp_in = wg ? 6 : 0, pp_out = wg ? 0 : 6;
#pragma unroll
      for (int s = 0; s < 7; s++) {
#pragma unroll
        for (int k = s * 4; k < s * 4 + 4; k++) {
          if (s < PRE) {
            auto f = [&](uint32_t d, const LnC& l) { return hfma2(d, l.rh, hmul2(d, l.rl)); };
            const uint32_t y = f(X[k][1], l0);
            X[k][0] = f(X[k][0], l0); X[k][1] = f(X[k][2], l1); X[k][2] = y; X[k][3] = f(X[k][3], l1);
          } else {
            const uint32_t y = ln_apply(X[k][1], l0);
            X[k][0] = ln_apply(X[k][0], l0); X[k][1] = ln_apply(X[k][2], l1); X[k][2] = y; X[k][3] = ln_apply(X[k][3], l1);
          }
        }
        if (__builtin_expect(!ok, 0)) { mbar_wait(bars + B_KV + s * 8, 0); if (s == 6) mbar_wait(bars + B_WQ, 0); }
        if (s == 0) fresh(ak);
        if (s == 6) { wg_wait<0>(); if ((tid & 127) == 0) mbar_arrive(bars + B_EMPTY + 3 * 8); }
        OBS(KOBS && (tid & 127) == 0, 40 + wg * 32 + s);
        if (PPM == 2 ? (wg ? s < 6 : s > 1) : (wg || s)) named_sync(pp_in, 256);
        OBS(KOBS && (tid & 127) == 32, 48 + wg * 32 + s);
        OBS(tid == 64 && s == 0, 2);
        wg_fence();
#pragma unroll
        for (int k = 0; k < 4; k++) {
          wgmma_rs_n120<1>(ak, X[s * 4 + k], mkdesc(HI_SW128, dlo + s * 1024 + k * 128), (s | k) != 0);
        }
        wg_commit();
        if (s == 6) {
          fresh(aq);
#pragma unroll
          for (int k = 0; k < 4 * QA; k++) {
            if (k == 4 * QA - PQE) named_arrive(pp_out, 256);
            wgmma_rs_n56<1>(aq, X[k], mkdesc(HI_SW128, dlq + k * 128), k);
          }
          wg_commit();
        }
        if (s < 6 || PQE == 0) named_arrive_if(PPM != 2 || (wg ? s != 5 : s != 0), pp_out, 256);
        fence_code(s);
        OBS(KOBS && (tid & 127) == 64, 56 + wg * 32 + s);
        if (s < 6) ok = mbar_try(bars + B_KV + s * 8 + 8, 0);
        if (s == 5) ok &= mbar_try(bars + B_WQ, 0);
        OBS(tid == 64 && s == 1, 28); OBS(tid == 64 && s == 5, 31);
        if (s > 0) wg_wait<1>();
        OBS(KOBS && (tid & 127) == 96, 64 + wg * 32 + s);
        if ((s == 2 || s == 3 || s == 5) && (tid & 127) == 0) mbar_arrive(bars + B_EMPTY + (s == 5 ? 2 : s - 2) * 8);
      }
      if ((tid & 127) == 0) mbar_arrive(bars + B_EMPTY + 4 * 8);
      OBS(tid == 32, 3);
      {
        const uint32_t kst = base + OFF_K + (2 + (warp ^ 4) * 2 + (mi & 1)) * 1792 + (mi >> 1) * 896 + r8 * 16;
#pragma unroll
        for (int n = 0; n < 7; n++)
          stsm4(kst + n * 128, pack2(ak[n * 4], ak[n * 4 + 1]), pack2(ak[n * 4 + 2], ak[n * 4 + 3]), pack2(av[n * 4], av[n * 4 + 1]), pack2(av[n * 4 + 2], av[n * 4 + 3]));
        named_arrive_if(warp == 3, 1, 64);
      }
      OBS(tid == 96, 32); OBS(tid == 224, 34);
      wg_wait<0>();
      if ((tid & 127) == 0) mbar_arrive(bars + B_EMPTY + 5 * 8);
      mbar_wait(bars + B_WQ2, 0);
    }
    const unsigned short *bp1 = (const unsigned short*)p.b1 + (g1 ? ft * 64 : 0) + w4 * 16 + g, *bp2 = (const unsigned short*)p.b2 + mt * 64 + w4 * 16 + g;
    const uint32_t braw[4] = {__ldg(bp1), __ldg(bp1 + 8), __ldg(bp2), __ldg(bp2 + 8)};
    auto q_rest = [&]() {
      wg_fence();
#pragma unroll
      for (int s = QA; s < 7; s++) {
#pragma unroll
        for (int k = s * 4; k < s * 4 + 4; k++) wgmma_rs_n56<1>(aq, X[k], mkdesc(HI_SW128, dlq + k * 128), 1);
        wg_commit();
        if (s == 5) { wg_wait<2>(); if ((tid & 127) == 0) mbar_arrive(bars + B_EMPTY + 6 * 8); }
      }
    };
    uint32_t Q[4][4];
    auto q_pack = [&]() {
#pragma unroll
      for (int n = 0; n < 14; n++) { const int m = n + 2 * (n > 7); Q[m >> 2][m & 3] = pack2(aq[n * 2], aq[n * 2 + 1]); }
#pragma unroll
      for (int h = 0; h < 2; h++) { Q[2][h] = t < 2 ? 0u : Q[1][2 + h]; Q[1][2 + h] = t < 2 ? Q[1][2 + h] : 0u; }
    };
    float acc[56];
    auto ai = [](int p) { return p < 4 ? 48 + (p & 1) * 4 + (p & 2) : (p - 4) * 4; };
    uint32_t xch, ts, tl;
    unsigned char *ug, *uc, *outp, *outq;
    auto setup_u = [&]() {
      xch = pin(base + OFF_K + (tid & 127) * 16);
      ug = pin(scr + (d1 * HU_T + 32 + ft) * BT + w4 * 3584 + lane * 4 + wg * 1792);
      uc = pin(scr + CNT_OFF + (C_U + d1 + (lane & (UREP - 1)) * 4) * 128);
    };
    auto setup_out = [&]() {
      const uint32_t tb = base + OFF_K + 6144 + warp * 2560;
      ts = pin(tb + mi * 160 + r8 * 16); tl = pin(tb + t * 160 + g * 16);
      unsigned char* o = p.out + (mt * 64 + w4 * 16 + g) * 896 + dt * 224;
      outp = pin(o + th * 7168 + t * 16); outq = pin(o + (t >> 1) * 7168 + 192 + (t & 1) * 16);
    };
    auto give = [&](const float (&a)[56], int id) {
#pragma unroll
      for (int i = 0; i < 48; i += 16) sts128(xch + i * 128, pack2(a[i + 2], a[i + 3]), pack2(a[i + 6], a[i + 7]), pack2(a[i + 10], a[i + 11]), pack2(a[i + 14], a[i + 15]));
      named_arrive(id, 256);
    };
    auto take = [&](uint32_t (&r)[12], int id) {
      named_sync(id, 256);
#pragma unroll
      for (int i = 0; i < 3; i++) { const uint4 v = lds128(xch + i * 2048); r[i * 4] = v.x; r[i * 4 + 1] = v.y; r[i * 4 + 2] = v.z; r[i * 4 + 3] = v.w; }
    };
    float hv[32];
    auto keep_h = [&](int i) {
      const float hb0 = 0.5f * bf_lo(braw[i]), hb1 = 0.5f * bf_lo(braw[i + 1]);
#pragma unroll
      for (int j = 0; j < 32; j++) hv[j] = fmaf(acc[ai(j >> 1) + (j & 1)], 0.5f, j >= 4 && j < 8 ? hb1 : hb0);
    };
    auto take_h = [&](int i) {
      const float hb1 = 0.5f * bf_lo(braw[i + 1]);
      uint32_t r[12];
      take(r, 5);
#pragma unroll
      for (int j = 0; j < 12; j++) { hv[8 + 2 * j] = fmaf(bf_lo(r[j]), 0.5f, hb1); hv[9 + 2 * j] = fmaf(bf_hi(r[j]), 0.5f, hb1); }
    };
    uint4 Xr[4];
    auto get_x = [&]() {
      const uint32_t xr = base + OFF_Q + (w4 * 16 + g) * 224;
      mbar_wait(bars + B_RES, 0);
      Xr[0] = lds128(xr + (t >> 1) * 1792 + 192 + (t & 1) * 16);
#pragma unroll
      for (int i = 1; i < 4; i++) Xr[i] = lds128(xr + th * 1792 + t * 16 + (i - 1) * 64);
    };
    auto gelu = [&](int j) {
      const float h0 = hv[2 * j], h1 = hv[2 * j + 1];
      const float t0 = tanh_fast(h0 * fmaf(h0 * h0, 0.2854192648f, 1.5957691216f)), t1 = tanh_fast(h1 * fmaf(h1 * h1, 0.2854192648f, 1.5957691216f));
      stg32(ug + (ai(j) & 2) * 896 + (ai(j) >> 2) * 128, pack2(fmaf(h0, t0, h0), fmaf(h1, t1, h1)));
    };
    uint32_t Sv[16];
    auto gate = [&](int i) {
      uint32_t R[4];
#pragma unroll
      for (int q = 0; q < 4; q++) {
        const int j = i * 4 + q;
        const float h0 = hv[2 * j], h1 = hv[2 * j + 1];
        R[q] = hmul2(Sv[j], pack2(fmaf(h0, tanh_fast(h0), h0), fmaf(h1, tanh_fast(h1), h1)));
      }
      stsm4(ts + i * 640, R[0], R[1], R[2], R[3]);
    };
    auto leave = [&](int i) {
      __syncwarp();
      const uint4 v = lds128(tl + i * 640), x = Xr[i];
      stg128(i ? outp + (i - 1) * 64 : outq, hadd2(x.x, v.x), hadd2(x.y, v.y), hadd2(x.z, v.z), hadd2(x.w, v.w));
    };
    if (wg == 0) {
      named_sync(0, 256);
      OBS(tid == 96, 14);
      q_rest();
      named_arrive(6, 256);
      wg_wait<0>();
      if (tid == 0) mbar_arrive(bars + B_EMPTY + 7 * 8);
      q_pack();
      const uint32_t qst = base + OFF_Q + 8192 + (mi >> 1) * 1024 + (w4 * 16 + (mi & 1) * 8 + r8) * 16;
#pragma unroll
      for (int n = 0; n < 4; n++) stsm4(qst + n * 2048, Q[n][0], Q[n][1], Q[n][2], Q[n][3]);
      smem_fence();
      named_arrive(7, 256);
      OBS(tid == 32, 5);
      fresh(acc);
      setup_u();
      if (g1) {
        mbar_wait(bars, 0); mbar_wait(bars + 8, 0);
        if (TS) {
          const uint32_t tg = lds64(bars + B_T0).x;
          while ((int)(clock() - tg) < 0);
        }
        named_sync(0, 256);
        gemm_issue<1>(acc, base >> 4, base >> 4, 0);
        OBS(tid == 0, 20);
        gemm_loop<1>(acc, base, 1, 32, rel, 40, 1, tid == 32 ? J1 : tid == 64 ? J2 : tid == 96 ? J3 : -1, bars + B_GATE - 8 + w4 * 8);
        wg_wait<0>();
        OBS(tid == 0, 21);
        give(acc, 5);
        mbar_arrive_if(rel, bars + B_EMPTY + 7 * 8);
        fence_code(30);
        keep_h(0);
#pragma unroll
        for (int j = 0; j < 16; j++) { gelu(j); if (j % GCH == GCH - 1 && j < 15) fence_code(8 + j); }
        if (w4) named_arrive(2, 256);
        else { named_sync(2, 256); asm volatile("{\n.reg .pred q;\nsetp.lt.u32 q, %1, %2;\n@q red.relaxed.gpu.global.add.u32 [%0], 1;\n}" :: "l"(uc), "r"(lane), "n"(UREP) : "memory"); OBS(tid == 0, 9); }
      } else {
        if (lane == 0 && w4) mbar_arrive(bars + B_GATE - 8 + w4 * 8);
      }
      setup_out();
      if (!RESP) get_x();
      uint32_t r[12];
      take(r, 3);
#pragma unroll
      for (int j = 0; j < 16; j++) Sv[j] = r[j < 4 ? 0 : j - 4];
      asm volatile("" :: "r"(r[0]), "r"(r[11]) : "memory");
      named_arrive(10, 256);
      if (RESP) get_x();
      take_h(2);
    } else {
      const uint32_t dq = ((base + OFF_Q) >> 4) + (64u << 16), dk = (base + OFF_K) >> 4;
      const bool odd = g & 1, early = 2 * t + (g & 1) > g;
      uint32_t selA[5], selB[4];
#pragma unroll
      for (int j = 0; j < 5; j++) selA[j] = j == w4 + (early ? 0 : 1) ? (odd ? 0x1044u : 0x4410u) : 0x4444u;
#pragma unroll
      for (int j = 0; j < 4; j++) selB[j] = j == w4 ? (odd ? 0x3244u : 0x4432u) : 0x4444u;
      float Sc[2][40], Op[2][2][16];
      uint32_t A[2][5][4];
      auto scores = [&](int T) {
        fresh(Sc[0]); fresh(Sc[1]);
#pragma unroll
        for (int k = 0; k < 2; k++) {
#pragma unroll
          for (int hh = 0; hh < 2; hh++)
            if (T) wgmma_n80<0, 0>(Sc[hh], mkdesc(8, dq + 512 + hh * 256 + k * 128), mkdesc(112, dk + (8u << 16) + 896 + hh * 24 + k * 16), k);
            else wgmma_rs_n80<0>(Sc[hh], Q[hh * 2 + k], mkdesc(112, dk + (8u << 16) + hh * 24 + k * 16), k);
        }
      };
      auto softmax = [&](int T) {
#pragma unroll
        for (int hh = 0; hh < 2; hh++) {
          uint32_t pp[2];
#pragma unroll
          for (int h = 0; h < 2; h++) {
            float c[3];
#pragma unroll
            for (int n = 0; n < 3; n++) {
              const float* q = Sc[hh] + (h + n) * 4 + 2 * h;
              asm("{\n.reg .pred p, a, b, c;\nsetp.ne.u32 p, %9, 0;\nsetp.eq.u32 a, %10, 1;\nsetp.eq.u32 b, %10, 2;\nsetp.eq.u32 c, %10, 3;\n"
                  "selp.f32 %0, %2, %1, p;\n@a selp.f32 %0, %4, %3, p;\n@b selp.f32 %0, %6, %5, p;\n@c selp.f32 %0, %8, %7, p;\n}"
                  : "=&f"(c[n]) : "f"(q[0]), "f"(q[1]), "f"(q[8]), "f"(q[9]), "f"(q[16]), "f"(q[17]), "f"(q[24]), "f"(q[25]), "r"((uint32_t)odd), "r"((tid >> 5) & 3));
            }
            uint32_t pk = pack2(early ? c[0] : c[2], c[1]);
            pk = pack2(bf_lo(pk) * SCALE, bf_hi(pk) * SCALE);
            float l0 = bf_lo(pk), l1 = bf_hi(pk);
            if (T == 0 && w4 == 0 && rb == 0) { if (early) l0 = -1e9f; if (h == 0) l1 = -1e9f; }
            float mx = fmaxf(l0, l1);
            mx = fmaxf(mx, __shfl_xor_sync(0xffffffffu, mx, 1));
            mx = fmaxf(mx, __shfl_xor_sync(0xffffffffu, mx, 2));
            float p0 = ex2_fast((l0 - mx) * LOG2E), p1 = ex2_fast((l1 - mx) * LOG2E);
            float sm = p0 + p1;
            sm += __shfl_xor_sync(0xffffffffu, sm, 1);
            sm += __shfl_xor_sync(0xffffffffu, sm, 2);
            const float inv = rcp_fast(sm);
            pp[h] = pack2(p0 * inv, p1 * inv);
          }
#pragma unroll
          for (int j = 0; j < 5; j++) {
            A[hh][j][0] = __byte_perm(pp[0], 0, selA[j]); A[hh][j][1] = j ? __byte_perm(pp[1], 0, selB[j ? j - 1 : 0]) : 0u;
            A[hh][j][2] = j < 4 ? __byte_perm(pp[0], 0, selB[j & 3]) : 0u; A[hh][j][3] = __byte_perm(pp[1], 0, selA[j]);
          }
        }
      };
      auto values = [&](int T) {
        fresh(Op[T][0]); fresh(Op[T][1]);
#pragma unroll
        for (int j = 0; j < 5; j++)
#pragma unroll
          for (int hh = 0; hh < 2; hh++) {
            wgmma_rs_n32<1>(Op[T][hh], A[hh][j], mkdesc(8, dk + (112u << 16) + 56 + T * 896 + hh * 24 + j * 224), j);
          }
        wg_commit();
      };
      uint32_t Ob[2][14];
      auto pack = [&](int T) {
        const float (&O)[2][16] = Op[T];
#pragma unroll
        for (int n = 0; n < 7; n++)
#pragma unroll
          for (int h = 0; h < 2; h++) {
            if (n < 3) Ob[T][n * 2 + h] = pack2(O[0][n * 4 + 2 * h], O[0][n * 4 + 2 * h + 1]);
            else if (n == 3) Ob[T][n * 2 + h] = pack2(t < 2 ? O[0][12 + 2 * h] : O[1][2 * h], t < 2 ? O[0][13 + 2 * h] : O[1][2 * h + 1]);
            else Ob[T][n * 2 + h] = pack2(O[1][(n - 3) * 4 + 2 * h], O[1][(n - 3) * 4 + 2 * h + 1]);
          }
      };
      smem_fence();
      named_sync(6, 256);
      OBS(tid == 224, 26);
      q_rest();
      named_sync(7, 256);
      wg_fence();
      scores(1);
      wg_commit();
      named_arrive_if(g1, 0, 256);
      wg_wait<2>();
      if (tid == 128) mbar_arrive(bars + B_EMPTY + 7 * 8);
      wg_wait<0>();
      q_pack();
      OBS(tid == 160, 10);
      softmax(1);
      OBS(tid == 160, 30);
      mbar_wait(bars + B_HALO, 0);
      OBS(tid == 160, 7);
      mbar_wait(bars + B_GATE, 0);
      wg_fence();
      scores(0);
      values(1);
      wg_wait<0>();
      OBS(tid == 160, 33);
      unsigned char* og = scr + O_OFF + rb * 2 * 57344 + hp * 7168 + w4 * 256 + lane * 4;
      auto put = [&](int T) {
#pragma unroll
        for (int n = 0; n < 14; n++) { stg32(og + T * 57344 + (n >> 1) * 1024 + (n & 1) * 128, Ob[T][n]); if (OSLEEP && n % OGRP == OGRP - 1) __nanosleep(OSLEEP); }
      };
      if (OMODE == 1) { pack(1); put(1); }
      softmax(0);
      if (OMODE == 2) { pack(1); put(1); }
      mbar_wait(bars + B_GATE + 8, 0);
      wg_fence();
      values(0);
      if (OMODE == 3) { pack(1); put(1); }
      wg_wait<0>();
      OBS(tid == 160, 35);
      named_sync(11, 128);
      if (tid == 160) mbar_arrive(bars + B_ATT);
      if (OMODE == 0) pack(1);
      pack(0);
      if (J3 > J2) mbar_wait(bars + B_GATE + 16, 0);
      if (OMODE == 0) put(1);
      put(0);
      named_sync(11, 128);
      if (warp == 4) publish(scr, C_O + rb);
      OBS(tid == 160, 8);
      setup_u(); setup_out();
      float as[56];
      if (g1) {
        take_h(0);
        if (!RESP && XE) get_x();
#pragma unroll
        for (int j = 4; j < OPJ; j++) { gelu(j); if (j % GCH == GCH - 1 && j < OPJ - 1) fence_code(40 + j); }
        if (OPJ == 16) named_arrive(2, 256);
      } else if (!RESP && XE) get_x();
      fresh(as);
      gemm_stage<0>(as, base, 0, 0);
      OBS(tid == 128, 22);
      if (OPJ < 16 && g1) {
#pragma unroll
        for (int j = OPJ; j < 16; j++) gelu(j);
        named_arrive(2, 256);
      }
      gemm_loop<0>(as, base, 1, 7, rel, 104);
      fresh(acc);
      if (SEARLY) { wg_wait<0>(); mbar_arrive_if(rel, bars + B_EMPTY + 6 * 8); give(as, 3); if (!RESP && !XE) get_x(); }
      gemm_stage<1>(acc, base, 7, 0);
      OBS(tid == 128, 24);
      if (!SEARLY) { wg_wait<1>(); mbar_arrive_if(rel, bars + B_EMPTY + 6 * 8); give(as, 3); }
#pragma unroll
      for (int j = 0; j < 16; j++) Sv[j] = pack2(as[ai(j)], as[ai(j) + 1]);
      gemm_loop<1, NX>(acc, base, 8, 35, rel, 65);
      if (RESP) get_x();
      named_sync(10, 256);
      wg_wait<0>();
      OBS(tid == 128, 25);
      give(acc, 5);
      fence_code(31);
      keep_h(2);
      gate(0); leave(0);
    }
    {
#pragma unroll
      for (int i = 1; i < 4; i++) { gate(i); leave(i); }
      OBS(tid == 128, 27);
    }
  }
}

typedef CUresult (*EncFn)(CUtensorMap*, CUtensorMapDataType, cuuint32_t, void*, const cuuint64_t*, const cuuint64_t*, const cuuint32_t*,
                          const cuuint32_t*, CUtensorMapInterleave, CUtensorMapSwizzle, CUtensorMapL2promotion, CUtensorMapFloatOOBfill);
void enc(EncFn f, CUtensorMap* m, const void* ptr, cuuint64_t d0, cuuint64_t d1, cuuint64_t d2, cuuint64_t s1, cuuint64_t s2, cuuint32_t b1, cuuint32_t b2, cuuint32_t b0 = 64) {
  const cuuint64_t gd[3] = {d0, d1, d2}, gs[2] = {s1 * 2, s2 * 2};
  const cuuint32_t bx[3] = {b0, b1, b2}, es[3] = {1, 1, 1};
  f(m, CU_TENSOR_MAP_DATA_TYPE_BFLOAT16, 3, (void*)ptr, gd, gs, bx, es, CU_TENSOR_MAP_INTERLEAVE_NONE, b0 == 64 ? CU_TENSOR_MAP_SWIZZLE_128B : CU_TENSOR_MAP_SWIZZLE_NONE,
    CU_TENSOR_MAP_L2_PROMOTION_L2_128B, CU_TENSOR_MAP_FLOAT_OOB_FILL_NONE);
}
}

extern "C" void kernel_launch(void* const* d_in, const int* in_sizes, int n_in, void* d_out, int out_size) {
  (void)in_sizes; (void)n_in; (void)out_size;
  void* fp = nullptr;
  cudaDriverEntryPointQueryResult qr;
  cudaGetDriverEntryPoint("cuTensorMapEncodeTiled", &fp, cudaEnableDefault, &qr);
  EncFn f = (EncFn)fp;
  CUtensorMap m_x, m_wkv, m_wq, m_w1, m_w2, m_res;
  void* scr = nullptr;
  cudaGetSymbolAddress(&scr, g_scr);
  enc(f, &m_x, d_in[0], D_, S_, 1, D_, D_, 128 >> XSPLIT, 1);
  enc(f, &m_wkv, d_in[1], D_, D_, 3, 3 * D_, D_, 64, 2);
  enc(f, &m_wq, d_in[1], D_, D_, 3, 3 * D_, D_, 224, 1);
  enc(f, &m_w1, d_in[4], F_, S_, 1, F_, F_, 64, 1);
  enc(f, &m_w2, d_in[6], S_, F_, 1, S_, S_, 64, 1);
  enc(f, &m_res, d_in[0], D_, S_, 1, D_, D_, 64, 1, 112);
  Params p;
  p.wqkv = (const unsigned char*)d_in[1]; p.wo = (const unsigned char*)d_in[2];
  p.w1 = (const unsigned char*)d_in[4]; p.b1 = (const unsigned char*)d_in[5];
  p.w2 = (const unsigned char*)d_in[6]; p.b2 = (const unsigned char*)d_in[7];
  p.out = (unsigned char*)d_out; p.scr = (unsigned char*)scr;
  cudaFuncSetAttribute(fused_kernel, cudaFuncAttributeMaxDynamicSharedMemorySize, SMEM_BYTES);
  fused_kernel<<<128, NTHREADS, SMEM_BYTES, cudaStreamPerThread>>>(m_x, m_wkv, m_wq, m_w1, m_w2, m_res, p);
}
```

```cpp
#include <cuda_runtime.h>
#include <cuda.h>
#include <cuda_bf16.h>
#include <stdint.h>

template<int TA, int TB> __device__ __forceinline__ void wgmma_n112(float (&d)[56], uint64_t da, uint64_t db, int sc) {
  asm volatile("{\n.reg .pred p;\nsetp.ne.b32 p, %58, 0;\n"
    "wgmma.mma_async.sync.aligned.m64n112k16.f32.bf16.bf16 {%0, %1, %2, %3, %4, %5, %6, %7, %8, %9, %10, %11, %12, %13, %14, %15, %16, %17, %18, %19, %20, %21, %22, %23, %24, %25, %26, %27, %28, %29, %30, %31, %32, %33, %34, %35, %36, %37, %38, %39, %40, %41, %42, %43, %44, %45, %46, %47, %48, %49, %50, %51, %52, %53, %54, %55}, %56, %57, p, 1, 1, %59, %60;\n}\n"
    : "+f"(d[0]), "+f"(d[1]), "+f"(d[2]), "+f"(d[3]), "+f"(d[4]), "+f"(d[5]), "+f"(d[6]), "+f"(d[7]), "+f"(d[8]), "+f"(d[9]), "+f"(d[10]), "+f"(d[11]), "+f"(d[12]), "+f"(d[13]), "+f"(d[14]), "+f"(d[15]), "+f"(d[16]), "+f"(d[17]), "+f"(d[18]), "+f"(d[19]), "+f"(d[20]), "+f"(d[21]), "+f"(d[22]), "+f"(d[23]), "+f"(d[24]), "+f"(d[25]), "+f"(d[26]), "+f"(d[27]), "+f"(d[28]), "+f"(d[29]), "+f"(d[30]), "+f"(d[31]), "+f"(d[32]), "+f"(d[33]), "+f"(d[34]), "+f"(d[35]), "+f"(d[36]), "+f"(d[37]), "+f"(d[38]), "+f"(d[39]), "+f"(d[40]), "+f"(d[41]), "+f"(d[42]), "+f"(d[43]), "+f"(d[44]), "+f"(d[45]), "+f"(d[46]), "+f"(d[47]), "+f"(d[48]), "+f"(d[49]), "+f"(d[50]), "+f"(d[51]), "+f"(d[52]), "+f"(d[53]), "+f"(d[54]), "+f"(d[55])
    : "l"(da), "l"(db), "r"(sc), "n"(TA), "n"(TB));
}

template<int TA, int TB> __device__ __forceinline__ void wgmma_n80(float (&d)[40], uint64_t da, uint64_t db, int sc) {
  asm volatile("{\n.reg .pred p;\nsetp.ne.b32 p, %42, 0;\n"
    "wgmma.mma_async.sync.aligned.m64n80k16.f32.bf16.bf16 {%0, %1, %2, %3, %4, %5, %6, %7, %8, %9, %10, %11, %12, %13, %14, %15, %16, %17, %18, %19, %20, %21, %22, %23, %24, %25, %26, %27, %28, %29, %30, %31, %32, %33, %34, %35, %36, %37, %38, %39}, %40, %41, p, 1, 1, %43, %44;\n}\n"
    : "+f"(d[0]), "+f"(d[1]), "+f"(d[2]), "+f"(d[3]), "+f"(d[4]), "+f"(d[5]), "+f"(d[6]), "+f"(d[7]), "+f"(d[8]), "+f"(d[9]), "+f"(d[10]), "+f"(d[11]), "+f"(d[12]), "+f"(d[13]), "+f"(d[14]), "+f"(d[15]), "+f"(d[16]), "+f"(d[17]), "+f"(d[18]), "+f"(d[19]), "+f"(d[20]), "+f"(d[21]), "+f"(d[22]), "+f"(d[23]), "+f"(d[24]), "+f"(d[25]), "+f"(d[26]), "+f"(d[27]), "+f"(d[28]), "+f"(d[29]), "+f"(d[30]), "+f"(d[31]), "+f"(d[32]), "+f"(d[33]), "+f"(d[34]), "+f"(d[35]), "+f"(d[36]), "+f"(d[37]), "+f"(d[38]), "+f"(d[39])
    : "l"(da), "l"(db), "r"(sc), "n"(TA), "n"(TB));
}

template<int TB> __device__ __forceinline__ void wgmma_rs_n120(float (&d)[60], const uint32_t (&a)[4], uint64_t db, int sc) {
  asm volatile("{\n.reg .pred p;\nsetp.ne.b32 p, %65, 0;\n"
    "wgmma.mma_async.sync.aligned.m64n120k16.f32.bf16.bf16 {%0, %1, %2, %3, %4, %5, %6, %7, %8, %9, %10, %11, %12, %13, %14, %15, %16, %17, %18, %19, %20, %21, %22, %23, %24, %25, %26, %27, %28, %29, %30, %31, %32, %33, %34, %35, %36, %37, %38, %39, %40, %41, %42, %43, %44, %45, %46, %47, %48, %49, %50, %51, %52, %53, %54, %55, %56, %57, %58, %59}, {%60, %61, %62, %63}, %64, p, 1, 1, %66;\n}\n"
    : "+f"(d[0]), "+f"(d[1]), "+f"(d[2]), "+f"(d[3]), "+f"(d[4]), "+f"(d[5]), "+f"(d[6]), "+f"(d[7]), "+f"(d[8]), "+f"(d[9]), "+f"(d[10]), "+f"(d[11]), "+f"(d[12]), "+f"(d[13]), "+f"(d[14]), "+f"(d[15]), "+f"(d[16]), "+f"(d[17]), "+f"(d[18]), "+f"(d[19]), "+f"(d[20]), "+f"(d[21]), "+f"(d[22]), "+f"(d[23]), "+f"(d[24]), "+f"(d[25]), "+f"(d[26]), "+f"(d[27]), "+f"(d[28]), "+f"(d[29]), "+f"(d[30]), "+f"(d[31]), "+f"(d[32]), "+f"(d[33]), "+f"(d[34]), "+f"(d[35]), "+f"(d[36]), "+f"(d[37]), "+f"(d[38]), "+f"(d[39]), "+f"(d[40]), "+f"(d[41]), "+f"(d[42]), "+f"(d[43]), "+f"(d[44]), "+f"(d[45]), "+f"(d[46]), "+f"(d[47]), "+f"(d[48]), "+f"(d[49]), "+f"(d[50]), "+f"(d[51]), "+f"(d[52]), "+f"(d[53]), "+f"(d[54]), "+f"(d[55]), "+f"(d[56]), "+f"(d[57]), "+f"(d[58]), "+f"(d[59])
    : "r"(a[0]), "r"(a[1]), "r"(a[2]), "r"(a[3]), "l"(db), "r"(sc), "n"(TB));
}

template<int TB> __device__ __forceinline__ void wgmma_rs_n56(float (&d)[28], const uint32_t (&a)[4], uint64_t db, int sc) {
  asm volatile("{\n.reg .pred p;\nsetp.ne.b32 p, %33, 0;\n"
    "wgmma.mma_async.sync.aligned.m64n56k16.f32.bf16.bf16 {%0, %1, %2, %3, %4, %5, %6, %7, %8, %9, %10, %11, %12, %13, %14, %15, %16, %17, %18, %19, %20, %21, %22, %23, %24, %25, %26, %27}, {%28, %29, %30, %31}, %32, p, 1, 1, %34;\n}\n"
    : "+f"(d[0]), "+f"(d[1]), "+f"(d[2]), "+f"(d[3]), "+f"(d[4]), "+f"(d[5]), "+f"(d[6]), "+f"(d[7]), "+f"(d[8]), "+f"(d[9]), "+f"(d[10]), "+f"(d[11]), "+f"(d[12]), "+f"(d[13]), "+f"(d[14]), "+f"(d[15]), "+f"(d[16]), "+f"(d[17]), "+f"(d[18]), "+f"(d[19]), "+f"(d[20]), "+f"(d[21]), "+f"(d[22]), "+f"(d[23]), "+f"(d[24]), "+f"(d[25]), "+f"(d[26]), "+f"(d[27])
    : "r"(a[0]), "r"(a[1]), "r"(a[2]), "r"(a[3]), "l"(db), "r"(sc), "n"(TB));
}

template<int TB> __device__ __forceinline__ void wgmma_rs_n32(float (&d)[16], const uint32_t (&a)[4], uint64_t db, int sc) {
  asm volatile("{\n.reg .pred p;\nsetp.ne.b32 p, %21, 0;\n"
    "wgmma.mma_async.sync.aligned.m64n32k16.f32.bf16.bf16 {%0, %1, %2, %3, %4, %5, %6, %7, %8, %9, %10, %11, %12, %13, %14, %15}, {%16, %17, %18, %19}, %20, p, 1, 1, %22;\n}\n"
    : "+f"(d[0]), "+f"(d[1]), "+f"(d[2]), "+f"(d[3]), "+f"(d[4]), "+f"(d[5]), "+f"(d[6]), "+f"(d[7]), "+f"(d[8]), "+f"(d[9]), "+f"(d[10]), "+f"(d[11]), "+f"(d[12]), "+f"(d[13]), "+f"(d[14]), "+f"(d[15])
    : "r"(a[0]), "r"(a[1]), "r"(a[2]), "r"(a[3]), "l"(db), "r"(sc), "n"(TB));
}

template<int TB> __device__ __forceinline__ void wgmma_rs_n80(float (&d)[40], const uint32_t (&a)[4], uint64_t db, int sc) {
  asm volatile("{\n.reg .pred p;\nsetp.ne.b32 p, %45, 0;\n"
    "wgmma.mma_async.sync.aligned.m64n80k16.f32.bf16.bf16 {%0, %1, %2, %3, %4, %5, %6, %7, %8, %9, %10, %11, %12, %13, %14, %15, %16, %17, %18, %19, %20, %21, %22, %23, %24, %25, %26, %27, %28, %29, %30, %31, %32, %33, %34, %35, %36, %37, %38, %39}, {%40, %41, %42, %43}, %44, p, 1, 1, %46;\n}\n"
    : "+f"(d[0]), "+f"(d[1]), "+f"(d[2]), "+f"(d[3]), "+f"(d[4]), "+f"(d[5]), "+f"(d[6]), "+f"(d[7]), "+f"(d[8]), "+f"(d[9]), "+f"(d[10]), "+f"(d[11]), "+f"(d[12]), "+f"(d[13]), "+f"(d[14]), "+f"(d[15]), "+f"(d[16]), "+f"(d[17]), "+f"(d[18]), "+f"(d[19]), "+f"(d[20]), "+f"(d[21]), "+f"(d[22]), "+f"(d[23]), "+f"(d[24]), "+f"(d[25]), "+f"(d[26]), "+f"(d[27]), "+f"(d[28]), "+f"(d[29]), "+f"(d[30]), "+f"(d[31]), "+f"(d[32]), "+f"(d[33]), "+f"(d[34]), "+f"(d[35]), "+f"(d[36]), "+f"(d[37]), "+f"(d[38]), "+f"(d[39])
    : "r"(a[0]), "r"(a[1]), "r"(a[2]), "r"(a[3]), "l"(db), "r"(sc), "n"(TB));
}

namespace {
constexpr int S_ = 2048, D_ = 448, F_ = 1792;
constexpr int NSLOT = 8, SLOT = 22528;
constexpr int OFF_X = 7 * 16384;
constexpr int OFF_WQ = 8 * 16384;
constexpr int OFF_Q = NSLOT * SLOT;
constexpr int OFF_K = OFF_Q + 16384;
constexpr int OFF_XW = OFF_K + 6144;
constexpr int OFF_BAR = 14 * 16384;
constexpr int OFF_LN = OFF_BAR + 512;
constexpr int OFF_OBS = OFF_BAR + 640;
constexpr int SMEM_BYTES = OFF_OBS + 1024;
#define PACE0 0
#define PACE1 540
#define PACE2 650
#define WARM 3
#define NW0 2
#define HEAT 1
#define T0 0
#define TP 250
#define J3 0
#define J1 9
#define J2 14
#define EARLY 4
#define PPE 4
#define PQE 2
#define LANDOBS 0
#define TRUNC 0
#define KOBS 0
#define PRE 1
#define QA 2
#define HEARLY 0
#define OSLEEP 20
#define PROBE 1
#define WOP 0
#define OGRP 2
#define OMODE 3
#define GCH 4
#define GLAG 2
#define GSLOW 0
#define RH 32
#define NOST 0
#define GOBS 0
#define HP 0
#define OPP 0
#define STAG 0
#define RESP 0
#define XE 1
#define NX 0
#define XS 15
#define XT 9
#define NPRE 1
#define U0 0
#define ALL4 0
#define UREP 1
#define TS 0
#define PPM 1
#define WPF 0
#define XSPLIT 1
#define XK 1
#define TAG 1
#define HWAIT 300
#define RB 31
#define UO 1
#define MU 0
#define P2 224
#define UP 170
#define POLL "relaxed"
#define OPJ 16
#define SEARLY 1
#define EXACT 0
#define SOBS 0
#define FREQ 0
#define OBS(c, i) do {} while (0)
#define OBSG(c, i, j) do {} while (0)
constexpr int NTHREADS = 384;
constexpr float SCALE = 0.18898223650461361f, LOG2E = 1.4426950408889634f;
constexpr int BT = 14336;

constexpr int HU_T = 67;
constexpr int O_OFF = 4 * HU_T * BT;
constexpr int HALO_OFF = O_OFF + 32 * 7 * 8192;
constexpr int CNT_OFF = HALO_OFF + 128 * 3584;
constexpr int SCR_BYTES = CNT_OFF + 193 * 128;
constexpr int C_WO = 0, C_TK = 1, C_U = 160, C_O = 8, C_H = 24, C_HALO = 32, C_EPOCH = 192;
__device__ __align__(1024) unsigned char g_scr[SCR_BYTES];

__device__ __forceinline__ uint32_t smem_u32(const void* p) { return (uint32_t)__cvta_generic_to_shared(p); }
__device__ __forceinline__ void mbar_init(uint32_t bar, uint32_t cnt) { asm volatile("mbarrier.init.shared::cta.b64 [%0], %1;" :: "r"(bar), "r"(cnt)); }
__device__ __forceinline__ void mbar_expect_tx(uint32_t bar, uint32_t bytes) { asm volatile("mbarrier.arrive.expect_tx.shared::cta.b64 _, [%0], %1;" :: "r"(bar), "r"(bytes) : "memory"); }
__device__ __forceinline__ void mbar_arrive_if(uint32_t c, uint32_t bar) { asm volatile("{\n.reg .pred q;\nsetp.ne.u32 q, %1, 0;\n@q mbarrier.arrive.shared::cta.b64 _, [%0];\n}" :: "r"(bar), "r"(c) : "memory"); }
__device__ __forceinline__ void mbar_arrive(uint32_t bar) { asm volatile("mbarrier.arrive.shared::cta.b64 _, [%0];" :: "r"(bar) : "memory"); }
__device__ __forceinline__ void mbar_wait(uint32_t bar, uint32_t parity) {
  asm volatile("{\n.reg .pred p;\n.reg .u32 n;\nmov.u32 n, 0;\nLAB_WAIT:\n"
               "mbarrier.try_wait.parity.shared::cta.b64 p, [%0], %1;\n@p bra DONE;\n"
               "add.u32 n, n, 1;\nsetp.lt.u32 p, n, 400000;\n@p bra LAB_WAIT;\ntrap;\nDONE:\n}" :: "r"(bar), "r"(parity) : "memory");
}
__device__ __forceinline__ uint32_t mbar_try(uint32_t bar, uint32_t parity) {
  uint32_t ok;
  asm volatile("{\n.reg .pred p;\nmbarrier.test_wait.parity.shared::cta.b64 p, [%1], %2;\nselp.u32 %0, 1, 0, p;\n}" : "=r"(ok) : "r"(bar), "r"(parity) : "memory");
  return ok;
}
__device__ __forceinline__ void tma3d(uint32_t dst, const CUtensorMap* m, int c0, int c1, int c2, uint32_t bar) {
  asm volatile("cp.async.bulk.tensor.3d.shared::cluster.global.mbarrier::complete_tx::bytes [%0], [%1, {%3, %4, %5}], [%2];"
               :: "r"(dst), "l"(m), "r"(bar), "r"(c0), "r"(c1), "r"(c2) : "memory");
}
__device__ __forceinline__ void bulk_g2s(uint32_t dst, const void* src, uint32_t bytes, uint32_t bar) {
  asm volatile("cp.async.bulk.shared::cluster.global.mbarrier::complete_tx::bytes [%0], [%1], %2, [%3];" :: "r"(dst), "l"(src), "r"(bytes), "r"(bar) : "memory");
}
__device__ __forceinline__ void wg_fence() { asm volatile("wgmma.fence.sync.aligned;" ::: "memory"); }
__device__ __forceinline__ void wg_commit() { asm volatile("wgmma.commit_group.sync.aligned;" ::: "memory"); }
template <int N> __device__ __forceinline__ void wg_wait() { asm volatile("wgmma.wait_group.sync.aligned %0;" :: "n"(N) : "memory"); }
__device__ __forceinline__ void smem_fence() { asm volatile("fence.proxy.async.shared::cta;" ::: "memory"); }
__device__ __forceinline__ void stg128(void* p, uint32_t a, uint32_t b, uint32_t c, uint32_t d) { asm volatile("st.global.v4.u32 [%0], {%1,%2,%3,%4};" :: "l"(p), "r"(a), "r"(b), "r"(c), "r"(d) : "memory"); }
__device__ __forceinline__ void stg32(void* p, uint32_t v) { asm volatile("st.global.u32 [%0], %1;" :: "l"(p), "r"(v) : "memory"); }
__device__ __forceinline__ uint4 ldg128(const void* p) { uint4 v; asm volatile("ld.global.nc.L1::no_allocate.v4.u32 {%0,%1,%2,%3}, [%4];" : "=r"(v.x), "=r"(v.y), "=r"(v.z), "=r"(v.w) : "l"(p)); return v; }
__device__ __forceinline__ void publish(unsigned char* scr, int i) {
  asm volatile("{\n.reg .pred q;\nelect.sync _|q, 0xffffffff;\n@q red.relaxed.gpu.global.inc.u32 [%0], 0xffffffff;\n}" :: "l"(scr + CNT_OFF + i * 128) : "memory");
}
__device__ __forceinline__ uint32_t probe(const unsigned char* p) { uint32_t v; asm volatile("ld.relaxed.gpu.global.u32 %0, [%1];" : "=r"(v) : "l"(p) : "memory"); return v; }
__device__ __forceinline__ void settle(uint32_t v) {
  asm volatile("{\n.reg .pred q;\nsetp.eq.u32 q, %0, 0x7fc1dead;\n@q st.volatile.shared.u32 [%1], %0;\n}" :: "r"(v), "r"(1024 + OFF_BAR + 376) : "memory");
  __syncwarp();
}
__device__ __forceinline__ void spin_ge(unsigned char* scr, int i, unsigned target) {
  asm volatile("{\n.reg .pred p;\n.reg .u32 n, v;\nmov.u32 n, 0;\nLAB_SPIN:\n"
               "ld." POLL ".gpu.global.u32 v, [%0];\nsetp.ge.u32 p, v, %1;\nvote.sync.all.pred p, p, 0xffffffff;\n@p bra DONE;\n"
               "add.u32 n, n, 1;\nsetp.lt.u32 p, n, 4000000;\n@p bra LAB_SPIN;\ntrap;\nDONE:\n}" :: "l"(scr + CNT_OFF + i * 128), "r"(target) : "memory");
}
__device__ __forceinline__ int lane_id() { int l; asm volatile("mov.u32 %0, %%laneid;" : "=r"(l)); return l; }
__device__ __forceinline__ uint32_t pin(uint32_t v) { return __shfl_xor_sync(0xffffffffu, v, blockIdx.y); }
__device__ __forceinline__ unsigned char* pin(unsigned char* p) { return (unsigned char*)(((uint64_t)pin((uint32_t)((uint64_t)p >> 32)) << 32) | pin((uint32_t)(uint64_t)p)); }
__device__ __forceinline__ bool elect() {
  uint32_t r; asm volatile("{\n.reg .pred p;\nelect.sync _|p, 0xffffffff;\nselp.u32 %0, 1, 0, p;\n}" : "=r"(r)); return r != 0;
}
__device__ __forceinline__ uint4 lds128(uint32_t a) { uint4 v; asm volatile("ld.shared.v4.u32 {%0,%1,%2,%3}, [%4];" : "=r"(v.x), "=r"(v.y), "=r"(v.z), "=r"(v.w) : "r"(a) : "memory"); return v; }
__device__ __forceinline__ uint2 lds64(uint32_t a) { uint2 v; asm volatile("ld.shared.v2.u32 {%0,%1}, [%2];" : "=r"(v.x), "=r"(v.y) : "r"(a) : "memory"); return v; }
__device__ __forceinline__ void sts128(uint32_t p, uint32_t a, uint32_t b, uint32_t c, uint32_t d) { asm volatile("st.shared.v4.u32 [%0], {%1,%2,%3,%4};" :: "r"(p), "r"(a), "r"(b), "r"(c), "r"(d) : "memory"); }
__device__ __forceinline__ void sts32(uint32_t a, float v) { asm volatile("st.shared.f32 [%0], %1;" :: "r"(a), "f"(v) : "memory"); }
__device__ __forceinline__ void named_sync(int id, int n) { asm volatile("bar.sync %0, %1;" :: "r"(id), "r"(n) : "memory"); }
__device__ __forceinline__ void named_arrive(int id, int n) { asm volatile("bar.arrive %0, %1;" :: "r"(id), "r"(n) : "memory"); }
__device__ __forceinline__ void named_arrive_if(uint32_t c, int id, int n) { asm volatile("{\n.reg .pred q;\nsetp.ne.u32 q, %2, 0;\n@q bar.arrive %0, %1;\n}" :: "r"(id), "r"(n), "r"(c) : "memory"); }
__device__ __forceinline__ uint64_t mkdesc(uint32_t hi, uint32_t lo) { return ((uint64_t)hi << 32) | lo; }
constexpr uint32_t HI_SW128 = 0x40000040u;
__device__ __forceinline__ uint32_t pack2(float lo, float hi) { uint32_t r; asm("cvt.rn.bf16x2.f32 %0, %1, %2;" : "=r"(r) : "f"(hi), "f"(lo)); return r; }
__device__ __forceinline__ float bf_lo(uint32_t v) { return __uint_as_float(v << 16); }
__device__ __forceinline__ float bf_hi(uint32_t v) { return __uint_as_float(v & 0xffff0000u); }
__device__ __forceinline__ float rbf(float x) { return bf_lo(pack2(x, 0.f)); }
__device__ __forceinline__ uint32_t hsub2(uint32_t a, uint32_t b) { uint32_t r; asm("sub.rn.bf16x2 %0, %1, %2;" : "=r"(r) : "r"(a), "r"(b)); return r; }
__device__ __forceinline__ uint32_t hadd2(uint32_t a, uint32_t b) { uint32_t r; asm("add.rn.bf16x2 %0, %1, %2;" : "=r"(r) : "r"(a), "r"(b)); return r; }
__device__ __forceinline__ uint32_t hmul2(uint32_t a, uint32_t b) { uint32_t r; asm("mul.rn.bf16x2 %0, %1, %2;" : "=r"(r) : "r"(a), "r"(b)); return r; }
__device__ __forceinline__ uint32_t hfma2(uint32_t a, uint32_t b, uint32_t c) { uint32_t r; asm("fma.rn.bf16x2 %0, %1, %2, %3;" : "=r"(r) : "r"(a), "r"(b), "r"(c)); return r; }
__device__ __forceinline__ float tanh_fast(float x) { float r; asm("tanh.approx.f32 %0, %1;" : "=f"(r) : "f"(x)); return r; }
__device__ __forceinline__ float rcp_fast(float x) { float r; asm("rcp.approx.ftz.f32 %0, %1;" : "=f"(r) : "f"(x)); return r; }
__device__ __forceinline__ float ex2_fast(float x) { float r; asm("ex2.approx.ftz.f32 %0, %1;" : "=f"(r) : "f"(x)); return r; }
__device__ __forceinline__ void mma16816(float (&c)[4], uint32_t a0, uint32_t a1, uint32_t a2, uint32_t a3, uint32_t b0, uint32_t b1) {
  asm volatile("mma.sync.aligned.m16n8k16.row.col.f32.bf16.bf16.f32 {%0,%1,%2,%3}, {%4,%5,%6,%7}, {%8,%9}, {%0,%1,%2,%3};"
               : "+f"(c[0]), "+f"(c[1]), "+f"(c[2]), "+f"(c[3]) : "r"(a0), "r"(a1), "r"(a2), "r"(a3), "r"(b0), "r"(b1));
}
__device__ __forceinline__ void ldsm4(uint32_t (&r)[4], uint32_t addr) {
  asm volatile("ldmatrix.sync.aligned.m8n8.x4.shared.b16 {%0,%1,%2,%3}, [%4];" : "=r"(r[0]), "=r"(r[1]), "=r"(r[2]), "=r"(r[3]) : "r"(addr) : "memory");
}
__device__ __forceinline__ void stsm4(uint32_t addr, uint32_t a, uint32_t b, uint32_t c, uint32_t d) {
  asm volatile("stmatrix.sync.aligned.m8n8.x4.shared.b16 [%0], {%1,%2,%3,%4};" :: "r"(addr), "r"(a), "r"(b), "r"(c), "r"(d) : "memory");
}

__device__ __forceinline__ float ln_rstd(float var, float eps = 1e-5f) {
  float sd;
  asm("sqrt.approx.ftz.f32 %0, %1;" : "=f"(sd) : "f"(rbf(rbf(var) + eps)));
  return rcp_fast(rbf(sd));
}
__device__ __forceinline__ float ln_var(float mean, float sq) { return fmaxf(fmaf(-mean, mean, sq * (1.0f / D_)), 0.f); }
struct LnC { uint32_t m, rh, rl; };
__device__ __forceinline__ LnC ln_consts(float sum, float sq, float eps) {
  const float mean = sum * (1.0f / D_), r = ln_rstd(ln_var(mean, sq), eps), rh = rbf(r);
  LnC c; c.m = pack2(mean, mean); c.rh = pack2(rh, rh); c.rl = pack2(r - rh, r - rh);
  return c;
}
__device__ __forceinline__ uint32_t ln_apply(uint32_t x, const LnC& c) {
  uint32_t d = hsub2(x, c.m);
  return hfma2(d, c.rh, hmul2(d, c.rl));
}

__device__ __forceinline__ void fence_code(int id) {
  asm volatile("{\n.reg .pred q;\nLAB_F:\nsetp.eq.u32 q, %0, %1;\n@q st.volatile.shared.u32 [%2], %2;\n@q bra LAB_F;\n}" :: "r"(blockIdx.x), "r"(0x70000000 + id), "r"(0) : "memory");
}
template <int N> __device__ __forceinline__ void fresh(float (&a)[N]) {
#pragma unroll
  for (int i = 0; i < N; i++) asm volatile("" : "=f"(a[i]));
}
constexpr int B_EMPTY = 64, B_X = 384, B_KV = 192, B_WQ = 248, B_HALO = 256, B_RES = 264, B_ATT = 272, B_GATE = 280, B_WO = 304, B_O = 312, B_XW = 320, B_WQ2 = 328, B_T0 = 336;

template <int TA>
__device__ __forceinline__ void gemm_issue(float (&acc)[56], uint32_t la, uint32_t lo, int sc) {
  wg_fence();
#pragma unroll
  for (int k = 0; k < 4; k++)
    wgmma_n112<TA, 1>(acc, mkdesc(TA ? HI_SW128 : 8, la + (TA ? 512u << 16 : 64u << 16) + k * 128), mkdesc(8, lo + (112u << 16) + 512 + k * 224), sc | k);
  wg_commit();
}
template <int TA>
__device__ __forceinline__ void gemm_stage(float (&acc)[56], uint32_t base, int it, int sc) {
  mbar_wait(base + OFF_BAR + (it & 7) * 8, (it >> 3) & 1);
  const uint32_t lo = (base >> 4) + (it & 7) * (SLOT >> 4);
  gemm_issue<TA>(acc, lo, lo, sc);
}
template <int TA, int EXTRA = 0>
__device__ __forceinline__ void gemm_loop(float (&acc)[56], uint32_t base, int it, int end, bool rel, int oi, uint32_t ok = 0, int gate_it = -1, uint32_t gate = 0) {
#pragma unroll 1
  for (; it < end;) {
    if (__builtin_expect(!ok, 0)) mbar_wait(base + OFF_BAR + (it & 7) * 8, (it >> 3) & 1);
    const uint32_t lo = (base >> 4) + (it & 7) * (SLOT >> 4);
    gemm_issue<TA>(acc, (unsigned)(it - XS) < EXTRA ? ((base + OFF_XW) >> 4) + (it - XS) * 512 : lo, lo, 1);
    OBS(SOBS && rel, oi + it);
    it++;
    ok = mbar_try(base + OFF_BAR + (it & 7) * 8, (it >> 3) & 1);
    wg_wait<1>();
    if (rel || it == gate_it) mbar_arrive(rel ? base + OFF_BAR + B_EMPTY + ((it - 2) & 7) * 8 : gate);
  }
}
template <int PER>
__device__ __forceinline__ void produce_box(uint32_t base, int it, int end, const CUtensorMap* mp, int c0, int c1, uint32_t tn = 0) {
#pragma unroll 1
  for (; it < end; it++) {
    const uint32_t fb = base + OFF_BAR + (it & 7) * 8;
    mbar_wait(fb + B_EMPTY, (it >> 3) & 1);
    if (PER) { while ((int)(clock() - tn) < 0); tn += PER; }
    if (elect()) { mbar_expect_tx(fb, 8192); tma3d(base + (it & 7) * SLOT, mp, c0, c1, 0, fb); }
    c1 += 64;
  }
}
template <int PER>
__device__ __forceinline__ void produce_lin(uint32_t base, int it, int end, const unsigned char* src, uint32_t bytes, uint32_t tn = 0) {
#pragma unroll 1
  for (; it < end; it++) {
    const uint32_t fb = base + OFF_BAR + (it & 7) * 8;
    mbar_wait(fb + B_EMPTY, (it >> 3) & 1);
    if (PER) { while ((int)(clock() - tn) < 0); tn += PER; }
    if (elect()) { mbar_expect_tx(fb, bytes); bulk_g2s(base + (it & 7) * SLOT + (bytes & 2048) * 4, src, bytes, fb); }
    src += bytes;
  }
}

__device__ __forceinline__ void retile_wo(const unsigned char* wo, unsigned char* scr, int u, int lane) {
  const int r8 = lane & 7, mi = lane >> 3;
  const unsigned char* src = wo + ((u >> 1) * 8 + r8) * 896 + ((u & 1) * 28 + mi) * 16;
  unsigned char* dst = scr + ((u & 1) * 2 * HU_T + 60 + (u >> 4)) * BT + ((u >> 1) & 7) * 1792 + mi * 128 + r8 * 16;
  uint4 v[7];
#pragma unroll
  for (int i = 0; i < 7; i++) v[i] = ldg128(src + i * 64);
#pragma unroll
  for (int i = 0; i < 7; i++) stg128(dst + i * 512 + ((i * 4 + mi) / 14) * (HU_T * BT - 1792), v[i].x, v[i].y, v[i].z, v[i].w);
  if (!(RB & 1)) publish(scr, C_WO);
}

struct Params {
  const unsigned char *wqkv, *wo, *w1, *b1, *w2, *b2;
  unsigned char *out, *scr;
};

__global__ void __launch_bounds__(NTHREADS, 1)
fused_kernel(const __grid_constant__ CUtensorMap m_x, const __grid_constant__ CUtensorMap m_wkv, const __grid_constant__ CUtensorMap m_wq,
             const __grid_constant__ CUtensorMap m_w1, const __grid_constant__ CUtensorMap m_w2, const __grid_constant__ CUtensorMap m_res, const Params p) {
  extern __shared__ __align__(1024) unsigned char smem_raw[];
  constexpr uint32_t base = 1024, bars = base + OFF_BAR;
  const int tid = threadIdx.x, lane = tid & 31, b = blockIdx.x;
  const int rb = (b >> 2) & 15, hp = ((b >> 6) << 2) | (b & 3);
  const int wcol = hp * 56 - (hp & 1) * 8;
  auto load_kv = [&](int s) { mbar_expect_tx(bars + B_KV + s * 8, 16384); tma3d(base + s * 16384, &m_wkv, wcol, s * 64, 1, bars + B_KV + s * 8); };
  if (tid < 32) {
    if (elect()) {
#pragma unroll
      for (int i = 0; i < 7; i++) mbar_init(bars + B_X + i * 8, 1);
      asm volatile("fence.mbarrier_init.release.cluster;" ::: "memory");
#pragma unroll
      for (int i = 0; i < 7; i++) { mbar_expect_tx(bars + B_X + i * 8, 16384 >> XSPLIT); tma3d(base + OFF_X + i * 16384 + XSPLIT * 8192, &m_x, i * 64, rb * 128 + XSPLIT * 64, 0, bars + B_X + i * 8); }
#pragma unroll
      for (int i = 0; i < 7; i++) { mbar_init(bars + B_KV + i * 8, 1); if (XSPLIT) mbar_init(bars + B_X + 64 + i * 8, 1); }
      asm volatile("fence.mbarrier_init.release.cluster;" ::: "memory");
      if (XSPLIT) {
#pragma unroll
        for (int i = 0; i < XK; i++) load_kv(i);
#pragma unroll
        for (int i = 0; i < 7; i++) { mbar_expect_tx(bars + B_X + 64 + i * 8, 8192); tma3d(base + OFF_X + i * 16384, &m_x, i * 64, rb * 128, 0, bars + B_X + 64 + i * 8); }
      }
#pragma unroll 1
      for (int i = XSPLIT * XK; i < NW0; i++) load_kv(i);
    }
  }
  const int warp = __shfl_sync(0xffffffffu, tid >> 5, 0);
  if (TS && tid == 64) sts32(bars + B_T0, __uint_as_float(clock() + TS));
  if (warp == 1) {
    if (elect()) {
#pragma unroll
      for (int i = 0; i < 16; i++) mbar_init(bars + i * 8, 2);
#pragma unroll
      for (int i = 0; i < 11; i++) mbar_init(bars + B_WQ + i * 8, 1);
      asm volatile("fence.mbarrier_init.release.cluster;" ::: "memory");
      if (smem_u32(smem_raw) != base) asm volatile("trap;");
    }
  }
  const int dt = b & 3, mt = b >> 2;
  const bool g1 = (b & 15) < 14;
  const int a1 = b - 2 * (b >> 4), ft = a1 >> 2, d1 = a1 & 3;
  const int g = lane >> 2, t = lane & 3, r8 = lane & 7, mi = lane >> 3;
  OBSG(FREQ && tid == 160, 128, 160);
  __syncthreads();
  if (warp >= 8) {
    asm volatile("setmaxnreg.dec.sync.aligned.u32 40;");
    const int pw = warp - 8;
    unsigned char* scr = p.scr;
    if (WPF && pw == 2) {
      mbar_wait(bars + B_X + (WPF - 1) * 8, 0);
      if (b < 112 && lane < 28) asm volatile("prefetch.global.L2 [%0];" :: "l"(p.wqkv + (b * 4 + lane / 7) * 2688 + (lane % 7) * 128) : "memory");
      if (lane == 31) asm volatile("prefetch.tensormap [%0];" :: "l"(&m_wq) : "memory");
      __syncwarp();
    }
    if (NW0 < 7 && pw == 3) {
      mbar_wait(bars + B_X, 0);
      if (elect()) {
#pragma unroll 1
        for (int i = NW0; i < 7; i++) load_kv(i);
      }
      __syncwarp();
    }
    {
      const int c0 = pw * 14 + (mi >> 1);
      unsigned char* dst = scr + (pw * HU_T + rb * 2 + (hp >> 2)) * BT + ((hp & 3) * 2 + (mi & 1)) * 1792 + (mi >> 1) * 128 + r8 * 16;
      const uint32_t xs = base + OFF_X + (hp * 16 + (lane & 15)) * 128;
      uint4 H[7];
      named_sync(9, 160);
#pragma unroll
      for (int i = 0; i < 7; i++) H[i] = lds128(xs + ((c0 + 2 * i) >> 3) * 16384 + ((((c0 + 2 * i) & 7) ^ r8) << 4));
      asm volatile("" :: "r"(H[6].w), "r"(H[0].x) : "memory");
      if (pw != 3) named_arrive(8, 384);
      else {
        named_sync(8, 384);
        if (elect()) {
          mbar_expect_tx(bars + B_WQ, 28672); tma3d(base + OFF_WQ, &m_wq, wcol, 0, 0, bars + B_WQ);
          mbar_expect_tx(bars + B_WQ2, 28672); tma3d(base + OFF_WQ + 28672, &m_wq, wcol, 224, 0, bars + B_WQ2);
        }
        __syncwarp();
      }
      const uint2 st = lds64(base + OFF_LN + (lane & 15) * 8);
      const float sum = __uint_as_float(st.x), mean = sum * (1.0f / D_), var = ln_var(mean, __uint_as_float(st.y));
      const float m = rbf(mean), r = ln_rstd(var), r2 = ln_rstd(var * r * r);
      const float nc = fmaf(m, (float)D_, -sum) * (1.0f / D_) * (r * r2);
      const uint32_t m2 = pack2(m, m), r2x = pack2(r * r2, r * r2), nc2 = pack2(nc, nc);
      auto f = [&](uint32_t v) { return hfma2(hsub2(v, m2), r2x, nc2); };
#pragma unroll
      for (int i = 0; i < 7; i++) stg128(dst + i * 256, f(H[i].x), f(H[i].y), f(H[i].z), f(H[i].w));
      if (pw != 1) named_arrive(4, 128);
    }
    const int lane = lane_id();
    if (pw == 0) {
      if (elect()) {
        asm volatile("prefetch.tensormap [%0];" :: "l"(&m_w1) : "memory");
        asm volatile("prefetch.tensormap [%0];" :: "l"(&m_w2) : "memory");
        asm volatile("prefetch.tensormap [%0];" :: "l"(&m_res) : "memory");
      }
      if (g1) produce_box<0>(base, 0, 32, &m_w1, ft * 64, 0);
      auto load_res = [&]() { if (elect()) { mbar_expect_tx(bars + B_RES, BT); tma3d(base + OFF_Q, &m_res, dt * 112, mt * 64, 0, bars + B_RES); } };
      if (RESP == 0) { mbar_wait(bars + B_ATT, 0); load_res(); }
      mbar_wait(bars + B_WO, 0);
      produce_lin<0>(base, 0, 7, scr + (dt * HU_T + 60) * BT, BT);
      if (NX) {
        produce_box<0>(base, 7, XT, &m_w2, mt * 64, 0);
        if (elect()) {
          mbar_expect_tx(bars + B_XW, NX * 8192);
#pragma unroll 1
          for (int i = 0; i < NX; i++) tma3d(base + OFF_XW + i * 8192, &m_w2, mt * 64, (XS - 7 + i) * 64, 0, bars + B_XW);
        }
        __syncwarp();
        produce_box<0>(base, XT, XS, &m_w2, mt * 64, (XT - 7) * 64);
        mbar_wait(bars + B_XW, 0);
#pragma unroll 1
        for (int it = XS; it < XS + NX; it++) { mbar_wait(bars + B_EMPTY + (it & 7) * 8, (it >> 3) & 1); if (lane == 0) mbar_arrive(bars + (it & 7) * 8); }
        __syncwarp();
        produce_box<0>(base, XS + NX, 35, &m_w2, mt * 64, (XS + NX - 7) * 64);
      } else produce_box<0>(base, 7, 35, &m_w2, mt * 64, 0);
      if (RESP) load_res();
    } else if (pw == 1) {
      named_sync(4, 128);
      const unsigned char* hl = scr + (rb * 2 + (hp >> 2)) * BT + (hp & 3) * 3584 + min(lane, 27) * 128;
      if (RB & 2) settle(probe(hl) ^ probe(hl + HU_T * BT) ^ probe(hl + 2 * HU_T * BT) ^ probe(hl + 3 * HU_T * BT));
      publish(scr, C_H + (b & 3));
      OBS(lane == 0, 4);
      if (g1) {
        spin_ge(scr, C_H + (lane & 3), 32);
        OBS(lane == 0, 16);
        if (HP) { produce_lin<HP>(base, 0, 8, scr + d1 * HU_T * BT, BT, clock()); produce_lin<0>(base, 8, 32, scr + (d1 * HU_T + 8) * BT, BT); }
        else produce_lin<0>(base, 0, 32, scr + d1 * HU_T * BT, BT);
      }
      mbar_wait(bars + B_O, 0);
      produce_lin<OPP>(base, 0, 7, scr + O_OFF + mt * 57344, 8192, clock());
      const unsigned char* us = scr + (dt * HU_T + 32) * BT;
#pragma unroll
      for (int i = 0; i < NPRE; i++) {
        mbar_wait(bars + B_EMPTY + ((7 + i) & 7) * 8, i > 0);
        if (elect()) mbar_expect_tx(bars + ((7 + i) & 7) * 8, BT);
        __syncwarp();
      }
      spin_ge(scr, C_U + (ALL4 ? lane & 3 : dt) + (mt & (UREP - 1)) * 4, 28);
      if (elect()) {
#pragma unroll
        for (int i = 0; i < NPRE; i++) bulk_g2s(base + ((7 + i) & 7) * SLOT + 8192, us + i * BT, BT, bars + ((7 + i) & 7) * 8);
      }
      const uint32_t tu = clock();
      OBS(lane == 0, 18);
      produce_lin<UP>(base, 7 + NPRE, 15, us + NPRE * BT, BT, tu + NPRE * UP - U0);
      produce_lin<0>(base, 15, 35, us + 8 * BT, BT);
      unsigned tk = 0;
      if (lane == 0) tk = atomicAdd((unsigned*)(scr + CNT_OFF + C_TK * 128), 1u);
      if (__shfl_sync(0xffffffffu, tk, 0) == 127) {
#pragma unroll 1
        for (int i = lane; i < 192; i += 32) *(unsigned*)(scr + CNT_OFF + i * 128) = 0;
        publish(scr, C_EPOCH);
      }
    } else if (pw == 2) {
      uint32_t tn = clock() + PACE0 + b * STAG;
      const unsigned char* src = p.w1 + b * 4096 + lane * 128;
#pragma unroll 1
      for (int i = 0; i < 28 + FREQ * 2; i++) {
        while ((int)(clock() - tn) < 0) __nanosleep(20);
        if (i == 14) src = p.w2 + b * 4096 + lane * 128;
        if (i < 28) asm volatile("prefetch.global.L2 [%0];" :: "l"(src) : "memory");
        OBSG(FREQ && lane == 0, 129 + i, 161 + i);
        src += 128 * 4096;
        tn += i < 14 ? PACE1 : PACE2;
      }
    } else {
      if (b < 112) retile_wo(p.wo, scr, b, lane_id());
      const int lane = lane_id();
      uint32_t tag;
      asm volatile("ld.relaxed.gpu.global.u32 %0, [%1];" : "=r"(tag) : "l"(scr + CNT_OFF + C_EPOCH * 128) : "memory");
      tag++;
      tag = (tag & 0x3fffu) | ((tag << 2) & 0x3fff0000u);
      unsigned char* hg = scr + HALO_OFF + (rb * 8 + hp) * 3584;
      named_sync(1, 64);
      if (rb < 15) {
#pragma unroll
        for (int q = 0; q < 7; q += 4) {
          uint4 v[4];
#pragma unroll
          for (int i = q; i < q + 4 && i < 7; i++) v[i - q] = lds128(base + OFF_K + 8 * 3584 + i * 512 + lane * 16 + (i * 32 + lane < 112 && !(lane & 7) ? 1792 : 0));
#pragma unroll
          for (int i = q; i < q + 4 && i < 7; i++) stg128(hg + i * 512 + lane * 16, (lane & 7) == (i * 32 + lane < 112) ? tag : v[i - q].x, v[i - q].y, v[i - q].z, v[i - q].w);
        }
      }
      if (TAG == 1 && rb < 15) publish(scr, C_HALO + rb * 8 + hp);
      OBS(lane == 0, 29);
      if (rb > 0) {
        if (TAG == 1) spin_ge(scr, C_HALO + (rb - 1) * 8 + hp, 1); else __nanosleep(HWAIT);
        const uint32_t la = base + OFF_K + min(lane, 27) * 128;
#pragma unroll 1
        for (int n = 0;; n++) {
          if (elect()) { mbar_expect_tx(bars + B_XW, 3584); bulk_g2s(base + OFF_K, hg - 8 * 3584, 3584, bars + B_XW); }
          __syncwarp();
          mbar_wait(bars + B_XW, n & 1);
          if (__all_sync(0xffffffffu, lds64(la + (lane < 14 ? 16 : 0)).x == tag)) break;
          if (n > 1000000) asm volatile("trap;");
        }
        if (lane < 14) { const uint4 v = lds128(la); sts128(la + 1792, v.x, v.y, v.z, v.w); }
      } else {
#pragma unroll
        for (int i = 0; i < 7; i++) sts128(base + OFF_K + i * 512 + lane * 16, 0, 0, 0, 0);
      }
      OBS(lane == 0, 12);
      smem_fence();
      __syncwarp();
      if (lane == 0) mbar_arrive(bars + B_HALO);
      __syncwarp();
      if ((RB & 1) && b < 112) {
        settle(probe(scr + (((b & 1) * 2 + (lane >> 4)) * HU_T + 60 + (b >> 4)) * BT + ((b >> 1) & 7) * 1792 + min(lane & 15, 13) * 128));
        publish(scr, C_WO);
      }
      if (RB & 1) mbar_wait(bars + (g1 ? B_GATE + 8 : B_ATT), 0);
      spin_ge(scr, C_WO, 112);
      if (lane == 0) mbar_arrive(bars + B_WO);
      mbar_wait(bars + B_ATT, 0);
      spin_ge(scr, C_O + (mt >> 1), 8);
      OBS(lane == 0, 17);
      if (lane == 0) mbar_arrive(bars + B_O);
    }
  } else {
    asm volatile("setmaxnreg.inc.sync.aligned.u32 232;");
    const int wg = warp >> 2, w4 = warp & 3, th = wg ^ 1;
    const bool rel = (tid & 127) < 2;
    unsigned char* scr = p.scr;
    uint32_t X[28][4];
    float aq[28];
    const uint32_t dlo = (base >> 4) + (512u << 16) + (hp & 1), dlq = dlo + (OFF_WQ >> 4);
    {
      uint32_t xa[4];
#pragma unroll
      for (int k = 0; k < 4; k++) xa[k] = base + OFF_X + (th * 64 + w4 * 16 + (mi >> 1) * 8 + r8) * 128 + (((2 * k + (mi & 1)) ^ r8) << 4);
      float c0[2][4] = {}, c1[2][4] = {};
      uint32_t one[8];
#pragma unroll
      for (int j = 0; j < 8; j++) asm volatile("{\n.reg .u32 y;\nmov.u32 y, %%tid.y;\nmad.lo.u32 %0, y, %1, 0x3f803f80;\n}" : "=r"(one[j]) : "r"(lane + j));
      asm volatile("" : "+l"(scr));
      uint32_t ok = 0;
      const uint32_t bx = bars + B_X + XSPLIT * wg * 64;
      if (HEAT) {
#pragma unroll 1
        for (int n = 0; n < 64 && !ok; n++) { mma16816(c0[0], 0, 0, 0, 0, 0, 0); ok = mbar_try(bars + B_X, 0); }
        if (XSPLIT && wg) ok = 0;
      }
#pragma unroll
      for (int i = 0; i < 8; i++) {
        if (i < 7) {
          if (!ok) mbar_wait(bx + i * 8, 0);
          OBS(tid == 64 && i == 0, 0); OBS(tid == 64 && i == 6, 15);
#pragma unroll
          for (int k = 0; k < 4; k++) ldsm4(X[i * 4 + k], xa[k] + i * 16384);
          if (i < 6) ok = mbar_try(bx + i * 8 + 8, 0);
        }
        if (i > 0) {
#pragma unroll
          for (int k = i * 4 - 4; k < i * 4; k++) {
            mma16816(c0[k & 1], X[k][0], one[(k & 1) * 4], X[k][1], one[(k & 1) * 4 + 1], X[k][0], X[k][1]);
            mma16816(c1[k & 1], X[k][2], one[(k & 1) * 4 + 2], X[k][3], one[(k & 1) * 4 + 3], X[k][2], X[k][3]);
          }
        }
      }
      float st[4];
#pragma unroll
      for (int j = 0; j < 2; j++) {
        st[j] = __shfl_sync(0xffffffffu, (g & 1) ? c0[0][2 * j + 1] + c0[1][2 * j + 1] : c0[0][2 * j] + c0[1][2 * j], (lane & 28) | (g >> 1));
        st[2 + j] = __shfl_sync(0xffffffffu, (g & 1) ? c1[0][2 * j + 1] + c1[1][2 * j + 1] : c1[0][2 * j] + c1[1][2 * j], (lane & 28) | (g >> 1));
      }
      named_arrive(8, 384);
      asm volatile("{\n.reg .pred q;\nsetp.ne.u32 q, %3, 0;\n@q st.shared.v2.f32 [%0], {%1,%2};\n@q bar.arrive 9, 160;\n}"
                   :: "r"(base + OFF_LN + ((t & 1) * 8 + g) * 8), "f"((t & 1) ? st[3] : st[1]), "f"((t & 1) ? st[2] : st[0]), "r"((uint32_t)((warp ^ 4) == hp)) : "memory");
      ok = mbar_try(bars + B_KV, 0);
      LnC l0, l1;
      float eps = 1e-5f;
#pragma unroll 1
      do {
        l0 = ln_consts(st[1], st[0], eps); l1 = ln_consts(st[3], st[2], eps);
#pragma unroll
        for (int k = 0; k < PRE * 16; k++) X[k >> 2][k & 3] = hsub2(X[k >> 2][k & 3], k & 2 ? l1.m : l0.m);
        eps += eps;
      } while ((l0.rl ^ l1.rl) == 4);
      OBS(tid == 32, 1);
      float ak[60], *av = ak + 32;
      const int pp_in = wg ? 6 : 0, pp_out = wg ? 0 : 6;
#pragma unroll
      for (int s = 0; s < 7; s++) {
#pragma unroll
        for (int k = s * 4; k < s * 4 + 4; k++) {
          if (s < PRE) {
            auto f = [&](uint32_t d, const LnC& l) { return hfma2(d, l.rh, hmul2(d, l.rl)); };
            const uint32_t y = f(X[k][1], l0);
            X[k][0] = f(X[k][0], l0); X[k][1] = f(X[k][2], l1); X[k][2] = y; X[k][3] = f(X[k][3], l1);
          } else {
            const uint32_t y = ln_apply(X[k][1], l0);
            X[k][0] = ln_apply(X[k][0], l0); X[k][1] = ln_apply(X[k][2], l1); X[k][2] = y; X[k][3] = ln_apply(X[k][3], l1);
          }
        }
        if (__builtin_expect(!ok, 0)) { mbar_wait(bars + B_KV + s * 8, 0); if (s == 6) mbar_wait(bars + B_WQ, 0); }
        if (s == 0) fresh(ak);
        if (s == 6) { wg_wait<0>(); if ((tid & 127) == 0) mbar_arrive(bars + B_EMPTY + 3 * 8); }
        OBS(KOBS && (tid & 127) == 0, 40 + wg * 32 + s);
        if (PPM == 2 ? (wg ? s < 6 : s > 1) : (wg || s)) named_sync(pp_in, 256);
        OBS(KOBS && (tid & 127) == 32, 48 + wg * 32 + s);
        OBS(tid == 64 && s == 0, 2);
        wg_fence();
#pragma unroll
        for (int k = 0; k < 4; k++) {
          wgmma_rs_n120<1>(ak, X[s * 4 + k], mkdesc(HI_SW128, dlo + s * 1024 + k * 128), (s | k) != 0);
        }
        wg_commit();
        if (s == 6) {
          fresh(aq);
#pragma unroll
          for (int k = 0; k < 4 * QA; k++) {
            if (k == 4 * QA - PQE) named_arrive(pp_out, 256);
            wgmma_rs_n56<1>(aq, X[k], mkdesc(HI_SW128, dlq + k * 128), k);
          }
          wg_commit();
        }
        if (s < 6 || PQE == 0) named_arrive_if(PPM != 2 || (wg ? s != 5 : s != 0), pp_out, 256);
        fence_code(s);
        OBS(KOBS && (tid & 127) == 64, 56 + wg * 32 + s);
        if (s < 6) ok = mbar_try(bars + B_KV + s * 8 + 8, 0);
        if (s == 5) ok &= mbar_try(bars + B_WQ, 0);
        OBS(tid == 64 && s == 5, 31);
        if (s > 0) wg_wait<1>();
        OBS(KOBS && (tid & 127) == 96, 64 + wg * 32 + s);
        if ((s == 2 || s == 3 || s == 5) && (tid & 127) == 0) mbar_arrive(bars + B_EMPTY + (s == 5 ? 2 : s - 2) * 8);
      }
      if ((tid & 127) == 0) mbar_arrive(bars + B_EMPTY + 4 * 8);
      OBS(tid == 32, 3);
      {
        const uint32_t kst = base + OFF_K + (2 + (warp ^ 4) * 2 + (mi & 1)) * 1792 + (mi >> 1) * 896 + r8 * 16;
#pragma unroll
        for (int n = 0; n < 7; n++)
          stsm4(kst + n * 128, pack2(ak[n * 4], ak[n * 4 + 1]), pack2(ak[n * 4 + 2], ak[n * 4 + 3]), pack2(av[n * 4], av[n * 4 + 1]), pack2(av[n * 4 + 2], av[n * 4 + 3]));
        named_arrive_if(warp == 3, 1, 64);
      }
      OBS(tid == 96, 32); OBS(tid == 224, 34);
      wg_wait<0>();
      if ((tid & 127) == 0) mbar_arrive(bars + B_EMPTY + 5 * 8);
      mbar_wait(bars + B_WQ2, 0);
    }
    const unsigned short *bp1 = (const unsigned short*)p.b1 + (g1 ? ft * 64 : 0) + w4 * 16 + g, *bp2 = (const unsigned short*)p.b2 + mt * 64 + w4 * 16 + g;
    const uint32_t braw[4] = {__ldg(bp1), __ldg(bp1 + 8), __ldg(bp2), __ldg(bp2 + 8)};
    auto q_rest = [&]() {
      wg_fence();
#pragma unroll
      for (int s = QA; s < 7; s++) {
#pragma unroll
        for (int k = s * 4; k < s * 4 + 4; k++) wgmma_rs_n56<1>(aq, X[k], mkdesc(HI_SW128, dlq + k * 128), 1);
        wg_commit();
        if (s == 5) { wg_wait<2>(); if ((tid & 127) == 0) mbar_arrive(bars + B_EMPTY + 6 * 8); }
      }
    };
    uint32_t Q[4][4];
    auto q_pack = [&]() {
#pragma unroll
      for (int n = 0; n < 14; n++) { const int m = n + 2 * (n > 7); Q[m >> 2][m & 3] = pack2(aq[n * 2], aq[n * 2 + 1]); }
#pragma unroll
      for (int h = 0; h < 2; h++) { Q[2][h] = t < 2 ? 0u : Q[1][2 + h]; Q[1][2 + h] = t < 2 ? Q[1][2 + h] : 0u; }
    };
    float acc[56];
    auto ai = [](int p) { return p < 4 ? 48 + (p & 1) * 4 + (p & 2) : (p - 4) * 4; };
    uint32_t xch, ts, tl;
    unsigned char *ug, *ur, *uc, *outp, *outq;
    auto setup_u = [&]() {
      xch = pin(base + OFF_K + (tid & 127) * 16);
      ug = pin(scr + (d1 * HU_T + 32 + ft) * BT + w4 * 3584 + lane * 4 + wg * 1792);
      const int n = wg ? min(lane, 11) : lane & 15;
      ur = pin(ug + (n < 14 ? n * 128 : (n - 2) * 128 + 1792));
      uc = pin(scr + CNT_OFF + (C_U + d1 + (lane & (UREP - 1)) * 4) * 128);
    };
    auto setup_out = [&]() {
      const uint32_t tb = base + OFF_K + 6144 + warp * 2560;
      ts = pin(tb + mi * 160 + r8 * 16); tl = pin(tb + t * 160 + g * 16);
      unsigned char* o = p.out + (mt * 64 + w4 * 16 + g) * 896 + dt * 224;
      outp = pin(o + th * 7168 + t * 16); outq = pin(o + (t >> 1) * 7168 + 192 + (t & 1) * 16);
    };
    auto give = [&](const float (&a)[56], int id) {
#pragma unroll
      for (int i = 0; i < 48; i += 16) sts128(xch + i * 128, pack2(a[i + 2], a[i + 3]), pack2(a[i + 6], a[i + 7]), pack2(a[i + 10], a[i + 11]), pack2(a[i + 14], a[i + 15]));
      named_arrive(id, 256);
    };
    auto take = [&](uint32_t (&r)[12], int id) {
      named_sync(id, 256);
#pragma unroll
      for (int i = 0; i < 3; i++) { const uint4 v = lds128(xch + i * 2048); r[i * 4] = v.x; r[i * 4 + 1] = v.y; r[i * 4 + 2] = v.z; r[i * 4 + 3] = v.w; }
    };
    float hv[32];
    auto keep_h = [&](int i) {
      const float hb0 = 0.5f * bf_lo(braw[i]), hb1 = 0.5f * bf_lo(braw[i + 1]);
#pragma unroll
      for (int j = 0; j < 32; j++) hv[j] = fmaf(acc[ai(j >> 1) + (j & 1)], 0.5f, j >= 4 && j < 8 ? hb1 : hb0);
    };
    auto take_h = [&](int i) {
      const float hb1 = 0.5f * bf_lo(braw[i + 1]);
      uint32_t r[12];
      take(r, 5);
#pragma unroll
      for (int j = 0; j < 12; j++) { hv[8 + 2 * j] = fmaf(bf_lo(r[j]), 0.5f, hb1); hv[9 + 2 * j] = fmaf(bf_hi(r[j]), 0.5f, hb1); }
    };
    uint4 Xr[4];
    auto get_x = [&]() {
      const uint32_t xr = base + OFF_Q + (w4 * 16 + g) * 224;
      mbar_wait(bars + B_RES, 0);
      Xr[0] = lds128(xr + (t >> 1) * 1792 + 192 + (t & 1) * 16);
#pragma unroll
      for (int i = 1; i < 4; i++) Xr[i] = lds128(xr + th * 1792 + t * 16 + (i - 1) * 64);
    };
    auto gelu = [&](int j) {
      const float h0 = hv[2 * j], h1 = hv[2 * j + 1];
      const float t0 = tanh_fast(h0 * fmaf(h0 * h0, 0.2854192648f, 1.5957691216f)), t1 = tanh_fast(h1 * fmaf(h1 * h1, 0.2854192648f, 1.5957691216f));
      stg32(ug + (ai(j) & 2) * 896 + (ai(j) >> 2) * 128, pack2(fmaf(h0, t0, h0), fmaf(h1, t1, h1)));
    };
    uint32_t Sv[16];
    auto gate = [&](int i) {
      uint32_t R[4];
#pragma unroll
      for (int q = 0; q < 4; q++) {
        const int j = i * 4 + q;
        const float h0 = hv[2 * j], h1 = hv[2 * j + 1];
        R[q] = hmul2(Sv[j], pack2(fmaf(h0, tanh_fast(h0), h0), fmaf(h1, tanh_fast(h1), h1)));
      }
      stsm4(ts + i * 640, R[0], R[1], R[2], R[3]);
    };
    auto leave = [&](int i) {
      __syncwarp();
      const uint4 v = lds128(tl + i * 640), x = Xr[i];
      stg128(i ? outp + (i - 1) * 64 : outq, hadd2(x.x, v.x), hadd2(x.y, v.y), hadd2(x.z, v.z), hadd2(x.w, v.w));
    };
    if (wg == 0) {
      named_sync(0, 256);
      OBS(tid == 96, 14);
      q_rest();
      named_arrive(6, 256);
      wg_wait<0>();
      if (tid == 0) mbar_arrive(bars + B_EMPTY + 7 * 8);
      q_pack();
      const uint32_t qst = base + OFF_Q + 8192 + (mi >> 1) * 1024 + (w4 * 16 + (mi & 1) * 8 + r8) * 16;
#pragma unroll
      for (int n = 0; n < 4; n++) stsm4(qst + n * 2048, Q[n][0], Q[n][1], Q[n][2], Q[n][3]);
      smem_fence();
      named_arrive(7, 256);
      OBS(tid == 32, 5);
      fresh(acc);
      setup_u();
      if (g1) {
        mbar_wait(bars, 0); mbar_wait(bars + 8, 0);
        if (TS) {
          const uint32_t tg = lds64(bars + B_T0).x;
          while ((int)(clock() - tg) < 0);
        }
        named_sync(0, 256);
        gemm_issue<1>(acc, base >> 4, base >> 4, 0);
        OBS(tid == 0, 20);
        gemm_loop<1>(acc, base, 1, 32, rel, 40, 1, tid == 32 ? J1 : tid == 64 ? J2 : tid == 96 ? J3 : -1, bars + B_GATE - 8 + w4 * 8);
        mbar_wait(bars + B_ATT, 0);
        wg_wait<0>();
        OBS(tid == 0, 21);
        give(acc, 5);
        mbar_arrive_if(rel, bars + B_EMPTY + 7 * 8);
        fence_code(30);
        keep_h(0);
#pragma unroll
        for (int j = 0; j < 16; j++) { gelu(j); if (j % GCH == GCH - 1 && j < 15) fence_code(8 + j); }
        if (RB & 16) settle(probe(ur));
        if (w4) named_arrive(2, 256);
        else { named_sync(2, 256); asm volatile("{\n.reg .pred q;\nsetp.lt.u32 q, %1, %2;\n@q red.relaxed.gpu.global.add.u32 [%0], 1;\n}" :: "l"(uc), "r"(lane), "n"(UREP) : "memory"); OBS(tid == 0, 9); }
      } else {
        if (lane == 0 && w4) mbar_arrive(bars + B_GATE - 8 + w4 * 8);
      }
      setup_out();
      if (!RESP) get_x();
      uint32_t r[12];
      take(r, 3);
#pragma unroll
      for (int j = 0; j < 16; j++) Sv[j] = r[j < 4 ? 0 : j - 4];
      asm volatile("" :: "r"(r[0]), "r"(r[11]) : "memory");
      named_arrive(10, 256);
      if (RESP) get_x();
      take_h(2);
    } else {
      const uint32_t dq = ((base + OFF_Q) >> 4) + (64u << 16), dk = (base + OFF_K) >> 4;
      const bool odd = g & 1, early = 2 * t + (g & 1) > g;
      uint32_t selA[5], selB[4];
#pragma unroll
      for (int j = 0; j < 5; j++) selA[j] = j == w4 + (early ? 0 : 1) ? (odd ? 0x1044u : 0x4410u) : 0x4444u;
#pragma unroll
      for (int j = 0; j < 4; j++) selB[j] = j == w4 ? (odd ? 0x3244u : 0x4432u) : 0x4444u;
      float Sc[2][40], Op[2][2][16];
      uint32_t A[2][5][4];
      auto scores = [&](int T) {
        fresh(Sc[0]); fresh(Sc[1]);
#pragma unroll
        for (int k = 0; k < 2; k++) {
#pragma unroll
          for (int hh = 0; hh < 2; hh++)
            if (T) wgmma_n80<0, 0>(Sc[hh], mkdesc(8, dq + 512 + hh * 256 + k * 128), mkdesc(112, dk + (8u << 16) + 896 + hh * 24 + k * 16), k);
            else wgmma_rs_n80<0>(Sc[hh], Q[hh * 2 + k], mkdesc(112, dk + (8u << 16) + hh * 24 + k * 16), k);
        }
      };
      auto softmax = [&](int T) {
#pragma unroll
        for (int hh = 0; hh < 2; hh++) {
          uint32_t pp[2];
#pragma unroll
          for (int h = 0; h < 2; h++) {
            float c[3];
#pragma unroll
            for (int n = 0; n < 3; n++) {
              const float* q = Sc[hh] + (h + n) * 4 + 2 * h;
              asm("{\n.reg .pred p, a, b, c;\nsetp.ne.u32 p, %9, 0;\nsetp.eq.u32 a, %10, 1;\nsetp.eq.u32 b, %10, 2;\nsetp.eq.u32 c, %10, 3;\n"
                  "selp.f32 %0, %2, %1, p;\n@a selp.f32 %0, %4, %3, p;\n@b selp.f32 %0, %6, %5, p;\n@c selp.f32 %0, %8, %7, p;\n}"
                  : "=&f"(c[n]) : "f"(q[0]), "f"(q[1]), "f"(q[8]), "f"(q[9]), "f"(q[16]), "f"(q[17]), "f"(q[24]), "f"(q[25]), "r"((uint32_t)odd), "r"((tid >> 5) & 3));
            }
            uint32_t pk = pack2(early ? c[0] : c[2], c[1]);
            pk = pack2(bf_lo(pk) * SCALE, bf_hi(pk) * SCALE);
            float l0 = bf_lo(pk), l1 = bf_hi(pk);
            if (T == 0 && w4 == 0 && rb == 0) { if (early) l0 = -1e9f; if (h == 0) l1 = -1e9f; }
            float mx = fmaxf(l0, l1);
            mx = fmaxf(mx, __shfl_xor_sync(0xffffffffu, mx, 1));
            mx = fmaxf(mx, __shfl_xor_sync(0xffffffffu, mx, 2));
            float p0 = ex2_fast((l0 - mx) * LOG2E), p1 = ex2_fast((l1 - mx) * LOG2E);
            float sm = p0 + p1;
            sm += __shfl_xor_sync(0xffffffffu, sm, 1);
            sm += __shfl_xor_sync(0xffffffffu, sm, 2);
            const float inv = rcp_fast(sm);
            pp[h] = pack2(p0 * inv, p1 * inv);
          }
#pragma unroll
          for (int j = 0; j < 5; j++) {
            A[hh][j][0] = __byte_perm(pp[0], 0, selA[j]); A[hh][j][1] = j ? __byte_perm(pp[1], 0, selB[j ? j - 1 : 0]) : 0u;
            A[hh][j][2] = j < 4 ? __byte_perm(pp[0], 0, selB[j & 3]) : 0u; A[hh][j][3] = __byte_perm(pp[1], 0, selA[j]);
          }
        }
      };
      auto values = [&](int T) {
        fresh(Op[T][0]); fresh(Op[T][1]);
#pragma unroll
        for (int j = 0; j < 5; j++)
#pragma unroll
          for (int hh = 0; hh < 2; hh++) {
            wgmma_rs_n32<1>(Op[T][hh], A[hh][j], mkdesc(8, dk + (112u << 16) + 56 + T * 896 + hh * 24 + j * 224), j);
          }
        wg_commit();
      };
      uint32_t Ob[2][14];
      auto pack = [&](int T) {
        const float (&O)[2][16] = Op[T];
#pragma unroll
        for (int n = 0; n < 7; n++)
#pragma unroll
          for (int h = 0; h < 2; h++) {
            if (n < 3) Ob[T][n * 2 + h] = pack2(O[0][n * 4 + 2 * h], O[0][n * 4 + 2 * h + 1]);
            else if (n == 3) Ob[T][n * 2 + h] = pack2(t < 2 ? O[0][12 + 2 * h] : O[1][2 * h], t < 2 ? O[0][13 + 2 * h] : O[1][2 * h + 1]);
            else Ob[T][n * 2 + h] = pack2(O[1][(n - 3) * 4 + 2 * h], O[1][(n - 3) * 4 + 2 * h + 1]);
          }
      };
      smem_fence();
      named_sync(6, 256);
      OBS(tid == 224, 26);
      q_rest();
      named_sync(7, 256);
      wg_fence();
      scores(1);
      wg_commit();
      named_arrive_if(g1, 0, 256);
      wg_wait<2>();
      if (tid == 128) mbar_arrive(bars + B_EMPTY + 7 * 8);
      wg_wait<0>();
      q_pack();
      OBS(tid == 160, 10);
      softmax(1);
      OBS(tid == 160, 30);
      mbar_wait(bars + B_HALO, 0);
      OBS(tid == 160, 7);
      mbar_wait(bars + B_GATE, 0);
      wg_fence();
      scores(0);
      values(1);
      wg_wait<0>();
      OBS(tid == 160, 33);
      unsigned char* og = scr + O_OFF + rb * 2 * 57344 + hp * 7168 + w4 * 256 + lane * 4;
      uint32_t seen[6];
      auto put = [&](int T) {
#pragma unroll
        for (int n = 0; n < 14; n++) { stg32(og + T * 57344 + (n >> 1) * 1024 + (n & 1) * 128, Ob[T][n]); if (n == 5 || n == 11 || n == 13) seen[T * 3 + n / 6] = (RB & 8) ? probe(og + T * 57344 + ((n >> 1) - (n == 13 ? 0 : min(g, 2))) * 1024 + (t & 1) * 128) : 0;
          if (OSLEEP && n % OGRP == OGRP - 1) __nanosleep(OSLEEP); }
      };
      if (OMODE == 1) { pack(1); put(1); }
      softmax(0);
      if (OMODE == 2) { pack(1); put(1); }
      mbar_wait(bars + B_GATE + 8, 0);
      wg_fence();
      values(0);
      if (OMODE == 3) { pack(1); put(1); }
      wg_wait<0>();
      OBS(tid == 160, 35);
      named_sync(11, 128);
      if (tid == 160) mbar_arrive(bars + B_ATT);
      if (OMODE == 0) pack(1);
      pack(0);
      if (J3 > J2) mbar_wait(bars + B_GATE + 16, 0);
      if (OMODE == 0) put(1);
      put(0);
      OBS(tid == 160, 28);
      if (RB & 8) settle(seen[0] ^ seen[1] ^ seen[2] ^ seen[3] ^ seen[4] ^ seen[5]);
      named_sync(11, 128);
      if (warp == 4) publish(scr, C_O + rb);
      OBS(tid == 160, 8);
      setup_u(); setup_out();
      float as[56];
      uint32_t uv = 0;
      if (g1) {
        take_h(0);
        if (!RESP && XE) get_x();
#pragma unroll
        for (int j = 4; j < OPJ; j++) { gelu(j); if (j % GCH == GCH - 1 && j < OPJ - 1) fence_code(40 + j); }
        if ((RB & 16) && !UO) settle(probe(ur));
        if ((RB & 16) && UO) uv = probe(ur);
        else named_arrive(2, 256);
      } else if (!RESP && XE) get_x();
      fresh(as);
      gemm_stage<0>(as, base, 0, 0);
      OBS(tid == 128, 22);
      if ((RB & 16) && UO) { settle(uv); named_arrive_if(g1, 2, 256); }
      gemm_loop<0>(as, base, 1, 7, rel, 104);
      fresh(acc);
      if (SEARLY) { wg_wait<0>(); mbar_arrive_if(rel, bars + B_EMPTY + 6 * 8); give(as, 3); if (!RESP && !XE) get_x(); }
      gemm_stage<1>(acc, base, 7, 0);
      OBS(tid == 128, 24);
      if (!SEARLY) { wg_wait<1>(); mbar_arrive_if(rel, bars + B_EMPTY + 6 * 8); give(as, 3); }
#pragma unroll
      for (int j = 0; j < 16; j++) Sv[j] = pack2(as[ai(j)], as[ai(j) + 1]);
      gemm_loop<1, NX>(acc, base, 8, 35, rel, 65);
      if (RESP) get_x();
      named_sync(10, 256);
      wg_wait<0>();
      OBS(tid == 128, 25);
      give(acc, 5);
      fence_code(31);
      keep_h(2);
      gate(0); leave(0);
    }
    {
#pragma unroll
      for (int i = 1; i < 4; i++) { gate(i); leave(i); }
      OBS(tid == 128, 27);
    }
  }
}

typedef CUresult (*EncFn)(CUtensorMap*, CUtensorMapDataType, cuuint32_t, void*, const cuuint64_t*, const cuuint64_t*, const cuuint32_t*,
                          const cuuint32_t*, CUtensorMapInterleave, CUtensorMapSwizzle, CUtensorMapL2promotion, CUtensorMapFloatOOBfill);
void enc(EncFn f, CUtensorMap* m, const void* ptr, cuuint64_t d0, cuuint64_t d1, cuuint64_t d2, cuuint64_t s1, cuuint64_t s2, cuuint32_t b1, cuuint32_t b2, cuuint32_t b0 = 64) {
  const cuuint64_t gd[3] = {d0, d1, d2}, gs[2] = {s1 * 2, s2 * 2};
  const cuuint32_t bx[3] = {b0, b1, b2}, es[3] = {1, 1, 1};
  f(m, CU_TENSOR_MAP_DATA_TYPE_BFLOAT16, 3, (void*)ptr, gd, gs, bx, es, CU_TENSOR_MAP_INTERLEAVE_NONE, b0 == 64 ? CU_TENSOR_MAP_SWIZZLE_128B : CU_TENSOR_MAP_SWIZZLE_NONE,
    CU_TENSOR_MAP_L2_PROMOTION_L2_128B, CU_TENSOR_MAP_FLOAT_OOB_FILL_NONE);
}
}

extern "C" void kernel_launch(void* const* d_in, const int* in_sizes, int n_in, void* d_out, int out_size) {
  (void)in_sizes; (void)n_in; (void)out_size;
  void* fp = nullptr;
  cudaDriverEntryPointQueryResult qr;
  cudaGetDriverEntryPoint("cuTensorMapEncodeTiled", &fp, cudaEnableDefault, &qr);
  EncFn f = (EncFn)fp;
  CUtensorMap m_x, m_wkv, m_wq, m_w1, m_w2, m_res;
  void* scr = nullptr;
  cudaGetSymbolAddress(&scr, g_scr);
  enc(f, &m_x, d_in[0], D_, S_, 1, D_, D_, 128 >> XSPLIT, 1);
  enc(f, &m_wkv, d_in[1], D_, D_, 3, 3 * D_, D_, 64, 2);
  enc(f, &m_wq, d_in[1], D_, D_, 3, 3 * D_, D_, 224, 1);
  enc(f, &m_w1, d_in[4], F_, S_, 1, F_, F_, 64, 1);
  enc(f, &m_w2, d_in[6], S_, F_, 1, S_, S_, 64, 1);
  enc(f, &m_res, d_in[0], D_, S_, 1, D_, D_, 64, 1, 112);
  Params p;
  p.wqkv = (const unsigned char*)d_in[1]; p.wo = (const unsigned char*)d_in[2];
  p.w1 = (const unsigned char*)d_in[4]; p.b1 = (const unsigned char*)d_in[5];
  p.w2 = (const unsigned char*)d_in[6]; p.b2 = (const unsigned char*)d_in[7];
  p.out = (unsigned char*)d_out; p.scr = (unsigned char*)scr;
  cudaFuncSetAttribute(fused_kernel, cudaFuncAttributeMaxDynamicSharedMemorySize, SMEM_BYTES);
  fused_kernel<<<128, NTHREADS, SMEM_BYTES, cudaStreamPerThread>>>(m_x, m_wkv, m_wq, m_w1, m_w2, m_res, p);
}
```

```cpp
#include <cuda_runtime.h>
#include <cuda.h>
#include <cuda_bf16.h>
#include <stdint.h>

template<int TA, int TB> __device__ __forceinline__ void wgmma_n112(float (&d)[56], uint64_t da, uint64_t db, int sc) {
  asm volatile("{\n.reg .pred p;\nsetp.ne.b32 p, %58, 0;\n"
    "wgmma.mma_async.sync.aligned.m64n112k16.f32.bf16.bf16 {%0, %1, %2, %3, %4, %5, %6, %7, %8, %9, %10, %11, %12, %13, %14, %15, %16, %17, %18, %19, %20, %21, %22, %23, %24, %25, %26, %27, %28, %29, %30, %31, %32, %33, %34, %35, %36, %37, %38, %39, %40, %41, %42, %43, %44, %45, %46, %47, %48, %49, %50, %51, %52, %53, %54, %55}, %56, %57, p, 1, 1, %59, %60;\n}\n"
    : "+f"(d[0]), "+f"(d[1]), "+f"(d[2]), "+f"(d[3]), "+f"(d[4]), "+f"(d[5]), "+f"(d[6]), "+f"(d[7]), "+f"(d[8]), "+f"(d[9]), "+f"(d[10]), "+f"(d[11]), "+f"(d[12]), "+f"(d[13]), "+f"(d[14]), "+f"(d[15]), "+f"(d[16]), "+f"(d[17]), "+f"(d[18]), "+f"(d[19]), "+f"(d[20]), "+f"(d[21]), "+f"(d[22]), "+f"(d[23]), "+f"(d[24]), "+f"(d[25]), "+f"(d[26]), "+f"(d[27]), "+f"(d[28]), "+f"(d[29]), "+f"(d[30]), "+f"(d[31]), "+f"(d[32]), "+f"(d[33]), "+f"(d[34]), "+f"(d[35]), "+f"(d[36]), "+f"(d[37]), "+f"(d[38]), "+f"(d[39]), "+f"(d[40]), "+f"(d[41]), "+f"(d[42]), "+f"(d[43]), "+f"(d[44]), "+f"(d[45]), "+f"(d[46]), "+f"(d[47]), "+f"(d[48]), "+f"(d[49]), "+f"(d[50]), "+f"(d[51]), "+f"(d[52]), "+f"(d[53]), "+f"(d[54]), "+f"(d[55])
    : "l"(da), "l"(db), "r"(sc), "n"(TA), "n"(TB));
}

template<int TA, int TB> __device__ __forceinline__ void wgmma_n80(float (&d)[40], uint64_t da, uint64_t db, int sc) {
  asm volatile("{\n.reg .pred p;\nsetp.ne.b32 p, %42, 0;\n"
    "wgmma.mma_async.sync.aligned.m64n80k16.f32.bf16.bf16 {%0, %1, %2, %3, %4, %5, %6, %7, %8, %9, %10, %11, %12, %13, %14, %15, %16, %17, %18, %19, %20, %21, %22, %23, %24, %25, %26, %27, %28, %29, %30, %31, %32, %33, %34, %35, %36, %37, %38, %39}, %40, %41, p, 1, 1, %43, %44;\n}\n"
    : "+f"(d[0]), "+f"(d[1]), "+f"(d[2]), "+f"(d[3]), "+f"(d[4]), "+f"(d[5]), "+f"(d[6]), "+f"(d[7]), "+f"(d[8]), "+f"(d[9]), "+f"(d[10]), "+f"(d[11]), "+f"(d[12]), "+f"(d[13]), "+f"(d[14]), "+f"(d[15]), "+f"(d[16]), "+f"(d[17]), "+f"(d[18]), "+f"(d[19]), "+f"(d[20]), "+f"(d[21]), "+f"(d[22]), "+f"(d[23]), "+f"(d[24]), "+f"(d[25]), "+f"(d[26]), "+f"(d[27]), "+f"(d[28]), "+f"(d[29]), "+f"(d[30]), "+f"(d[31]), "+f"(d[32]), "+f"(d[33]), "+f"(d[34]), "+f"(d[35]), "+f"(d[36]), "+f"(d[37]), "+f"(d[38]), "+f"(d[39])
    : "l"(da), "l"(db), "r"(sc), "n"(TA), "n"(TB));
}

template<int TB> __device__ __forceinline__ void wgmma_rs_n120(float (&d)[60], const uint32_t (&a)[4], uint64_t db, int sc) {
  asm volatile("{\n.reg .pred p;\nsetp.ne.b32 p, %65, 0;\n"
    "wgmma.mma_async.sync.aligned.m64n120k16.f32.bf16.bf16 {%0, %1, %2, %3, %4, %5, %6, %7, %8, %9, %10, %11, %12, %13, %14, %15, %16, %17, %18, %19, %20, %21, %22, %23, %24, %25, %26, %27, %28, %29, %30, %31, %32, %33, %34, %35, %36, %37, %38, %39, %40, %41, %42, %43, %44, %45, %46, %47, %48, %49, %50, %51, %52, %53, %54, %55, %56, %57, %58, %59}, {%60, %61, %62, %63}, %64, p, 1, 1, %66;\n}\n"
    : "+f"(d[0]), "+f"(d[1]), "+f"(d[2]), "+f"(d[3]), "+f"(d[4]), "+f"(d[5]), "+f"(d[6]), "+f"(d[7]), "+f"(d[8]), "+f"(d[9]), "+f"(d[10]), "+f"(d[11]), "+f"(d[12]), "+f"(d[13]), "+f"(d[14]), "+f"(d[15]), "+f"(d[16]), "+f"(d[17]), "+f"(d[18]), "+f"(d[19]), "+f"(d[20]), "+f"(d[21]), "+f"(d[22]), "+f"(d[23]), "+f"(d[24]), "+f"(d[25]), "+f"(d[26]), "+f"(d[27]), "+f"(d[28]), "+f"(d[29]), "+f"(d[30]), "+f"(d[31]), "+f"(d[32]), "+f"(d[33]), "+f"(d[34]), "+f"(d[35]), "+f"(d[36]), "+f"(d[37]), "+f"(d[38]), "+f"(d[39]), "+f"(d[40]), "+f"(d[41]), "+f"(d[42]), "+f"(d[43]), "+f"(d[44]), "+f"(d[45]), "+f"(d[46]), "+f"(d[47]), "+f"(d[48]), "+f"(d[49]), "+f"(d[50]), "+f"(d[51]), "+f"(d[52]), "+f"(d[53]), "+f"(d[54]), "+f"(d[55]), "+f"(d[56]), "+f"(d[57]), "+f"(d[58]), "+f"(d[59])
    : "r"(a[0]), "r"(a[1]), "r"(a[2]), "r"(a[3]), "l"(db), "r"(sc), "n"(TB));
}

template<int TB> __device__ __forceinline__ void wgmma_rs_n56(float (&d)[28], const uint32_t (&a)[4], uint64_t db, int sc) {
  asm volatile("{\n.reg .pred p;\nsetp.ne.b32 p, %33, 0;\n"
    "wgmma.mma_async.sync.aligned.m64n56k16.f32.bf16.bf16 {%0, %1, %2, %3, %4, %5, %6, %7, %8, %9, %10, %11, %12, %13, %14, %15, %16, %17, %18, %19, %20, %21, %22, %23, %24, %25, %26, %27}, {%28, %29, %30, %31}, %32, p, 1, 1, %34;\n}\n"
    : "+f"(d[0]), "+f"(d[1]), "+f"(d[2]), "+f"(d[3]), "+f"(d[4]), "+f"(d[5]), "+f"(d[6]), "+f"(d[7]), "+f"(d[8]), "+f"(d[9]), "+f"(d[10]), "+f"(d[11]), "+f"(d[12]), "+f"(d[13]), "+f"(d[14]), "+f"(d[15]), "+f"(d[16]), "+f"(d[17]), "+f"(d[18]), "+f"(d[19]), "+f"(d[20]), "+f"(d[21]), "+f"(d[22]), "+f"(d[23]), "+f"(d[24]), "+f"(d[25]), "+f"(d[26]), "+f"(d[27])
    : "r"(a[0]), "r"(a[1]), "r"(a[2]), "r"(a[3]), "l"(db), "r"(sc), "n"(TB));
}

template<int TB> __device__ __forceinline__ void wgmma_rs_n32(float (&d)[16], const uint32_t (&a)[4], uint64_t db, int sc) {
  asm volatile("{\n.reg .pred p;\nsetp.ne.b32 p, %21, 0;\n"
    "wgmma.mma_async.sync.aligned.m64n32k16.f32.bf16.bf16 {%0, %1, %2, %3, %4, %5, %6, %7, %8, %9, %10, %11, %12, %13, %14, %15}, {%16, %17, %18, %19}, %20, p, 1, 1, %22;\n}\n"
    : "+f"(d[0]), "+f"(d[1]), "+f"(d[2]), "+f"(d[3]), "+f"(d[4]), "+f"(d[5]), "+f"(d[6]), "+f"(d[7]), "+f"(d[8]), "+f"(d[9]), "+f"(d[10]), "+f"(d[11]), "+f"(d[12]), "+f"(d[13]), "+f"(d[14]), "+f"(d[15])
    : "r"(a[0]), "r"(a[1]), "r"(a[2]), "r"(a[3]), "l"(db), "r"(sc), "n"(TB));
}

template<int TB> __device__ __forceinline__ void wgmma_rs_n80(float (&d)[40], const uint32_t (&a)[4], uint64_t db, int sc) {
  asm volatile("{\n.reg .pred p;\nsetp.ne.b32 p, %45, 0;\n"
    "wgmma.mma_async.sync.aligned.m64n80k16.f32.bf16.bf16 {%0, %1, %2, %3, %4, %5, %6, %7, %8, %9, %10, %11, %12, %13, %14, %15, %16, %17, %18, %19, %20, %21, %22, %23, %24, %25, %26, %27, %28, %29, %30, %31, %32, %33, %34, %35, %36, %37, %38, %39}, {%40, %41, %42, %43}, %44, p, 1, 1, %46;\n}\n"
    : "+f"(d[0]), "+f"(d[1]), "+f"(d[2]), "+f"(d[3]), "+f"(d[4]), "+f"(d[5]), "+f"(d[6]), "+f"(d[7]), "+f"(d[8]), "+f"(d[9]), "+f"(d[10]), "+f"(d[11]), "+f"(d[12]), "+f"(d[13]), "+f"(d[14]), "+f"(d[15]), "+f"(d[16]), "+f"(d[17]), "+f"(d[18]), "+f"(d[19]), "+f"(d[20]), "+f"(d[21]), "+f"(d[22]), "+f"(d[23]), "+f"(d[24]), "+f"(d[25]), "+f"(d[26]), "+f"(d[27]), "+f"(d[28]), "+f"(d[29]), "+f"(d[30]), "+f"(d[31]), "+f"(d[32]), "+f"(d[33]), "+f"(d[34]), "+f"(d[35]), "+f"(d[36]), "+f"(d[37]), "+f"(d[38]), "+f"(d[39])
    : "r"(a[0]), "r"(a[1]), "r"(a[2]), "r"(a[3]), "l"(db), "r"(sc), "n"(TB));
}

namespace {
constexpr int S_ = 2048, D_ = 448, F_ = 1792;
constexpr int NSLOT = 8, SLOT = 22528;
constexpr int OFF_X = 7 * 16384;
constexpr int OFF_WQ = 8 * 16384;
constexpr int OFF_Q = NSLOT * SLOT;
constexpr int OFF_K = OFF_Q + 16384;
constexpr int OFF_XW = OFF_K + 6144;
constexpr int OFF_BAR = 14 * 16384;
constexpr int OFF_LN = OFF_BAR + 512;
constexpr int OFF_OBS = OFF_BAR + 640;
constexpr int SMEM_BYTES = OFF_OBS + 1024;
#define PACE0 0
#define PACE1 540
#define PACE2 650
#define WARM 3
#define NW0 2
#define HEAT 1
#define T0 0
#define TP 250
#define J3 0
#define J1 9
#define J2 14
#define EARLY 4
#define PPE 4
#define PQE 2
#define LANDOBS 0
#define TRUNC 0
#define KOBS 0
#define PRE 1
#define QA 2
#define HEARLY 0
#define OSLEEP 20
#define PROBE 1
#define WOP 0
#define OGRP 2
#define OMODE 3
#define GCH 4
#define GLAG 2
#define GSLOW 0
#define RH 32
#define NOST 0
#define GOBS 0
#define HP 0
#define OPP 0
#define STAG 0
#define RESP 0
#define XE 1
#define NX 0
#define XS 15
#define XT 9
#define NPRE 1
#define U0 0
#define ALL4 0
#define UREP 1
#define TS 0
#define PPM 1
#define WPF 0
#define XSPLIT 1
#define XK 1
#define TAG 1
#define HWAIT 300
#define RB 31
#define UO 1
#define FSM 1
#define XP 0
#define MU 0
#define P2 224
#define UP 170
#define POLL "relaxed"
#define OPJ 16
#define SEARLY 1
#define EXACT 0
#define SOBS 0
#define FREQ 0
#define OBS(c, i) do {} while (0)
#define OBSG(c, i, j) do {} while (0)
constexpr int NTHREADS = 384;
constexpr float SCALE = 0.18898223650461361f, LOG2E = 1.4426950408889634f;
constexpr uint32_t SC_HI = 0x3e423e42u, SC_LO = 0xb9f7b9f7u;
constexpr int BT = 14336;

constexpr int HU_T = 67;
constexpr int O_OFF = 4 * HU_T * BT;
constexpr int HALO_OFF = O_OFF + 32 * 7 * 8192;
constexpr int CNT_OFF = HALO_OFF + 128 * 3584;
constexpr int SCR_BYTES = CNT_OFF + 193 * 128;
constexpr int C_WO = 0, C_TK = 1, C_U = 160, C_O = 8, C_H = 24, C_HALO = 32, C_EPOCH = 192;
__device__ __align__(1024) unsigned char g_scr[SCR_BYTES];

__device__ __forceinline__ uint32_t smem_u32(const void* p) { return (uint32_t)__cvta_generic_to_shared(p); }
__device__ __forceinline__ void mbar_init(uint32_t bar, uint32_t cnt) { asm volatile("mbarrier.init.shared::cta.b64 [%0], %1;" :: "r"(bar), "r"(cnt)); }
__device__ __forceinline__ void mbar_expect_tx(uint32_t bar, uint32_t bytes) { asm volatile("mbarrier.arrive.expect_tx.shared::cta.b64 _, [%0], %1;" :: "r"(bar), "r"(bytes) : "memory"); }
__device__ __forceinline__ void mbar_arrive_if(uint32_t c, uint32_t bar) { asm volatile("{\n.reg .pred q;\nsetp.ne.u32 q, %1, 0;\n@q mbarrier.arrive.shared::cta.b64 _, [%0];\n}" :: "r"(bar), "r"(c) : "memory"); }
__device__ __forceinline__ void mbar_arrive(uint32_t bar) { asm volatile("mbarrier.arrive.shared::cta.b64 _, [%0];" :: "r"(bar) : "memory"); }
__device__ __forceinline__ void mbar_wait(uint32_t bar, uint32_t parity) {
  asm volatile("{\n.reg .pred p;\n.reg .u32 n;\nmov.u32 n, 0;\nLAB_WAIT:\n"
               "mbarrier.try_wait.parity.shared::cta.b64 p, [%0], %1;\n@p bra DONE;\n"
               "add.u32 n, n, 1;\nsetp.lt.u32 p, n, 400000;\n@p bra LAB_WAIT;\ntrap;\nDONE:\n}" :: "r"(bar), "r"(parity) : "memory");
}
__device__ __forceinline__ uint32_t mbar_try(uint32_t bar, uint32_t parity) {
  uint32_t ok;
  asm volatile("{\n.reg .pred p;\nmbarrier.test_wait.parity.shared::cta.b64 p, [%1], %2;\nselp.u32 %0, 1, 0, p;\n}" : "=r"(ok) : "r"(bar), "r"(parity) : "memory");
  return ok;
}
__device__ __forceinline__ void tma3d(uint32_t dst, const CUtensorMap* m, int c0, int c1, int c2, uint32_t bar) {
  asm volatile("cp.async.bulk.tensor.3d.shared::cluster.global.mbarrier::complete_tx::bytes [%0], [%1, {%3, %4, %5}], [%2];"
               :: "r"(dst), "l"(m), "r"(bar), "r"(c0), "r"(c1), "r"(c2) : "memory");
}
__device__ __forceinline__ void bulk_g2s(uint32_t dst, const void* src, uint32_t bytes, uint32_t bar) {
  asm volatile("cp.async.bulk.shared::cluster.global.mbarrier::complete_tx::bytes [%0], [%1], %2, [%3];" :: "r"(dst), "l"(src), "r"(bytes), "r"(bar) : "memory");
}
__device__ __forceinline__ void wg_fence() { asm volatile("wgmma.fence.sync.aligned;" ::: "memory"); }
__device__ __forceinline__ void wg_commit() { asm volatile("wgmma.commit_group.sync.aligned;" ::: "memory"); }
template <int N> __device__ __forceinline__ void wg_wait() { asm volatile("wgmma.wait_group.sync.aligned %0;" :: "n"(N) : "memory"); }
__device__ __forceinline__ void smem_fence() { asm volatile("fence.proxy.async.shared::cta;" ::: "memory"); }
__device__ __forceinline__ void stg128(void* p, uint32_t a, uint32_t b, uint32_t c, uint32_t d) { asm volatile("st.global.v4.u32 [%0], {%1,%2,%3,%4};" :: "l"(p), "r"(a), "r"(b), "r"(c), "r"(d) : "memory"); }
__device__ __forceinline__ void stg32(void* p, uint32_t v) { asm volatile("st.global.u32 [%0], %1;" :: "l"(p), "r"(v) : "memory"); }
__device__ __forceinline__ uint4 ldg128(const void* p) { uint4 v; asm volatile("ld.global.nc.L1::no_allocate.v4.u32 {%0,%1,%2,%3}, [%4];" : "=r"(v.x), "=r"(v.y), "=r"(v.z), "=r"(v.w) : "l"(p)); return v; }
__device__ __forceinline__ void publish(unsigned char* scr, int i) {
  asm volatile("{\n.reg .pred q;\nelect.sync _|q, 0xffffffff;\n@q red.relaxed.gpu.global.inc.u32 [%0], 0xffffffff;\n}" :: "l"(scr + CNT_OFF + i * 128) : "memory");
}
__device__ __forceinline__ uint32_t probe(const unsigned char* p) { uint32_t v; asm volatile("ld.relaxed.gpu.global.u32 %0, [%1];" : "=r"(v) : "l"(p) : "memory"); return v; }
__device__ __forceinline__ void settle(uint32_t v) {
  asm volatile("{\n.reg .pred q;\nsetp.eq.u32 q, %0, 0x7fc1dead;\n@q st.volatile.shared.u32 [%1], %0;\n}" :: "r"(v), "r"(1024 + OFF_BAR + 376) : "memory");
  __syncwarp();
}
__device__ __forceinline__ void spin_ge(unsigned char* scr, int i, unsigned target) {
  asm volatile("{\n.reg .pred p;\n.reg .u32 n, v;\nmov.u32 n, 0;\nLAB_SPIN:\n"
               "ld." POLL ".gpu.global.u32 v, [%0];\nsetp.ge.u32 p, v, %1;\nvote.sync.all.pred p, p, 0xffffffff;\n@p bra DONE;\n"
               "add.u32 n, n, 1;\nsetp.lt.u32 p, n, 4000000;\n@p bra LAB_SPIN;\ntrap;\nDONE:\n}" :: "l"(scr + CNT_OFF + i * 128), "r"(target) : "memory");
}
__device__ __forceinline__ int lane_id() { int l; asm volatile("mov.u32 %0, %%laneid;" : "=r"(l)); return l; }
__device__ __forceinline__ uint32_t pin(uint32_t v) { return __shfl_xor_sync(0xffffffffu, v, blockIdx.y); }
__device__ __forceinline__ unsigned char* pin(unsigned char* p) { return (unsigned char*)(((uint64_t)pin((uint32_t)((uint64_t)p >> 32)) << 32) | pin((uint32_t)(uint64_t)p)); }
__device__ __forceinline__ bool elect() {
  uint32_t r; asm volatile("{\n.reg .pred p;\nelect.sync _|p, 0xffffffff;\nselp.u32 %0, 1, 0, p;\n}" : "=r"(r)); return r != 0;
}
__device__ __forceinline__ uint4 lds128(uint32_t a) { uint4 v; asm volatile("ld.shared.v4.u32 {%0,%1,%2,%3}, [%4];" : "=r"(v.x), "=r"(v.y), "=r"(v.z), "=r"(v.w) : "r"(a) : "memory"); return v; }
__device__ __forceinline__ uint2 lds64(uint32_t a) { uint2 v; asm volatile("ld.shared.v2.u32 {%0,%1}, [%2];" : "=r"(v.x), "=r"(v.y) : "r"(a) : "memory"); return v; }
__device__ __forceinline__ void sts128(uint32_t p, uint32_t a, uint32_t b, uint32_t c, uint32_t d) { asm volatile("st.shared.v4.u32 [%0], {%1,%2,%3,%4};" :: "r"(p), "r"(a), "r"(b), "r"(c), "r"(d) : "memory"); }
__device__ __forceinline__ void sts32(uint32_t a, float v) { asm volatile("st.shared.f32 [%0], %1;" :: "r"(a), "f"(v) : "memory"); }
__device__ __forceinline__ void named_sync(int id, int n) { asm volatile("bar.sync %0, %1;" :: "r"(id), "r"(n) : "memory"); }
__device__ __forceinline__ void named_arrive(int id, int n) { asm volatile("bar.arrive %0, %1;" :: "r"(id), "r"(n) : "memory"); }
__device__ __forceinline__ void named_arrive_if(uint32_t c, int id, int n) { asm volatile("{\n.reg .pred q;\nsetp.ne.u32 q, %2, 0;\n@q bar.arrive %0, %1;\n}" :: "r"(id), "r"(n), "r"(c) : "memory"); }
__device__ __forceinline__ uint64_t mkdesc(uint32_t hi, uint32_t lo) { return ((uint64_t)hi << 32) | lo; }
constexpr uint32_t HI_SW128 = 0x40000040u;
__device__ __forceinline__ uint32_t pack2(float lo, float hi) { uint32_t r; asm("cvt.rn.bf16x2.f32 %0, %1, %2;" : "=r"(r) : "f"(hi), "f"(lo)); return r; }
__device__ __forceinline__ float bf_lo(uint32_t v) { return __uint_as_float(v << 16); }
__device__ __forceinline__ float bf_hi(uint32_t v) { return __uint_as_float(v & 0xffff0000u); }
__device__ __forceinline__ float rbf(float x) { return bf_lo(pack2(x, 0.f)); }
__device__ __forceinline__ uint32_t hsub2(uint32_t a, uint32_t b) { uint32_t r; asm("sub.rn.bf16x2 %0, %1, %2;" : "=r"(r) : "r"(a), "r"(b)); return r; }
__device__ __forceinline__ uint32_t hadd2(uint32_t a, uint32_t b) { uint32_t r; asm("add.rn.bf16x2 %0, %1, %2;" : "=r"(r) : "r"(a), "r"(b)); return r; }
__device__ __forceinline__ uint32_t place(uint32_t v, uint32_t sel) { uint32_t r; asm volatile("prmt.b32 %0, %1, 0, %2;" : "=r"(r) : "r"(v), "r"(sel)); return r; }
__device__ __forceinline__ uint32_t hmax2(uint32_t a, uint32_t b) { uint32_t r; asm("max.bf16x2 %0, %1, %2;" : "=r"(r) : "r"(a), "r"(b)); return r; }
__device__ __forceinline__ uint32_t hmul2(uint32_t a, uint32_t b) { uint32_t r; asm("mul.rn.bf16x2 %0, %1, %2;" : "=r"(r) : "r"(a), "r"(b)); return r; }
__device__ __forceinline__ uint32_t hfma2(uint32_t a, uint32_t b, uint32_t c) { uint32_t r; asm("fma.rn.bf16x2 %0, %1, %2, %3;" : "=r"(r) : "r"(a), "r"(b), "r"(c)); return r; }
__device__ __forceinline__ float tanh_fast(float x) { float r; asm("tanh.approx.f32 %0, %1;" : "=f"(r) : "f"(x)); return r; }
__device__ __forceinline__ float rcp_fast(float x) { float r; asm("rcp.approx.ftz.f32 %0, %1;" : "=f"(r) : "f"(x)); return r; }
__device__ __forceinline__ float ex2_fast(float x) { float r; asm("ex2.approx.ftz.f32 %0, %1;" : "=f"(r) : "f"(x)); return r; }
__device__ __forceinline__ void mma16816(float (&c)[4], uint32_t a0, uint32_t a1, uint32_t a2, uint32_t a3, uint32_t b0, uint32_t b1) {
  asm volatile("mma.sync.aligned.m16n8k16.row.col.f32.bf16.bf16.f32 {%0,%1,%2,%3}, {%4,%5,%6,%7}, {%8,%9}, {%0,%1,%2,%3};"
               : "+f"(c[0]), "+f"(c[1]), "+f"(c[2]), "+f"(c[3]) : "r"(a0), "r"(a1), "r"(a2), "r"(a3), "r"(b0), "r"(b1));
}
__device__ __forceinline__ void ldsm4(uint32_t (&r)[4], uint32_t addr) {
  asm volatile("ldmatrix.sync.aligned.m8n8.x4.shared.b16 {%0,%1,%2,%3}, [%4];" : "=r"(r[0]), "=r"(r[1]), "=r"(r[2]), "=r"(r[3]) : "r"(addr) : "memory");
}
__device__ __forceinline__ void stsm4(uint32_t addr, uint32_t a, uint32_t b, uint32_t c, uint32_t d) {
  asm volatile("stmatrix.sync.aligned.m8n8.x4.shared.b16 [%0], {%1,%2,%3,%4};" :: "r"(addr), "r"(a), "r"(b), "r"(c), "r"(d) : "memory");
}

__device__ __forceinline__ float ln_rstd(float var, float eps = 1e-5f) {
  float sd;
  asm("sqrt.approx.ftz.f32 %0, %1;" : "=f"(sd) : "f"(rbf(rbf(var) + eps)));
  return rcp_fast(rbf(sd));
}
__device__ __forceinline__ float ln_var(float mean, float sq) { return fmaxf(fmaf(-mean, mean, sq * (1.0f / D_)), 0.f); }
struct LnC { uint32_t m, rh, rl; };
__device__ __forceinline__ LnC ln_consts(float sum, float sq, float eps) {
  const float mean = sum * (1.0f / D_), r = ln_rstd(ln_var(mean, sq), eps), rh = rbf(r);
  LnC c; c.m = pack2(mean, mean); c.rh = pack2(rh, rh); c.rl = pack2(r - rh, r - rh);
  return c;
}
__device__ __forceinline__ uint32_t ln_apply(uint32_t x, const LnC& c) {
  uint32_t d = hsub2(x, c.m);
  return hfma2(d, c.rh, hmul2(d, c.rl));
}

__device__ __forceinline__ void fence_code(int id) {
  asm volatile("{\n.reg .pred q;\nLAB_F:\nsetp.eq.u32 q, %0, %1;\n@q st.volatile.shared.u32 [%2], %2;\n@q bra LAB_F;\n}" :: "r"(blockIdx.x), "r"(0x70000000 + id), "r"(0) : "memory");
}
template <int N> __device__ __forceinline__ void fresh(float (&a)[N]) {
#pragma unroll
  for (int i = 0; i < N; i++) asm volatile("" : "=f"(a[i]));
}
constexpr int B_EMPTY = 64, B_X = 384, B_KV = 192, B_WQ = 248, B_HALO = 256, B_RES = 264, B_ATT = 272, B_GATE = 280, B_WO = 304, B_O = 312, B_XW = 320, B_WQ2 = 328, B_T0 = 336, B_TAG = 344;

template <int TA>
__device__ __forceinline__ void gemm_issue(float (&acc)[56], uint32_t la, uint32_t lo, int sc) {
  wg_fence();
#pragma unroll
  for (int k = 0; k < 4; k++)
    wgmma_n112<TA, 1>(acc, mkdesc(TA ? HI_SW128 : 8, la + (TA ? 512u << 16 : 64u << 16) + k * 128), mkdesc(8, lo + (112u << 16) + 512 + k * 224), sc | k);
  wg_commit();
}
template <int TA>
__device__ __forceinline__ void gemm_stage(float (&acc)[56], uint32_t base, int it, int sc) {
  mbar_wait(base + OFF_BAR + (it & 7) * 8, (it >> 3) & 1);
  const uint32_t lo = (base >> 4) + (it & 7) * (SLOT >> 4);
  gemm_issue<TA>(acc, lo, lo, sc);
}
template <int TA, int EXTRA = 0>
__device__ __forceinline__ void gemm_loop(float (&acc)[56], uint32_t base, int it, int end, bool rel, int oi, uint32_t ok = 0, int gate_it = -1, uint32_t gate = 0) {
#pragma unroll 1
  for (; it < end;) {
    if (__builtin_expect(!ok, 0)) mbar_wait(base + OFF_BAR + (it & 7) * 8, (it >> 3) & 1);
    const uint32_t lo = (base >> 4) + (it & 7) * (SLOT >> 4);
    gemm_issue<TA>(acc, (unsigned)(it - XS) < EXTRA ? ((base + OFF_XW) >> 4) + (it - XS) * 512 : lo, lo, 1);
    OBS(SOBS && rel, oi + it);
    it++;
    ok = mbar_try(base + OFF_BAR + (it & 7) * 8, (it >> 3) & 1);
    wg_wait<1>();
    if (rel || it == gate_it) mbar_arrive(rel ? base + OFF_BAR + B_EMPTY + ((it - 2) & 7) * 8 : gate);
  }
}
template <int PER>
__device__ __forceinline__ void produce_box(uint32_t base, int it, int end, const CUtensorMap* mp, int c0, int c1, uint32_t tn = 0) {
#pragma unroll 1
  for (; it < end; it++) {
    const uint32_t fb = base + OFF_BAR + (it & 7) * 8;
    mbar_wait(fb + B_EMPTY, (it >> 3) & 1);
    if (PER) { while ((int)(clock() - tn) < 0); tn += PER; }
    if (elect()) { mbar_expect_tx(fb, 8192); tma3d(base + (it & 7) * SLOT, mp, c0, c1, 0, fb); }
    c1 += 64;
  }
}
template <int PER>
__device__ __forceinline__ void produce_lin(uint32_t base, int it, int end, const unsigned char* src, uint32_t bytes, uint32_t tn = 0) {
#pragma unroll 1
  for (; it < end; it++) {
    const uint32_t fb = base + OFF_BAR + (it & 7) * 8;
    mbar_wait(fb + B_EMPTY, (it >> 3) & 1);
    if (PER) { while ((int)(clock() - tn) < 0); tn += PER; }
    if (elect()) { mbar_expect_tx(fb, bytes); bulk_g2s(base + (it & 7) * SLOT + (bytes & 2048) * 4, src, bytes, fb); }
    src += bytes;
  }
}

__device__ __forceinline__ void retile_wo(const unsigned char* wo, unsigned char* scr, int u, int lane) {
  const int r8 = lane & 7, mi = lane >> 3;
  const unsigned char* src = wo + ((u >> 1) * 8 + r8) * 896 + ((u & 1) * 28 + mi) * 16;
  unsigned char* dst = scr + ((u & 1) * 2 * HU_T + 60 + (u >> 4)) * BT + ((u >> 1) & 7) * 1792 + mi * 128 + r8 * 16;
  uint4 v[7];
#pragma unroll
  for (int i = 0; i < 7; i++) v[i] = ldg128(src + i * 64);
#pragma unroll
  for (int i = 0; i < 7; i++) stg128(dst + i * 512 + ((i * 4 + mi) / 14) * (HU_T * BT - 1792), v[i].x, v[i].y, v[i].z, v[i].w);
  if (!(RB & 1)) publish(scr, C_WO);
}

struct Params {
  const unsigned char *wqkv, *wo, *w1, *b1, *w2, *b2;
  unsigned char *out, *scr;
};

__global__ void __launch_bounds__(NTHREADS, 1)
fused_kernel(const __grid_constant__ CUtensorMap m_x, const __grid_constant__ CUtensorMap m_wkv, const __grid_constant__ CUtensorMap m_wq,
             const __grid_constant__ CUtensorMap m_w1, const __grid_constant__ CUtensorMap m_w2, const __grid_constant__ CUtensorMap m_res, const Params p) {
  extern __shared__ __align__(1024) unsigned char smem_raw[];
  constexpr uint32_t base = 1024, bars = base + OFF_BAR;
  const int tid = threadIdx.x, lane = tid & 31, b = blockIdx.x;
  const int rb = (b >> 2) & 15, hp = ((b >> 6) << 2) | (b & 3);
  const int wcol = hp * 56 - (hp & 1) * 8;
  auto load_kv = [&](int s) { mbar_expect_tx(bars + B_KV + s * 8, 16384); tma3d(base + s * 16384, &m_wkv, wcol, s * 64, 1, bars + B_KV + s * 8); };
  if (tid < 32) {
    if (elect()) {
#pragma unroll
      for (int i = 0; i < 7; i++) mbar_init(bars + B_X + i * 8, 1);
      asm volatile("fence.mbarrier_init.release.cluster;" ::: "memory");
#pragma unroll
      for (int i = 0; i < 7; i++) { mbar_expect_tx(bars + B_X + i * 8, 16384 >> XSPLIT); tma3d(base + OFF_X + i * 16384 + XSPLIT * 8192, &m_x, i * 64, rb * 128 + XSPLIT * 64, 0, bars + B_X + i * 8); }
#pragma unroll
      for (int i = 0; i < 7; i++) { mbar_init(bars + B_KV + i * 8, 1); if (XSPLIT) mbar_init(bars + B_X + 64 + i * 8, 1); }
      asm volatile("fence.mbarrier_init.release.cluster;" ::: "memory");
      if (XSPLIT) {
#pragma unroll
        for (int i = 0; i < XK; i++) load_kv(i);
#pragma unroll
        for (int i = 0; i < 7; i++) { mbar_expect_tx(bars + B_X + 64 + i * 8, 8192); tma3d(base + OFF_X + i * 16384, &m_x, i * 64, rb * 128, 0, bars + B_X + 64 + i * 8); }
      }
#pragma unroll 1
      for (int i = XSPLIT * XK; i < NW0; i++) load_kv(i);
    }
  }
  const int warp = __shfl_sync(0xffffffffu, tid >> 5, 0);
  if (TS && tid == 64) sts32(bars + B_T0, __uint_as_float(clock() + TS));
  if (warp == 1) {
    if (elect()) {
#pragma unroll
      for (int i = 0; i < 16; i++) mbar_init(bars + i * 8, 2);
#pragma unroll
      for (int i = 0; i < 11; i++) mbar_init(bars + B_WQ + i * 8, 1);
      asm volatile("fence.mbarrier_init.release.cluster;" ::: "memory");
      if (smem_u32(smem_raw) != base) asm volatile("trap;");
    }
  }
  const int dt = b & 3, mt = b >> 2;
  const bool g1 = (b & 15) < 14;
  const int a1 = b - 2 * (b >> 4), ft = a1 >> 2, d1 = a1 & 3;
  const int g = lane >> 2, t = lane & 3, r8 = lane & 7, mi = lane >> 3;
  OBSG(FREQ && tid == 160, 128, 160);
  __syncthreads();
  if (warp >= 8) {
    asm volatile("setmaxnreg.dec.sync.aligned.u32 40;");
    const int pw = warp - 8;
    unsigned char* scr = p.scr;
    if (WPF && pw == 2) {
      mbar_wait(bars + B_X + (WPF - 1) * 8, 0);
      if (b < 112 && lane < 28) asm volatile("prefetch.global.L2 [%0];" :: "l"(p.wqkv + (b * 4 + lane / 7) * 2688 + (lane % 7) * 128) : "memory");
      if (lane == 31) asm volatile("prefetch.tensormap [%0];" :: "l"(&m_wq) : "memory");
      __syncwarp();
    }
    if (NW0 < 7 && pw == 3) {
      mbar_wait(bars + B_X, 0);
      if (elect()) {
#pragma unroll 1
        for (int i = NW0; i < 7; i++) load_kv(i);
      }
      __syncwarp();
    }
    {
      const int c0 = pw * 14 + (mi >> 1);
      unsigned char* dst = scr + (pw * HU_T + rb * 2 + (hp >> 2)) * BT + ((hp & 3) * 2 + (mi & 1)) * 1792 + (mi >> 1) * 128 + r8 * 16;
      const uint32_t xs = base + OFF_X + (hp * 16 + (lane & 15)) * 128;
      uint4 H[7];
      named_sync(9, 160);
#pragma unroll
      for (int i = 0; i < 7; i++) H[i] = lds128(xs + ((c0 + 2 * i) >> 3) * 16384 + ((((c0 + 2 * i) & 7) ^ r8) << 4));
      asm volatile("" :: "r"(H[6].w), "r"(H[0].x) : "memory");
      if (pw != 3) named_arrive(8, 384);
      else {
        named_sync(8, 384);
        if (elect()) {
          mbar_expect_tx(bars + B_WQ, 28672); tma3d(base + OFF_WQ, &m_wq, wcol, 0, 0, bars + B_WQ);
          mbar_expect_tx(bars + B_WQ2, 28672); tma3d(base + OFF_WQ + 28672, &m_wq, wcol, 224, 0, bars + B_WQ2);
        }
        __syncwarp();
      }
      const uint2 st = lds64(base + OFF_LN + (lane & 15) * 8);
      const float sum = __uint_as_float(st.x), mean = sum * (1.0f / D_), var = ln_var(mean, __uint_as_float(st.y));
      const float m = rbf(mean), r = ln_rstd(var), r2 = ln_rstd(var * r * r);
      const float nc = fmaf(m, (float)D_, -sum) * (1.0f / D_) * (r * r2);
      const uint32_t m2 = pack2(m, m), r2x = pack2(r * r2, r * r2), nc2 = pack2(nc, nc);
      auto f = [&](uint32_t v) { return hfma2(hsub2(v, m2), r2x, nc2); };
#pragma unroll
      for (int i = 0; i < 7; i++) stg128(dst + i * 256, f(H[i].x), f(H[i].y), f(H[i].z), f(H[i].w));
      if (pw != 1) named_arrive(4, 128);
    }
    const int lane = lane_id();
    if (pw == 0) {
      if (elect()) {
        asm volatile("prefetch.tensormap [%0];" :: "l"(&m_w1) : "memory");
        asm volatile("prefetch.tensormap [%0];" :: "l"(&m_w2) : "memory");
        asm volatile("prefetch.tensormap [%0];" :: "l"(&m_res) : "memory");
      }
      __syncwarp();
      const uint32_t e = probe(scr + CNT_OFF + C_EPOCH * 128) + 1;
      sts32(bars + B_TAG, __uint_as_float((e & 0x3fffu) | ((e << 2) & 0x3fff0000u)));
      named_arrive(1, 96);
      if (g1) produce_box<0>(base, 0, 32, &m_w1, ft * 64, 0);
      auto load_res = [&]() { if (elect()) { mbar_expect_tx(bars + B_RES, BT); tma3d(base + OFF_Q, &m_res, dt * 112, mt * 64, 0, bars + B_RES); } };
      if (RESP == 0) { mbar_wait(bars + B_ATT, 0); load_res(); }
      mbar_wait(bars + B_WO, 0);
      produce_lin<0>(base, 0, 7, scr + (dt * HU_T + 60) * BT, BT);
      if (NX) {
        produce_box<0>(base, 7, XT, &m_w2, mt * 64, 0);
        if (elect()) {
          mbar_expect_tx(bars + B_XW, NX * 8192);
#pragma unroll 1
          for (int i = 0; i < NX; i++) tma3d(base + OFF_XW + i * 8192, &m_w2, mt * 64, (XS - 7 + i) * 64, 0, bars + B_XW);
        }
        __syncwarp();
        produce_box<0>(base, XT, XS, &m_w2, mt * 64, (XT - 7) * 64);
        mbar_wait(bars + B_XW, 0);
#pragma unroll 1
        for (int it = XS; it < XS + NX; it++) { mbar_wait(bars + B_EMPTY + (it & 7) * 8, (it >> 3) & 1); if (lane == 0) mbar_arrive(bars + (it & 7) * 8); }
        __syncwarp();
        produce_box<0>(base, XS + NX, 35, &m_w2, mt * 64, (XS + NX - 7) * 64);
      } else produce_box<0>(base, 7, 35, &m_w2, mt * 64, 0);
      if (RESP) load_res();
    } else if (pw == 1) {
      named_sync(4, 128);
      const unsigned char* hl = scr + (rb * 2 + (hp >> 2)) * BT + (hp & 3) * 3584 + min(lane, 27) * 128;
      if (RB & 2) settle(probe(hl) ^ probe(hl + HU_T * BT) ^ probe(hl + 2 * HU_T * BT) ^ probe(hl + 3 * HU_T * BT));
      publish(scr, C_H + (b & 3));
      OBS(lane == 0, 4);
      if (g1) {
        spin_ge(scr, C_H + (lane & 3), 32);
        OBS(lane == 0, 16);
        if (HP) { produce_lin<HP>(base, 0, 8, scr + d1 * HU_T * BT, BT, clock()); produce_lin<0>(base, 8, 32, scr + (d1 * HU_T + 8) * BT, BT); }
        else produce_lin<0>(base, 0, 32, scr + d1 * HU_T * BT, BT);
      }
      mbar_wait(bars + B_O, 0);
      produce_lin<OPP>(base, 0, 7, scr + O_OFF + mt * 57344, 8192, clock());
      const unsigned char* us = scr + (dt * HU_T + 32) * BT;
#pragma unroll
      for (int i = 0; i < NPRE; i++) {
        mbar_wait(bars + B_EMPTY + ((7 + i) & 7) * 8, i > 0);
        if (elect()) mbar_expect_tx(bars + ((7 + i) & 7) * 8, BT);
        __syncwarp();
      }
      spin_ge(scr, C_U + (ALL4 ? lane & 3 : dt) + (mt & (UREP - 1)) * 4, 28);
      if (elect()) {
#pragma unroll
        for (int i = 0; i < NPRE; i++) bulk_g2s(base + ((7 + i) & 7) * SLOT + 8192, us + i * BT, BT, bars + ((7 + i) & 7) * 8);
      }
      const uint32_t tu = clock();
      OBS(lane == 0, 18);
      produce_lin<UP>(base, 7 + NPRE, 15, us + NPRE * BT, BT, tu + NPRE * UP - U0);
      produce_lin<0>(base, 15, 35, us + 8 * BT, BT);
      unsigned tk = 0;
      if (lane == 0) tk = atomicAdd((unsigned*)(scr + CNT_OFF + C_TK * 128), 1u);
      if (__shfl_sync(0xffffffffu, tk, 0) == 127) {
#pragma unroll 1
        for (int i = lane; i < 192; i += 32) *(unsigned*)(scr + CNT_OFF + i * 128) = 0;
        publish(scr, C_EPOCH);
      }
    } else if (pw == 2) {
      uint32_t tn = clock() + PACE0 + b * STAG;
      const unsigned char* src = p.w1 + b * 4096 + lane * 128;
#pragma unroll 1
      for (int i = 0; i < 28 + FREQ * 2; i++) {
        while ((int)(clock() - tn) < 0) __nanosleep(20);
        if (i == 14) src = p.w2 + b * 4096 + lane * 128;
        if (i < 28) asm volatile("prefetch.global.L2 [%0];" :: "l"(src) : "memory");
        OBSG(FREQ && lane == 0, 129 + i, 161 + i);
        src += 128 * 4096;
        tn += i < 14 ? PACE1 : PACE2;
      }
    } else {
      if (b < 112) retile_wo(p.wo, scr, b, lane_id());
      const int lane = lane_id();
      unsigned char* hg = scr + HALO_OFF + (rb * 8 + hp) * 3584;
      named_sync(1, 96);
      const uint32_t tag = lds64(bars + B_TAG).x;
      if (rb < 15) {
#pragma unroll
        for (int q = 0; q < 7; q += 4) {
          uint4 v[4];
#pragma unroll
          for (int i = q; i < q + 4 && i < 7; i++) v[i - q] = lds128(base + OFF_K + 8 * 3584 + i * 512 + lane * 16 + (i * 32 + lane < 112 && !(lane & 7) ? 1792 : 0));
#pragma unroll
          for (int i = q; i < q + 4 && i < 7; i++) stg128(hg + i * 512 + lane * 16, (lane & 7) == (i * 32 + lane < 112) ? tag : v[i - q].x, v[i - q].y, v[i - q].z, v[i - q].w);
        }
      }
      if (TAG == 1 && rb < 15) publish(scr, C_HALO + rb * 8 + hp);
      OBS(lane == 0, 29);
      if (rb > 0) {
        if (TAG == 1) spin_ge(scr, C_HALO + (rb - 1) * 8 + hp, 1); else __nanosleep(HWAIT);
        const uint32_t la = base + OFF_K + min(lane, 27) * 128;
#pragma unroll 1
        for (int n = 0;; n++) {
          if (elect()) { mbar_expect_tx(bars + B_XW, 3584); bulk_g2s(base + OFF_K, hg - 8 * 3584, 3584, bars + B_XW); }
          __syncwarp();
          mbar_wait(bars + B_XW, n & 1);
          if ((XP & 2) || __all_sync(0xffffffffu, lds64(la + (lane < 14 ? 16 : 0)).x == tag)) break;
          if (n > 1000000) asm volatile("trap;");
        }
        if (!(XP & 2) && lane < 14) { const uint4 v = lds128(la); sts128(la + 1792, v.x, v.y, v.z, v.w); }
      } else {
#pragma unroll
        for (int i = 0; i < 7; i++) sts128(base + OFF_K + i * 512 + lane * 16, 0, 0, 0, 0);
      }
      OBS(lane == 0, 12);
      if (!(XP & 1) || rb == 0) smem_fence();
      __syncwarp();
      if (lane == 0) mbar_arrive(bars + B_HALO);
      __syncwarp();
      if ((RB & 1) && b < 112) {
        settle(probe(scr + (((b & 1) * 2 + (lane >> 4)) * HU_T + 60 + (b >> 4)) * BT + ((b >> 1) & 7) * 1792 + min(lane & 15, 13) * 128));
        publish(scr, C_WO);
      }
      if (RB & 1) mbar_wait(bars + (g1 ? B_GATE + 8 : B_ATT), 0);
      spin_ge(scr, C_WO, 112);
      if (lane == 0) mbar_arrive(bars + B_WO);
      mbar_wait(bars + B_ATT, 0);
      spin_ge(scr, C_O + (mt >> 1), 8);
      OBS(lane == 0, 17);
      if (lane == 0) mbar_arrive(bars + B_O);
    }
  } else {
    asm volatile("setmaxnreg.inc.sync.aligned.u32 232;");
    const int wg = warp >> 2, w4 = warp & 3, th = wg ^ 1;
    const bool rel = (tid & 127) < 2;
    unsigned char* scr = p.scr;
    uint32_t X[28][4];
    float aq[28];
    const uint32_t dlo = (base >> 4) + (512u << 16) + (hp & 1), dlq = dlo + (OFF_WQ >> 4);
    {
      uint32_t xa[4];
#pragma unroll
      for (int k = 0; k < 4; k++) xa[k] = base + OFF_X + (th * 64 + w4 * 16 + (mi >> 1) * 8 + r8) * 128 + (((2 * k + (mi & 1)) ^ r8) << 4);
      float c0[2][4] = {}, c1[2][4] = {};
      uint32_t one[8];
#pragma unroll
      for (int j = 0; j < 8; j++) asm volatile("{\n.reg .u32 y;\nmov.u32 y, %%tid.y;\nmad.lo.u32 %0, y, %1, 0x3f803f80;\n}" : "=r"(one[j]) : "r"(lane + j));
      asm volatile("" : "+l"(scr));
      uint32_t ok = 0;
      const uint32_t bx = bars + B_X + XSPLIT * wg * 64;
      if (HEAT) {
#pragma unroll 1
        for (int n = 0; n < 64 && !ok; n++) { mma16816(c0[0], 0, 0, 0, 0, 0, 0); ok = mbar_try(bars + B_X, 0); }
        if (XSPLIT && wg) ok = 0;
      }
#pragma unroll
      for (int i = 0; i < 8; i++) {
        if (i < 7) {
          if (!ok) mbar_wait(bx + i * 8, 0);
          OBS(tid == 64 && i == 0, 0); OBS(tid == 64 && i == 6, 15);
#pragma unroll
          for (int k = 0; k < 4; k++) ldsm4(X[i * 4 + k], xa[k] + i * 16384);
          if (i < 6) ok = mbar_try(bx + i * 8 + 8, 0);
        }
        if (i > 0) {
#pragma unroll
          for (int k = i * 4 - 4; k < i * 4; k++) {
            mma16816(c0[k & 1], X[k][0], one[(k & 1) * 4], X[k][1], one[(k & 1) * 4 + 1], X[k][0], X[k][1]);
            mma16816(c1[k & 1], X[k][2], one[(k & 1) * 4 + 2], X[k][3], one[(k & 1) * 4 + 3], X[k][2], X[k][3]);
          }
        }
      }
      float st[4];
#pragma unroll
      for (int j = 0; j < 2; j++) {
        st[j] = __shfl_sync(0xffffffffu, (g & 1) ? c0[0][2 * j + 1] + c0[1][2 * j + 1] : c0[0][2 * j] + c0[1][2 * j], (lane & 28) | (g >> 1));
        st[2 + j] = __shfl_sync(0xffffffffu, (g & 1) ? c1[0][2 * j + 1] + c1[1][2 * j + 1] : c1[0][2 * j] + c1[1][2 * j], (lane & 28) | (g >> 1));
      }
      named_arrive(8, 384);
      asm volatile("{\n.reg .pred q;\nsetp.ne.u32 q, %3, 0;\n@q st.shared.v2.f32 [%0], {%1,%2};\n@q bar.arrive 9, 160;\n}"
                   :: "r"(base + OFF_LN + ((t & 1) * 8 + g) * 8), "f"((t & 1) ? st[3] : st[1]), "f"((t & 1) ? st[2] : st[0]), "r"((uint32_t)((warp ^ 4) == hp)) : "memory");
      ok = mbar_try(bars + B_KV, 0);
      LnC l0, l1;
      float eps = 1e-5f;
#pragma unroll 1
      do {
        l0 = ln_consts(st[1], st[0], eps); l1 = ln_consts(st[3], st[2], eps);
#pragma unroll
        for (int k = 0; k < PRE * 16; k++) X[k >> 2][k & 3] = hsub2(X[k >> 2][k & 3], k & 2 ? l1.m : l0.m);
        eps += eps;
      } while ((l0.rl ^ l1.rl) == 4);
      OBS(tid == 32, 1);
      float ak[60], *av = ak + 32;
      const int pp_in = wg ? 6 : 0, pp_out = wg ? 0 : 6;
#pragma unroll
      for (int s = 0; s < 7; s++) {
#pragma unroll
        for (int k = s * 4; k < s * 4 + 4; k++) {
          if (s < PRE) {
            auto f = [&](uint32_t d, const LnC& l) { return hfma2(d, l.rh, hmul2(d, l.rl)); };
            const uint32_t y = f(X[k][1], l0);
            X[k][0] = f(X[k][0], l0); X[k][1] = f(X[k][2], l1); X[k][2] = y; X[k][3] = f(X[k][3], l1);
          } else {
            const uint32_t y = ln_apply(X[k][1], l0);
            X[k][0] = ln_apply(X[k][0], l0); X[k][1] = ln_apply(X[k][2], l1); X[k][2] = y; X[k][3] = ln_apply(X[k][3], l1);
          }
        }
        if (__builtin_expect(!ok, 0)) { mbar_wait(bars + B_KV + s * 8, 0); if (s == 6) mbar_wait(bars + B_WQ, 0); }
        if (s == 0) fresh(ak);
        if (s == 6) { wg_wait<0>(); if ((tid & 127) == 0) mbar_arrive(bars + B_EMPTY + 3 * 8); }
        OBS(KOBS && (tid & 127) == 0, 40 + wg * 32 + s);
        if (PPM == 2 ? (wg ? s < 6 : s > 1) : (wg || s)) named_sync(pp_in, 256);
        OBS(KOBS && (tid & 127) == 32, 48 + wg * 32 + s);
        OBS(tid == 64 && s == 0, 2);
        wg_fence();
#pragma unroll
        for (int k = 0; k < 4; k++) {
          wgmma_rs_n120<1>(ak, X[s * 4 + k], mkdesc(HI_SW128, dlo + s * 1024 + k * 128), (s | k) != 0);
        }
        wg_commit();
        if (s == 6) {
          fresh(aq);
#pragma unroll
          for (int k = 0; k < 4 * QA; k++) {
            if (k == 4 * QA - PQE) named_arrive(pp_out, 256);
            wgmma_rs_n56<1>(aq, X[k], mkdesc(HI_SW128, dlq + k * 128), k);
          }
          wg_commit();
        }
        if (s < 6 || PQE == 0) named_arrive_if(PPM != 2 || (wg ? s != 5 : s != 0), pp_out, 256);
        fence_code(s);
        OBS(KOBS && (tid & 127) == 64, 56 + wg * 32 + s);
        if (s < 6) ok = mbar_try(bars + B_KV + s * 8 + 8, 0);
        if (s == 5) ok &= mbar_try(bars + B_WQ, 0);
        OBS(tid == 64 && s == 5, 31);
        if (s > 0) wg_wait<1>();
        OBS(KOBS && (tid & 127) == 96, 64 + wg * 32 + s);
        if ((s == 2 || s == 3 || s == 5) && (tid & 127) == 0) mbar_arrive(bars + B_EMPTY + (s == 5 ? 2 : s - 2) * 8);
      }
      if ((tid & 127) == 0) mbar_arrive(bars + B_EMPTY + 4 * 8);
      OBS(tid == 32, 3);
      {
        const uint32_t kst = base + OFF_K + (2 + (warp ^ 4) * 2 + (mi & 1)) * 1792 + (mi >> 1) * 896 + r8 * 16;
#pragma unroll
        for (int n = 0; n < 7; n++)
          stsm4(kst + n * 128, pack2(ak[n * 4], ak[n * 4 + 1]), pack2(ak[n * 4 + 2], ak[n * 4 + 3]), pack2(av[n * 4], av[n * 4 + 1]), pack2(av[n * 4 + 2], av[n * 4 + 3]));
        named_arrive_if(warp == 3, 1, 96);
      }
      OBS(tid == 96, 32); OBS(tid == 224, 34);
      wg_wait<0>();
      if ((tid & 127) == 0) mbar_arrive(bars + B_EMPTY + 5 * 8);
      mbar_wait(bars + B_WQ2, 0);
    }
    const unsigned short *bp1 = (const unsigned short*)p.b1 + (g1 ? ft * 64 : 0) + w4 * 16 + g, *bp2 = (const unsigned short*)p.b2 + mt * 64 + w4 * 16 + g;
    const uint32_t braw[4] = {__ldg(bp1), __ldg(bp1 + 8), __ldg(bp2), __ldg(bp2 + 8)};
    auto q_rest = [&]() {
      wg_fence();
#pragma unroll
      for (int s = QA; s < 7; s++) {
#pragma unroll
        for (int k = s * 4; k < s * 4 + 4; k++) wgmma_rs_n56<1>(aq, X[k], mkdesc(HI_SW128, dlq + k * 128), 1);
        wg_commit();
        if (s == 5) { wg_wait<2>(); if ((tid & 127) == 0) mbar_arrive(bars + B_EMPTY + 6 * 8); }
      }
    };
    uint32_t Q[4][4];
    auto q_pack = [&]() {
#pragma unroll
      for (int n = 0; n < 14; n++) { const int m = n + 2 * (n > 7); Q[m >> 2][m & 3] = pack2(aq[n * 2], aq[n * 2 + 1]); }
#pragma unroll
      for (int h = 0; h < 2; h++) { Q[2][h] = t < 2 ? 0u : Q[1][2 + h]; Q[1][2 + h] = t < 2 ? Q[1][2 + h] : 0u; }
    };
    float acc[56];
    auto ai = [](int p) { return p < 4 ? 48 + (p & 1) * 4 + (p & 2) : (p - 4) * 4; };
    uint32_t xch, ts, tl;
    unsigned char *ug, *ur, *uc, *outp, *outq;
    auto setup_u = [&]() {
      xch = pin(base + OFF_K + (tid & 127) * 16);
      ug = pin(scr + (d1 * HU_T + 32 + ft) * BT + w4 * 3584 + lane * 4 + wg * 1792);
      const int n = wg ? min(lane, 11) : lane & 15;
      ur = pin(ug + (n < 14 ? n * 128 : (n - 2) * 128 + 1792));
      uc = pin(scr + CNT_OFF + (C_U + d1 + (lane & (UREP - 1)) * 4) * 128);
    };
    auto setup_out = [&]() {
      const uint32_t tb = base + OFF_K + 6144 + warp * 2560;
      ts = pin(tb + mi * 160 + r8 * 16); tl = pin(tb + t * 160 + g * 16);
      unsigned char* o = p.out + (mt * 64 + w4 * 16 + g) * 896 + dt * 224;
      outp = pin(o + th * 7168 + t * 16); outq = pin(o + (t >> 1) * 7168 + 192 + (t & 1) * 16);
    };
    auto give = [&](const float (&a)[56], int id) {
#pragma unroll
      for (int i = 0; i < 48; i += 16) sts128(xch + i * 128, pack2(a[i + 2], a[i + 3]), pack2(a[i + 6], a[i + 7]), pack2(a[i + 10], a[i + 11]), pack2(a[i + 14], a[i + 15]));
      named_arrive(id, 256);
    };
    auto take = [&](uint32_t (&r)[12], int id) {
      named_sync(id, 256);
#pragma unroll
      for (int i = 0; i < 3; i++) { const uint4 v = lds128(xch + i * 2048); r[i * 4] = v.x; r[i * 4 + 1] = v.y; r[i * 4 + 2] = v.z; r[i * 4 + 3] = v.w; }
    };
    float hv[32];
    auto keep_h = [&](int i) {
      const float hb0 = 0.5f * bf_lo(braw[i]), hb1 = 0.5f * bf_lo(braw[i + 1]);
#pragma unroll
      for (int j = 0; j < 32; j++) hv[j] = fmaf(acc[ai(j >> 1) + (j & 1)], 0.5f, j >= 4 && j < 8 ? hb1 : hb0);
    };
    auto take_h = [&](int i) {
      const float hb1 = 0.5f * bf_lo(braw[i + 1]);
      uint32_t r[12];
      take(r, 5);
#pragma unroll
      for (int j = 0; j < 12; j++) { hv[8 + 2 * j] = fmaf(bf_lo(r[j]), 0.5f, hb1); hv[9 + 2 * j] = fmaf(bf_hi(r[j]), 0.5f, hb1); }
    };
    uint4 Xr[4];
    auto get_x = [&]() {
      const uint32_t xr = base + OFF_Q + (w4 * 16 + g) * 224;
      mbar_wait(bars + B_RES, 0);
      Xr[0] = lds128(xr + (t >> 1) * 1792 + 192 + (t & 1) * 16);
#pragma unroll
      for (int i = 1; i < 4; i++) Xr[i] = lds128(xr + th * 1792 + t * 16 + (i - 1) * 64);
    };
    auto gelu = [&](int j) {
      const float h0 = hv[2 * j], h1 = hv[2 * j + 1];
      const float t0 = tanh_fast(h0 * fmaf(h0 * h0, 0.2854192648f, 1.5957691216f)), t1 = tanh_fast(h1 * fmaf(h1 * h1, 0.2854192648f, 1.5957691216f));
      stg32(ug + (ai(j) & 2) * 896 + (ai(j) >> 2) * 128, pack2(fmaf(h0, t0, h0), fmaf(h1, t1, h1)));
    };
    uint32_t Sv[16];
    auto gate = [&](int i) {
      uint32_t R[4];
#pragma unroll
      for (int q = 0; q < 4; q++) {
        const int j = i * 4 + q;
        const float h0 = hv[2 * j], h1 = hv[2 * j + 1];
        R[q] = hmul2(Sv[j], pack2(fmaf(h0, tanh_fast(h0), h0), fmaf(h1, tanh_fast(h1), h1)));
      }
      stsm4(ts + i * 640, R[0], R[1], R[2], R[3]);
    };
    auto leave = [&](int i) {
      __syncwarp();
      const uint4 v = lds128(tl + i * 640), x = Xr[i];
      stg128(i ? outp + (i - 1) * 64 : outq, hadd2(x.x, v.x), hadd2(x.y, v.y), hadd2(x.z, v.z), hadd2(x.w, v.w));
    };
    if (wg == 0) {
      named_sync(0, 256);
      OBS(tid == 96, 14);
      q_rest();
      named_arrive(6, 256);
      wg_wait<0>();
      if (tid == 0) mbar_arrive(bars + B_EMPTY + 7 * 8);
      q_pack();
      const uint32_t qst = base + OFF_Q + 8192 + (mi >> 1) * 1024 + (w4 * 16 + (mi & 1) * 8 + r8) * 16;
#pragma unroll
      for (int n = 0; n < 4; n++) stsm4(qst + n * 2048, Q[n][0], Q[n][1], Q[n][2], Q[n][3]);
      smem_fence();
      named_arrive(7, 256);
      OBS(tid == 32, 5);
      fresh(acc);
      setup_u();
      if (g1) {
        mbar_wait(bars, 0); mbar_wait(bars + 8, 0);
        if (TS) {
          const uint32_t tg = lds64(bars + B_T0).x;
          while ((int)(clock() - tg) < 0);
        }
        named_sync(0, 256);
        gemm_issue<1>(acc, base >> 4, base >> 4, 0);
        OBS(tid == 0, 20);
        gemm_loop<1>(acc, base, 1, 32, rel, 40, 1, tid == 32 ? J1 : tid == 64 ? J2 : tid == 96 ? J3 : -1, bars + B_GATE - 8 + w4 * 8);
        mbar_wait(bars + B_ATT, 0);
        wg_wait<0>();
        OBS(tid == 0, 21);
        give(acc, 5);
        mbar_arrive_if(rel, bars + B_EMPTY + 7 * 8);
        fence_code(30);
        keep_h(0);
#pragma unroll
        for (int j = 0; j < 16; j++) { gelu(j); if (j % GCH == GCH - 1 && j < 15) fence_code(8 + j); }
        if (RB & 16) settle(probe(ur));
        if (w4) named_arrive(2, 256);
        else { named_sync(2, 256); asm volatile("{\n.reg .pred q;\nsetp.lt.u32 q, %1, %2;\n@q red.relaxed.gpu.global.add.u32 [%0], 1;\n}" :: "l"(uc), "r"(lane), "n"(UREP) : "memory"); OBS(tid == 0, 9); }
      } else {
        if (lane == 0 && w4) mbar_arrive(bars + B_GATE - 8 + w4 * 8);
      }
      setup_out();
      if (!RESP) get_x();
      uint32_t r[12];
      take(r, 3);
#pragma unroll
      for (int j = 0; j < 16; j++) Sv[j] = r[j < 4 ? 0 : j - 4];
      asm volatile("" :: "r"(r[0]), "r"(r[11]) : "memory");
      named_arrive(10, 256);
      if (RESP) get_x();
      take_h(2);
    } else {
      const uint32_t dq = ((base + OFF_Q) >> 4) + (64u << 16), dk = (base + OFF_K) >> 4;
      const bool odd = g & 1, early = 2 * t + (g & 1) > g;
      uint32_t selA[5], selB[4];
#pragma unroll
      for (int j = 0; j < 5; j++) { selA[j] = j == w4 + (early ? 0 : 1) ? (odd ? 0x1044u : 0x4410u) : 0x4444u; }
#pragma unroll
      for (int j = 0; j < 4; j++) { selB[j] = j == w4 ? (odd ? 0x3244u : 0x4432u) : 0x4444u; }
      float Sc[2][40], Op[2][2][16];
      uint32_t A[2][5][4];
      auto scores = [&](int T) {
        fresh(Sc[0]); fresh(Sc[1]);
#pragma unroll
        for (int k = 0; k < 2; k++) {
#pragma unroll
          for (int hh = 0; hh < 2; hh++)
            if (T) wgmma_n80<0, 0>(Sc[hh], mkdesc(8, dq + 512 + hh * 256 + k * 128), mkdesc(112, dk + (8u << 16) + 896 + hh * 24 + k * 16), k);
            else wgmma_rs_n80<0>(Sc[hh], Q[hh * 2 + k], mkdesc(112, dk + (8u << 16) + hh * 24 + k * 16), k);
        }
      };
      auto softmax = [&](int T) {
        uint32_t L[2][2];
        auto pick = [&](int w) {
#pragma unroll
          for (int hh = 0; hh < 2; hh++) {
            const float* q = Sc[hh] + w * 8;
            auto at = [&](int i) { return odd ? q[i + 1] : q[i]; };
            L[hh][0] = pack2(early ? at(0) : at(8), early ? at(6) : at(14)); L[hh][1] = pack2(at(4), at(10));
          }
          asm volatile("" ::: "memory");
        };
        if (w4 & 2) { if (w4 & 1) pick(3); else pick(2); } else { if (w4 & 1) pick(1); else pick(0); }
#pragma unroll
        for (int hh = 0; hh < 2; hh++) {
          uint32_t a = hfma2(L[hh][0], SC_HI, hmul2(L[hh][0], SC_LO)), c = hfma2(L[hh][1], SC_HI, hmul2(L[hh][1], SC_LO));
          if (T == 0 && w4 == 0 && rb == 0) { if (early) a = 0xce6ece6eu; c = (c & 0xffff0000u) | 0xce6eu; }
          uint32_t mx = hmax2(a, c);
          mx = hmax2(mx, __shfl_xor_sync(0xffffffffu, mx, 1));
          mx = hmax2(mx, __shfl_xor_sync(0xffffffffu, mx, 2));
          uint32_t pp[2];
#pragma unroll
          for (int h = 0; h < 2; h++) {
            const float m = h ? bf_hi(mx) : bf_lo(mx);
            const float p0 = ex2_fast(((h ? bf_hi(a) : bf_lo(a)) - m) * LOG2E), p1 = ex2_fast(((h ? bf_hi(c) : bf_lo(c)) - m) * LOG2E);
            float sm = p0 + p1;
            sm += __shfl_xor_sync(0xffffffffu, sm, 1);
            sm += __shfl_xor_sync(0xffffffffu, sm, 2);
            const float inv = rcp_fast(sm);
            pp[h] = pack2(p0 * inv, p1 * inv);
          }
#pragma unroll
          for (int j = 0; j < 5; j++) {
            A[hh][j][0] = place(pp[0], selA[j]); A[hh][j][1] = j ? place(pp[1], selB[j ? j - 1 : 0]) : 0u;
            A[hh][j][2] = j < 4 ? place(pp[0], selB[j & 3]) : 0u; A[hh][j][3] = place(pp[1], selA[j]);
          }
        }
      };
      auto values = [&](int T) {
        fresh(Op[T][0]); fresh(Op[T][1]);
#pragma unroll
        for (int j = 0; j < 5; j++)
#pragma unroll
          for (int hh = 0; hh < 2; hh++) {
            wgmma_rs_n32<1>(Op[T][hh], A[hh][j], mkdesc(8, dk + (112u << 16) + 56 + T * 896 + hh * 24 + j * 224), j);
          }
        wg_commit();
      };
      uint32_t Ob[2][14];
      auto pack = [&](int T) {
        const float (&O)[2][16] = Op[T];
#pragma unroll
        for (int n = 0; n < 7; n++)
#pragma unroll
          for (int h = 0; h < 2; h++) {
            if (n < 3) Ob[T][n * 2 + h] = pack2(O[0][n * 4 + 2 * h], O[0][n * 4 + 2 * h + 1]);
            else if (n == 3) Ob[T][n * 2 + h] = pack2(t < 2 ? O[0][12 + 2 * h] : O[1][2 * h], t < 2 ? O[0][13 + 2 * h] : O[1][2 * h + 1]);
            else Ob[T][n * 2 + h] = pack2(O[1][(n - 3) * 4 + 2 * h], O[1][(n - 3) * 4 + 2 * h + 1]);
          }
      };
      smem_fence();
      named_sync(6, 256);
      OBS(tid == 224, 26);
      q_rest();
      named_sync(7, 256);
      wg_fence();
      scores(1);
      wg_commit();
      named_arrive_if(g1, 0, 256);
      wg_wait<2>();
      if (tid == 128) mbar_arrive(bars + B_EMPTY + 7 * 8);
      wg_wait<0>();
      OBS(tid == 160, 10);
      softmax(1);
      q_pack();
      OBS(tid == 160, 30);
      mbar_wait(bars + B_HALO, 0);
      OBS(tid == 160, 7);
      mbar_wait(bars + B_GATE, 0);
      wg_fence();
      scores(0);
      values(1);
      wg_wait<0>();
      OBS(tid == 160, 33);
      unsigned char* og = scr + O_OFF + rb * 2 * 57344 + hp * 7168 + w4 * 256 + lane * 4;
      uint32_t seen[6];
      auto put = [&](int T) {
#pragma unroll
        for (int n = 0; n < 14; n++) { stg32(og + T * 57344 + (n >> 1) * 1024 + (n & 1) * 128, Ob[T][n]); if (n == 5 || n == 11 || n == 13) seen[T * 3 + n / 6] = (RB & 8) ? probe(og + T * 57344 + ((n >> 1) - (n == 13 ? 0 : min(g, 2))) * 1024 + (t & 1) * 128) : 0;
          if (OSLEEP && n % OGRP == OGRP - 1) __nanosleep(OSLEEP); }
      };
      if (OMODE == 1) { pack(1); put(1); }
      softmax(0);
      if (OMODE == 2) { pack(1); put(1); }
      mbar_wait(bars + B_GATE + 8, 0);
      wg_fence();
      values(0);
      if (OMODE == 3) { pack(1); put(1); }
      wg_wait<0>();
      OBS(tid == 160, 35);
      named_sync(11, 128);
      if (tid == 160) mbar_arrive(bars + B_ATT);
      if (OMODE == 0) pack(1);
      pack(0);
      if (J3 > J2) mbar_wait(bars + B_GATE + 16, 0);
      if (OMODE == 0) put(1);
      put(0);
      OBS(tid == 160, 28);
      if (RB & 8) settle(seen[0] ^ seen[1] ^ seen[2] ^ seen[3] ^ seen[4] ^ seen[5]);
      named_sync(11, 128);
      if (warp == 4) publish(scr, C_O + rb);
      OBS(tid == 160, 8);
      setup_u(); setup_out();
      float as[56];
      uint32_t uv = 0;
      if (g1) {
        take_h(0);
        if (!RESP && XE) get_x();
#pragma unroll
        for (int j = 4; j < OPJ; j++) { gelu(j); if (j % GCH == GCH - 1 && j < OPJ - 1) fence_code(40 + j); }
        if ((RB & 16) && !UO) settle(probe(ur));
        if ((RB & 16) && UO) uv = probe(ur);
        else named_arrive(2, 256);
      } else if (!RESP && XE) get_x();
      fresh(as);
      gemm_stage<0>(as, base, 0, 0);
      OBS(tid == 128, 22);
      if ((RB & 16) && UO) { settle(uv); named_arrive_if(g1, 2, 256); }
      gemm_loop<0>(as, base, 1, 7, rel, 104);
      fresh(acc);
      if (SEARLY) { wg_wait<0>(); mbar_arrive_if(rel, bars + B_EMPTY + 6 * 8); give(as, 3); if (!RESP && !XE) get_x(); }
      gemm_stage<1>(acc, base, 7, 0);
      OBS(tid == 128, 24);
      if (!SEARLY) { wg_wait<1>(); mbar_arrive_if(rel, bars + B_EMPTY + 6 * 8); give(as, 3); }
#pragma unroll
      for (int j = 0; j < 16; j++) Sv[j] = pack2(as[ai(j)], as[ai(j) + 1]);
      gemm_loop<1, NX>(acc, base, 8, 35, rel, 65);
      if (RESP) get_x();
      named_sync(10, 256);
      wg_wait<0>();
      OBS(tid == 128, 25);
      give(acc, 5);
      fence_code(31);
      keep_h(2);
      gate(0); leave(0);
    }
    {
#pragma unroll
      for (int i = 1; i < 4; i++) { gate(i); leave(i); }
      OBS(tid == 128, 27);
    }
  }
}

typedef CUresult (*EncFn)(CUtensorMap*, CUtensorMapDataType, cuuint32_t, void*, const cuuint64_t*, const cuuint64_t*, const cuuint32_t*,
                          const cuuint32_t*, CUtensorMapInterleave, CUtensorMapSwizzle, CUtensorMapL2promotion, CUtensorMapFloatOOBfill);
void enc(EncFn f, CUtensorMap* m, const void* ptr, cuuint64_t d0, cuuint64_t d1, cuuint64_t d2, cuuint64_t s1, cuuint64_t s2, cuuint32_t b1, cuuint32_t b2, cuuint32_t b0 = 64) {
  const cuuint64_t gd[3] = {d0, d1, d2}, gs[2] = {s1 * 2, s2 * 2};
  const cuuint32_t bx[3] = {b0, b1, b2}, es[3] = {1, 1, 1};
  f(m, CU_TENSOR_MAP_DATA_TYPE_BFLOAT16, 3, (void*)ptr, gd, gs, bx, es, CU_TENSOR_MAP_INTERLEAVE_NONE, b0 == 64 ? CU_TENSOR_MAP_SWIZZLE_128B : CU_TENSOR_MAP_SWIZZLE_NONE,
    CU_TENSOR_MAP_L2_PROMOTION_L2_128B, CU_TENSOR_MAP_FLOAT_OOB_FILL_NONE);
}
}

extern "C" void kernel_launch(void* const* d_in, const int* in_sizes, int n_in, void* d_out, int out_size) {
  (void)in_sizes; (void)n_in; (void)out_size;
  void* fp = nullptr;
  cudaDriverEntryPointQueryResult qr;
  cudaGetDriverEntryPoint("cuTensorMapEncodeTiled", &fp, cudaEnableDefault, &qr);
  EncFn f = (EncFn)fp;
  CUtensorMap m_x, m_wkv, m_wq, m_w1, m_w2, m_res;
  void* scr = nullptr;
  cudaGetSymbolAddress(&scr, g_scr);
  enc(f, &m_x, d_in[0], D_, S_, 1, D_, D_, 128 >> XSPLIT, 1);
  enc(f, &m_wkv, d_in[1], D_, D_, 3, 3 * D_, D_, 64, 2);
  enc(f, &m_wq, d_in[1], D_, D_, 3, 3 * D_, D_, 224, 1);
  enc(f, &m_w1, d_in[4], F_, S_, 1, F_, F_, 64, 1);
  enc(f, &m_w2, d_in[6], S_, F_, 1, S_, S_, 64, 1);
  enc(f, &m_res, d_in[0], D_, S_, 1, D_, D_, 64, 1, 112);
  Params p;
  p.wqkv = (const unsigned char*)d_in[1]; p.wo = (const unsigned char*)d_in[2];
  p.w1 = (const unsigned char*)d_in[4]; p.b1 = (const unsigned char*)d_in[5];
  p.w2 = (const unsigned char*)d_in[6]; p.b2 = (const unsigned char*)d_in[7];
  p.out = (unsigned char*)d_out; p.scr = (unsigned char*)scr;
  cudaFuncSetAttribute(fused_kernel, cudaFuncAttributeMaxDynamicSharedMemorySize, SMEM_BYTES);
  fused_kernel<<<128, NTHREADS, SMEM_BYTES, cudaStreamPerThread>>>(m_x, m_wkv, m_wq, m_w1, m_w2, m_res, p);
}
```

```cpp
#include <cuda_runtime.h>
#include <cuda.h>
#include <cuda_bf16.h>
#include <stdint.h>

template<int TA, int TB> __device__ __forceinline__ void wgmma_n112(float (&d)[56], uint64_t da, uint64_t db, int sc) {
  asm volatile("{\n.reg .pred p;\nsetp.ne.b32 p, %58, 0;\n"
    "wgmma.mma_async.sync.aligned.m64n112k16.f32.bf16.bf16 {%0, %1, %2, %3, %4, %5, %6, %7, %8, %9, %10, %11, %12, %13, %14, %15, %16, %17, %18, %19, %20, %21, %22, %23, %24, %25, %26, %27, %28, %29, %30, %31, %32, %33, %34, %35, %36, %37, %38, %39, %40, %41, %42, %43, %44, %45, %46, %47, %48, %49, %50, %51, %52, %53, %54, %55}, %56, %57, p, 1, 1, %59, %60;\n}\n"
    : "+f"(d[0]), "+f"(d[1]), "+f"(d[2]), "+f"(d[3]), "+f"(d[4]), "+f"(d[5]), "+f"(d[6]), "+f"(d[7]), "+f"(d[8]), "+f"(d[9]), "+f"(d[10]), "+f"(d[11]), "+f"(d[12]), "+f"(d[13]), "+f"(d[14]), "+f"(d[15]), "+f"(d[16]), "+f"(d[17]), "+f"(d[18]), "+f"(d[19]), "+f"(d[20]), "+f"(d[21]), "+f"(d[22]), "+f"(d[23]), "+f"(d[24]), "+f"(d[25]), "+f"(d[26]), "+f"(d[27]), "+f"(d[28]), "+f"(d[29]), "+f"(d[30]), "+f"(d[31]), "+f"(d[32]), "+f"(d[33]), "+f"(d[34]), "+f"(d[35]), "+f"(d[36]), "+f"(d[37]), "+f"(d[38]), "+f"(d[39]), "+f"(d[40]), "+f"(d[41]), "+f"(d[42]), "+f"(d[43]), "+f"(d[44]), "+f"(d[45]), "+f"(d[46]), "+f"(d[47]), "+f"(d[48]), "+f"(d[49]), "+f"(d[50]), "+f"(d[51]), "+f"(d[52]), "+f"(d[53]), "+f"(d[54]), "+f"(d[55])
    : "l"(da), "l"(db), "r"(sc), "n"(TA), "n"(TB));
}

template<int TA, int TB> __device__ __forceinline__ void wgmma_n80(float (&d)[40], uint64_t da, uint64_t db, int sc) {
  asm volatile("{\n.reg .pred p;\nsetp.ne.b32 p, %42, 0;\n"
    "wgmma.mma_async.sync.aligned.m64n80k16.f32.bf16.bf16 {%0, %1, %2, %3, %4, %5, %6, %7, %8, %9, %10, %11, %12, %13, %14, %15, %16, %17, %18, %19, %20, %21, %22, %23, %24, %25, %26, %27, %28, %29, %30, %31, %32, %33, %34, %35, %36, %37, %38, %39}, %40, %41, p, 1, 1, %43, %44;\n}\n"
    : "+f"(d[0]), "+f"(d[1]), "+f"(d[2]), "+f"(d[3]), "+f"(d[4]), "+f"(d[5]), "+f"(d[6]), "+f"(d[7]), "+f"(d[8]), "+f"(d[9]), "+f"(d[10]), "+f"(d[11]), "+f"(d[12]), "+f"(d[13]), "+f"(d[14]), "+f"(d[15]), "+f"(d[16]), "+f"(d[17]), "+f"(d[18]), "+f"(d[19]), "+f"(d[20]), "+f"(d[21]), "+f"(d[22]), "+f"(d[23]), "+f"(d[24]), "+f"(d[25]), "+f"(d[26]), "+f"(d[27]), "+f"(d[28]), "+f"(d[29]), "+f"(d[30]), "+f"(d[31]), "+f"(d[32]), "+f"(d[33]), "+f"(d[34]), "+f"(d[35]), "+f"(d[36]), "+f"(d[37]), "+f"(d[38]), "+f"(d[39])
    : "l"(da), "l"(db), "r"(sc), "n"(TA), "n"(TB));
}

template<int TB> __device__ __forceinline__ void wgmma_rs_n120(float (&d)[60], const uint32_t (&a)[4], uint64_t db, int sc) {
  asm volatile("{\n.reg .pred p;\nsetp.ne.b32 p, %65, 0;\n"
    "wgmma.mma_async.sync.aligned.m64n120k16.f32.bf16.bf16 {%0, %1, %2, %3, %4, %5, %6, %7, %8, %9, %10, %11, %12, %13, %14, %15, %16, %17, %18, %19, %20, %21, %22, %23, %24, %25, %26, %27, %28, %29, %30, %31, %32, %33, %34, %35, %36, %37, %38, %39, %40, %41, %42, %43, %44, %45, %46, %47, %48, %49, %50, %51, %52, %53, %54, %55, %56, %57, %58, %59}, {%60, %61, %62, %63}, %64, p, 1, 1, %66;\n}\n"
    : "+f"(d[0]), "+f"(d[1]), "+f"(d[2]), "+f"(d[3]), "+f"(d[4]), "+f"(d[5]), "+f"(d[6]), "+f"(d[7]), "+f"(d[8]), "+f"(d[9]), "+f"(d[10]), "+f"(d[11]), "+f"(d[12]), "+f"(d[13]), "+f"(d[14]), "+f"(d[15]), "+f"(d[16]), "+f"(d[17]), "+f"(d[18]), "+f"(d[19]), "+f"(d[20]), "+f"(d[21]), "+f"(d[22]), "+f"(d[23]), "+f"(d[24]), "+f"(d[25]), "+f"(d[26]), "+f"(d[27]), "+f"(d[28]), "+f"(d[29]), "+f"(d[30]), "+f"(d[31]), "+f"(d[32]), "+f"(d[33]), "+f"(d[34]), "+f"(d[35]), "+f"(d[36]), "+f"(d[37]), "+f"(d[38]), "+f"(d[39]), "+f"(d[40]), "+f"(d[41]), "+f"(d[42]), "+f"(d[43]), "+f"(d[44]), "+f"(d[45]), "+f"(d[46]), "+f"(d[47]), "+f"(d[48]), "+f"(d[49]), "+f"(d[50]), "+f"(d[51]), "+f"(d[52]), "+f"(d[53]), "+f"(d[54]), "+f"(d[55]), "+f"(d[56]), "+f"(d[57]), "+f"(d[58]), "+f"(d[59])
    : "r"(a[0]), "r"(a[1]), "r"(a[2]), "r"(a[3]), "l"(db), "r"(sc), "n"(TB));
}

template<int TB> __device__ __forceinline__ void wgmma_rs_n56(float (&d)[28], const uint32_t (&a)[4], uint64_t db, int sc) {
  asm volatile("{\n.reg .pred p;\nsetp.ne.b32 p, %33, 0;\n"
    "wgmma.mma_async.sync.aligned.m64n56k16.f32.bf16.bf16 {%0, %1, %2, %3, %4, %5, %6, %7, %8, %9, %10, %11, %12, %13, %14, %15, %16, %17, %18, %19, %20, %21, %22, %23, %24, %25, %26, %27}, {%28, %29, %30, %31}, %32, p, 1, 1, %34;\n}\n"
    : "+f"(d[0]), "+f"(d[1]), "+f"(d[2]), "+f"(d[3]), "+f"(d[4]), "+f"(d[5]), "+f"(d[6]), "+f"(d[7]), "+f"(d[8]), "+f"(d[9]), "+f"(d[10]), "+f"(d[11]), "+f"(d[12]), "+f"(d[13]), "+f"(d[14]), "+f"(d[15]), "+f"(d[16]), "+f"(d[17]), "+f"(d[18]), "+f"(d[19]), "+f"(d[20]), "+f"(d[21]), "+f"(d[22]), "+f"(d[23]), "+f"(d[24]), "+f"(d[25]), "+f"(d[26]), "+f"(d[27])
    : "r"(a[0]), "r"(a[1]), "r"(a[2]), "r"(a[3]), "l"(db), "r"(sc), "n"(TB));
}

template<int TB> __device__ __forceinline__ void wgmma_rs_n32(float (&d)[16], const uint32_t (&a)[4], uint64_t db, int sc) {
  asm volatile("{\n.reg .pred p;\nsetp.ne.b32 p, %21, 0;\n"
    "wgmma.mma_async.sync.aligned.m64n32k16.f32.bf16.bf16 {%0, %1, %2, %3, %4, %5, %6, %7, %8, %9, %10, %11, %12, %13, %14, %15}, {%16, %17, %18, %19}, %20, p, 1, 1, %22;\n}\n"
    : "+f"(d[0]), "+f"(d[1]), "+f"(d[2]), "+f"(d[3]), "+f"(d[4]), "+f"(d[5]), "+f"(d[6]), "+f"(d[7]), "+f"(d[8]), "+f"(d[9]), "+f"(d[10]), "+f"(d[11]), "+f"(d[12]), "+f"(d[13]), "+f"(d[14]), "+f"(d[15])
    : "r"(a[0]), "r"(a[1]), "r"(a[2]), "r"(a[3]), "l"(db), "r"(sc), "n"(TB));
}

template<int TB> __device__ __forceinline__ void wgmma_rs_n80(float (&d)[40], const uint32_t (&a)[4], uint64_t db, int sc) {
  asm volatile("{\n.reg .pred p;\nsetp.ne.b32 p, %45, 0;\n"
    "wgmma.mma_async.sync.aligned.m64n80k16.f32.bf16.bf16 {%0, %1, %2, %3, %4, %5, %6, %7, %8, %9, %10, %11, %12, %13, %14, %15, %16, %17, %18, %19, %20, %21, %22, %23, %24, %25, %26, %27, %28, %29, %30, %31, %32, %33, %34, %35, %36, %37, %38, %39}, {%40, %41, %42, %43}, %44, p, 1, 1, %46;\n}\n"
    : "+f"(d[0]), "+f"(d[1]), "+f"(d[2]), "+f"(d[3]), "+f"(d[4]), "+f"(d[5]), "+f"(d[6]), "+f"(d[7]), "+f"(d[8]), "+f"(d[9]), "+f"(d[10]), "+f"(d[11]), "+f"(d[12]), "+f"(d[13]), "+f"(d[14]), "+f"(d[15]), "+f"(d[16]), "+f"(d[17]), "+f"(d[18]), "+f"(d[19]), "+f"(d[20]), "+f"(d[21]), "+f"(d[22]), "+f"(d[23]), "+f"(d[24]), "+f"(d[25]), "+f"(d[26]), "+f"(d[27]), "+f"(d[28]), "+f"(d[29]), "+f"(d[30]), "+f"(d[31]), "+f"(d[32]), "+f"(d[33]), "+f"(d[34]), "+f"(d[35]), "+f"(d[36]), "+f"(d[37]), "+f"(d[38]), "+f"(d[39])
    : "r"(a[0]), "r"(a[1]), "r"(a[2]), "r"(a[3]), "l"(db), "r"(sc), "n"(TB));
}

namespace {
constexpr int S_ = 2048, D_ = 448, F_ = 1792;
constexpr int NSLOT = 8, SLOT = 22528;
constexpr int OFF_X = 7 * 16384;
constexpr int OFF_WQ = 8 * 16384;
constexpr int OFF_Q = NSLOT * SLOT;
constexpr int OFF_K = OFF_Q + 16384;
constexpr int OFF_XW = OFF_K + 6144;
constexpr int OFF_BAR = 14 * 16384;
constexpr int OFF_LN = OFF_BAR + 512;
constexpr int OFF_OBS = OFF_BAR + 640;
constexpr int SMEM_BYTES = OFF_OBS + 1024;
#define PACE0 0
#define PACE1 540
#define PACE2 650
#define WARM 3
#define NW0 2
#define HEAT 1
#define T0 0
#define TP 250
#define J3 0
#define J1 9
#define J2 14
#define EARLY 4
#define PPE 4
#define PQE 2
#define LANDOBS 0
#define TRUNC 0
#define KOBS 0
#define PRE 1
#define QA 2
#define HEARLY 0
#define OSLEEP 20
#define PROBE 1
#define WOP 0
#define OGRP 2
#define OMODE 3
#define GCH 4
#define GLAG 2
#define GSLOW 0
#define RH 32
#define NOST 0
#define GOBS 0
#define HP 0
#define OPP 0
#define STAG 0
#define RESP 0
#define XE 1
#define NX 0
#define XS 15
#define XT 9
#define NPRE 1
#define U0 0
#define ALL4 0
#define UREP 1
#define TS 0
#define PPM 1
#define WPF 7
#define XSPLIT 1
#define XK 1
#define TAG 1
#define HWAIT 300
#define RB 31
#define UO 1
#define FSM 1
#define XP 0
#define HREP 1
#define HSL 200
#define WOW 3
#define WQA 4
#define WQC 0
#define WQW 3
#define HNAP 0
#define HL 1
#define WQS 0
#define WQM 0
#define EPO 4
#define MU 0
#define P2 224
#define UP 170
#define POLL "relaxed"
#define OPJ 16
#define SEARLY 1
#define EXACT 0
#define SOBS 0
#define FREQ 0
#define OBS(c, i) do {} while (0)
#define OBSG(c, i, j) do {} while (0)
constexpr int NTHREADS = 384;
constexpr float SCALE = 0.18898223650461361f, LOG2E = 1.4426950408889634f;
constexpr uint32_t SC_HI = 0x3e423e42u, SC_LO = 0xb9f7b9f7u;
constexpr int BT = 14336;

constexpr int HU_T = 67;
constexpr int O_OFF = 4 * HU_T * BT;
constexpr int HALO_OFF = O_OFF + 32 * 7 * 8192;
constexpr int CNT_OFF = HALO_OFF + 128 * 3584;
constexpr int SCR_BYTES = CNT_OFF + 193 * 128;
constexpr int C_WO = 0, C_TK = 1, C_U = 160, C_O = 8, C_H = 176, C_HALO = 32, C_EPOCH = EPO ? C_H : 192;
__device__ __align__(1024) unsigned char g_scr[SCR_BYTES];

__device__ __forceinline__ uint32_t smem_u32(const void* p) { return (uint32_t)__cvta_generic_to_shared(p); }
__device__ __forceinline__ void mbar_init(uint32_t bar, uint32_t cnt) { asm volatile("mbarrier.init.shared::cta.b64 [%0], %1;" :: "r"(bar), "r"(cnt)); }
__device__ __forceinline__ void mbar_expect_tx(uint32_t bar, uint32_t bytes) { asm volatile("mbarrier.arrive.expect_tx.shared::cta.b64 _, [%0], %1;" :: "r"(bar), "r"(bytes) : "memory"); }
__device__ __forceinline__ void mbar_arrive_if(uint32_t c, uint32_t bar) { asm volatile("{\n.reg .pred q;\nsetp.ne.u32 q, %1, 0;\n@q mbarrier.arrive.shared::cta.b64 _, [%0];\n}" :: "r"(bar), "r"(c) : "memory"); }
__device__ __forceinline__ void mbar_arrive(uint32_t bar) { asm volatile("mbarrier.arrive.shared::cta.b64 _, [%0];" :: "r"(bar) : "memory"); }
__device__ __forceinline__ void mbar_wait(uint32_t bar, uint32_t parity) {
  asm volatile("{\n.reg .pred p;\n.reg .u32 n;\nmov.u32 n, 0;\nLAB_WAIT:\n"
               "mbarrier.try_wait.parity.shared::cta.b64 p, [%0], %1;\n@p bra DONE;\n"
               "add.u32 n, n, 1;\nsetp.lt.u32 p, n, 400000;\n@p bra LAB_WAIT;\ntrap;\nDONE:\n}" :: "r"(bar), "r"(parity) : "memory");
}
__device__ __forceinline__ uint32_t mbar_try(uint32_t bar, uint32_t parity) {
  uint32_t ok;
  asm volatile("{\n.reg .pred p;\nmbarrier.test_wait.parity.shared::cta.b64 p, [%1], %2;\nselp.u32 %0, 1, 0, p;\n}" : "=r"(ok) : "r"(bar), "r"(parity) : "memory");
  return ok;
}
__device__ __forceinline__ void tma3d(uint32_t dst, const CUtensorMap* m, int c0, int c1, int c2, uint32_t bar) {
  asm volatile("cp.async.bulk.tensor.3d.shared::cluster.global.mbarrier::complete_tx::bytes [%0], [%1, {%3, %4, %5}], [%2];"
               :: "r"(dst), "l"(m), "r"(bar), "r"(c0), "r"(c1), "r"(c2) : "memory");
}
__device__ __forceinline__ void bulk_g2s(uint32_t dst, const void* src, uint32_t bytes, uint32_t bar) {
  asm volatile("cp.async.bulk.shared::cluster.global.mbarrier::complete_tx::bytes [%0], [%1], %2, [%3];" :: "r"(dst), "l"(src), "r"(bytes), "r"(bar) : "memory");
}
__device__ __forceinline__ void wg_fence() { asm volatile("wgmma.fence.sync.aligned;" ::: "memory"); }
__device__ __forceinline__ void wg_commit() { asm volatile("wgmma.commit_group.sync.aligned;" ::: "memory"); }
template <int N> __device__ __forceinline__ void wg_wait() { asm volatile("wgmma.wait_group.sync.aligned %0;" :: "n"(N) : "memory"); }
__device__ __forceinline__ void smem_fence() { asm volatile("fence.proxy.async.shared::cta;" ::: "memory"); }
__device__ __forceinline__ void stg128(void* p, uint32_t a, uint32_t b, uint32_t c, uint32_t d) { asm volatile("st.global.v4.u32 [%0], {%1,%2,%3,%4};" :: "l"(p), "r"(a), "r"(b), "r"(c), "r"(d) : "memory"); }
__device__ __forceinline__ void stg32(void* p, uint32_t v) { asm volatile("st.global.u32 [%0], %1;" :: "l"(p), "r"(v) : "memory"); }
__device__ __forceinline__ uint4 ldg128(const void* p) { uint4 v; asm volatile("ld.global.nc.L1::no_allocate.v4.u32 {%0,%1,%2,%3}, [%4];" : "=r"(v.x), "=r"(v.y), "=r"(v.z), "=r"(v.w) : "l"(p)); return v; }
__device__ __forceinline__ void publish(unsigned char* scr, int i) {
  asm volatile("{\n.reg .pred q;\nelect.sync _|q, 0xffffffff;\n@q red.relaxed.gpu.global.inc.u32 [%0], 0xffffffff;\n}" :: "l"(scr + CNT_OFF + i * 128) : "memory");
}
__device__ __forceinline__ uint32_t probe(const unsigned char* p) { uint32_t v; asm volatile("ld.relaxed.gpu.global.u32 %0, [%1];" : "=r"(v) : "l"(p) : "memory"); return v; }
__device__ __forceinline__ void settle(uint32_t v) {
  asm volatile("{\n.reg .pred q;\nsetp.eq.u32 q, %0, 0x7fc1dead;\n@q st.volatile.shared.u32 [%1], %0;\n}" :: "r"(v), "r"(1024 + OFF_BAR + 376) : "memory");
  __syncwarp();
}
template <int NAP = 0>
__device__ __forceinline__ void spin_ge(unsigned char* scr, int i, unsigned target) {
  if (NAP) {
    for (int n = 0; !__all_sync(0xffffffffu, probe(scr + CNT_OFF + i * 128) >= target); n++) { __nanosleep(NAP); if (n > 2000000) asm volatile("trap;"); }
    return;
  }
  asm volatile("{\n.reg .pred p;\n.reg .u32 n, v;\nmov.u32 n, 0;\nLAB_SPIN:\n"
               "ld." POLL ".gpu.global.u32 v, [%0];\nsetp.ge.u32 p, v, %1;\nvote.sync.all.pred p, p, 0xffffffff;\n@p bra DONE;\n"
               "add.u32 n, n, 1;\nsetp.lt.u32 p, n, 4000000;\n@p bra LAB_SPIN;\ntrap;\nDONE:\n}" :: "l"(scr + CNT_OFF + i * 128), "r"(target) : "memory");
}
__device__ __forceinline__ int lane_id() { int l; asm volatile("mov.u32 %0, %%laneid;" : "=r"(l)); return l; }
__device__ __forceinline__ uint32_t pin(uint32_t v) { return __shfl_xor_sync(0xffffffffu, v, blockIdx.y); }
__device__ __forceinline__ unsigned char* pin(unsigned char* p) { return (unsigned char*)(((uint64_t)pin((uint32_t)((uint64_t)p >> 32)) << 32) | pin((uint32_t)(uint64_t)p)); }
__device__ __forceinline__ bool elect() {
  uint32_t r; asm volatile("{\n.reg .pred p;\nelect.sync _|p, 0xffffffff;\nselp.u32 %0, 1, 0, p;\n}" : "=r"(r)); return r != 0;
}
__device__ __forceinline__ uint4 lds128(uint32_t a) { uint4 v; asm volatile("ld.shared.v4.u32 {%0,%1,%2,%3}, [%4];" : "=r"(v.x), "=r"(v.y), "=r"(v.z), "=r"(v.w) : "r"(a) : "memory"); return v; }
__device__ __forceinline__ uint2 lds64(uint32_t a) { uint2 v; asm volatile("ld.shared.v2.u32 {%0,%1}, [%2];" : "=r"(v.x), "=r"(v.y) : "r"(a) : "memory"); return v; }
__device__ __forceinline__ void sts128(uint32_t p, uint32_t a, uint32_t b, uint32_t c, uint32_t d) { asm volatile("st.shared.v4.u32 [%0], {%1,%2,%3,%4};" :: "r"(p), "r"(a), "r"(b), "r"(c), "r"(d) : "memory"); }
__device__ __forceinline__ void sts32(uint32_t a, float v) { asm volatile("st.shared.f32 [%0], %1;" :: "r"(a), "f"(v) : "memory"); }
__device__ __forceinline__ void named_sync(int id, int n) { asm volatile("bar.sync %0, %1;" :: "r"(id), "r"(n) : "memory"); }
__device__ __forceinline__ void named_arrive(int id, int n) { asm volatile("bar.arrive %0, %1;" :: "r"(id), "r"(n) : "memory"); }
__device__ __forceinline__ void named_arrive_if(uint32_t c, int id, int n) { asm volatile("{\n.reg .pred q;\nsetp.ne.u32 q, %2, 0;\n@q bar.arrive %0, %1;\n}" :: "r"(id), "r"(n), "r"(c) : "memory"); }
__device__ __forceinline__ uint64_t mkdesc(uint32_t hi, uint32_t lo) { return ((uint64_t)hi << 32) | lo; }
constexpr uint32_t HI_SW128 = 0x40000040u;
__device__ __forceinline__ uint32_t pack2(float lo, float hi) { uint32_t r; asm("cvt.rn.bf16x2.f32 %0, %1, %2;" : "=r"(r) : "f"(hi), "f"(lo)); return r; }
__device__ __forceinline__ float bf_lo(uint32_t v) { return __uint_as_float(v << 16); }
__device__ __forceinline__ float bf_hi(uint32_t v) { return __uint_as_float(v & 0xffff0000u); }
__device__ __forceinline__ float rbf(float x) { return bf_lo(pack2(x, 0.f)); }
__device__ __forceinline__ uint32_t hsub2(uint32_t a, uint32_t b) { uint32_t r; asm("sub.rn.bf16x2 %0, %1, %2;" : "=r"(r) : "r"(a), "r"(b)); return r; }
__device__ __forceinline__ uint32_t hadd2(uint32_t a, uint32_t b) { uint32_t r; asm("add.rn.bf16x2 %0, %1, %2;" : "=r"(r) : "r"(a), "r"(b)); return r; }
__device__ __forceinline__ uint32_t place(uint32_t v, uint32_t sel) { uint32_t r; asm volatile("prmt.b32 %0, %1, 0, %2;" : "=r"(r) : "r"(v), "r"(sel)); return r; }
__device__ __forceinline__ uint32_t hmax2(uint32_t a, uint32_t b) { uint32_t r; asm("max.bf16x2 %0, %1, %2;" : "=r"(r) : "r"(a), "r"(b)); return r; }
__device__ __forceinline__ uint32_t hmul2(uint32_t a, uint32_t b) { uint32_t r; asm("mul.rn.bf16x2 %0, %1, %2;" : "=r"(r) : "r"(a), "r"(b)); return r; }
__device__ __forceinline__ uint32_t hfma2(uint32_t a, uint32_t b, uint32_t c) { uint32_t r; asm("fma.rn.bf16x2 %0, %1, %2, %3;" : "=r"(r) : "r"(a), "r"(b), "r"(c)); return r; }
__device__ __forceinline__ float tanh_fast(float x) { float r; asm("tanh.approx.f32 %0, %1;" : "=f"(r) : "f"(x)); return r; }
__device__ __forceinline__ float rcp_fast(float x) { float r; asm("rcp.approx.ftz.f32 %0, %1;" : "=f"(r) : "f"(x)); return r; }
__device__ __forceinline__ float ex2_fast(float x) { float r; asm("ex2.approx.ftz.f32 %0, %1;" : "=f"(r) : "f"(x)); return r; }
__device__ __forceinline__ void mma16816(float (&c)[4], uint32_t a0, uint32_t a1, uint32_t a2, uint32_t a3, uint32_t b0, uint32_t b1) {
  asm volatile("mma.sync.aligned.m16n8k16.row.col.f32.bf16.bf16.f32 {%0,%1,%2,%3}, {%4,%5,%6,%7}, {%8,%9}, {%0,%1,%2,%3};"
               : "+f"(c[0]), "+f"(c[1]), "+f"(c[2]), "+f"(c[3]) : "r"(a0), "r"(a1), "r"(a2), "r"(a3), "r"(b0), "r"(b1));
}
__device__ __forceinline__ void ldsm4(uint32_t (&r)[4], uint32_t addr) {
  asm volatile("ldmatrix.sync.aligned.m8n8.x4.shared.b16 {%0,%1,%2,%3}, [%4];" : "=r"(r[0]), "=r"(r[1]), "=r"(r[2]), "=r"(r[3]) : "r"(addr) : "memory");
}
__device__ __forceinline__ void stsm4(uint32_t addr, uint32_t a, uint32_t b, uint32_t c, uint32_t d) {
  asm volatile("stmatrix.sync.aligned.m8n8.x4.shared.b16 [%0], {%1,%2,%3,%4};" :: "r"(addr), "r"(a), "r"(b), "r"(c), "r"(d) : "memory");
}

__device__ __forceinline__ float ln_rstd(float var, float eps = 1e-5f) {
  float sd;
  asm("sqrt.approx.ftz.f32 %0, %1;" : "=f"(sd) : "f"(rbf(rbf(var) + eps)));
  return rcp_fast(rbf(sd));
}
__device__ __forceinline__ float ln_var(float mean, float sq) { return fmaxf(fmaf(-mean, mean, sq * (1.0f / D_)), 0.f); }
struct LnC { uint32_t m, rh, rl; };
__device__ __forceinline__ LnC ln_consts(float sum, float sq, float eps) {
  const float mean = sum * (1.0f / D_), r = ln_rstd(ln_var(mean, sq), eps), rh = rbf(r);
  LnC c; c.m = pack2(mean, mean); c.rh = pack2(rh, rh); c.rl = pack2(r - rh, r - rh);
  return c;
}
__device__ __forceinline__ uint32_t ln_apply(uint32_t x, const LnC& c) {
  uint32_t d = hsub2(x, c.m);
  return hfma2(d, c.rh, hmul2(d, c.rl));
}

__device__ __forceinline__ void fence_code(int id) {
  asm volatile("{\n.reg .pred q;\nLAB_F:\nsetp.eq.u32 q, %0, %1;\n@q st.volatile.shared.u32 [%2], %2;\n@q bra LAB_F;\n}" :: "r"(blockIdx.x), "r"(0x70000000 + id), "r"(0) : "memory");
}
template <int N> __device__ __forceinline__ void fresh(float (&a)[N]) {
#pragma unroll
  for (int i = 0; i < N; i++) asm volatile("" : "=f"(a[i]));
}
constexpr int B_EMPTY = 64, B_X = 384, B_KV = 192, B_WQ = 248, B_HALO = 256, B_RES = 264, B_ATT = 272, B_GATE = 280, B_WO = 304, B_O = 312, B_XW = 320, B_WQ2 = 328, B_XD = 336, B_TAG = 344, B_T0 = 352;

template <int TA>
__device__ __forceinline__ void gemm_issue(float (&acc)[56], uint32_t la, uint32_t lo, int sc) {
  wg_fence();
#pragma unroll
  for (int k = 0; k < 4; k++)
    wgmma_n112<TA, 1>(acc, mkdesc(TA ? HI_SW128 : 8, la + (TA ? 512u << 16 : 64u << 16) + k * 128), mkdesc(8, lo + (112u << 16) + 512 + k * 224), sc | k);
  wg_commit();
}
template <int TA>
__device__ __forceinline__ void gemm_stage(float (&acc)[56], uint32_t base, int it, int sc) {
  mbar_wait(base + OFF_BAR + (it & 7) * 8, (it >> 3) & 1);
  const uint32_t lo = (base >> 4) + (it & 7) * (SLOT >> 4);
  gemm_issue<TA>(acc, lo, lo, sc);
}
template <int TA, int EXTRA = 0>
__device__ __forceinline__ void gemm_loop(float (&acc)[56], uint32_t base, int it, int end, bool rel, int oi, uint32_t ok = 0, int gate_it = -1, uint32_t gate = 0) {
#pragma unroll 1
  for (; it < end;) {
    if (__builtin_expect(!ok, 0)) mbar_wait(base + OFF_BAR + (it & 7) * 8, (it >> 3) & 1);
    const uint32_t lo = (base >> 4) + (it & 7) * (SLOT >> 4);
    gemm_issue<TA>(acc, (unsigned)(it - XS) < EXTRA ? ((base + OFF_XW) >> 4) + (it - XS) * 512 : lo, lo, 1);
    OBS(SOBS && rel, oi + it);
    it++;
    ok = mbar_try(base + OFF_BAR + (it & 7) * 8, (it >> 3) & 1);
    wg_wait<1>();
    if (rel || it == gate_it) mbar_arrive(rel ? base + OFF_BAR + B_EMPTY + ((it - 2) & 7) * 8 : gate);
  }
}
template <int PER>
__device__ __forceinline__ void produce_box(uint32_t base, int it, int end, const CUtensorMap* mp, int c0, int c1, uint32_t tn = 0) {
#pragma unroll 1
  for (; it < end; it++) {
    const uint32_t fb = base + OFF_BAR + (it & 7) * 8;
    mbar_wait(fb + B_EMPTY, (it >> 3) & 1);
    if (PER) { while ((int)(clock() - tn) < 0); tn += PER; }
    if (elect()) { mbar_expect_tx(fb, 8192); tma3d(base + (it & 7) * SLOT, mp, c0, c1, 0, fb); }
    c1 += 64;
  }
}
template <int PER>
__device__ __forceinline__ void produce_lin(uint32_t base, int it, int end, const unsigned char* src, uint32_t bytes, uint32_t tn = 0) {
#pragma unroll 1
  for (; it < end; it++) {
    const uint32_t fb = base + OFF_BAR + (it & 7) * 8;
    mbar_wait(fb + B_EMPTY, (it >> 3) & 1);
    if (PER) { while ((int)(clock() - tn) < 0); tn += PER; }
    if (elect()) { mbar_expect_tx(fb, bytes); bulk_g2s(base + (it & 7) * SLOT + (bytes & 2048) * 4, src, bytes, fb); }
    src += bytes;
  }
}

__device__ __forceinline__ void retile_wo(const unsigned char* wo, unsigned char* scr, int u, int lane) {
  const int r8 = lane & 7, mi = lane >> 3;
  const unsigned char* src = wo + ((u >> 1) * 8 + r8) * 896 + ((u & 1) * 28 + mi) * 16;
  unsigned char* dst = scr + ((u & 1) * 2 * HU_T + 60 + (u >> 4)) * BT + ((u >> 1) & 7) * 1792 + mi * 128 + r8 * 16;
  uint4 v[7];
#pragma unroll
  for (int i = 0; i < 7; i++) v[i] = ldg128(src + i * 64);
#pragma unroll
  for (int i = 0; i < 7; i++) stg128(dst + i * 512 + ((i * 4 + mi) / 14) * (HU_T * BT - 1792), v[i].x, v[i].y, v[i].z, v[i].w);
  if (!(RB & 1)) publish(scr, C_WO);
}

struct Params {
  const unsigned char *wqkv, *wo, *w1, *b1, *w2, *b2;
  unsigned char *out, *scr;
};

__global__ void __launch_bounds__(NTHREADS, 1)
fused_kernel(const __grid_constant__ CUtensorMap m_x, const __grid_constant__ CUtensorMap m_wkv, const __grid_constant__ CUtensorMap m_wq,
             const __grid_constant__ CUtensorMap m_w1, const __grid_constant__ CUtensorMap m_w2, const __grid_constant__ CUtensorMap m_res, const Params p) {
  extern __shared__ __align__(1024) unsigned char smem_raw[];
  constexpr uint32_t base = 1024, bars = base + OFF_BAR;
  const int tid = threadIdx.x, lane = tid & 31, b = blockIdx.x;
  const int rb = (b >> 2) & 15, hp = ((b >> 6) << 2) | (b & 3);
  const int wcol = hp * 56 - (hp & 1) * 8;
  auto load_wq = [&](int s0, int s1, uint32_t bar) {
    mbar_expect_tx(bar, (s1 - s0) * 8192);
#pragma unroll 1
    for (int s = s0; s < s1; s++) tma3d(base + OFF_WQ + s * 8192, &m_wq, wcol, s * 64, 0, bar);
  };
  auto load_kv = [&](int s) { mbar_expect_tx(bars + B_KV + s * 8, 16384); tma3d(base + s * 16384, &m_wkv, wcol, s * 64, 1, bars + B_KV + s * 8); };
  if (tid < 32) {
    if (elect()) {
#pragma unroll
      for (int i = 0; i < 7; i++) mbar_init(bars + B_X + i * 8, 1);
      asm volatile("fence.mbarrier_init.release.cluster;" ::: "memory");
#pragma unroll
      for (int i = 0; i < 7; i++) { mbar_expect_tx(bars + B_X + i * 8, 16384 >> XSPLIT); tma3d(base + OFF_X + i * 16384 + XSPLIT * 8192, &m_x, i * 64, rb * 128 + XSPLIT * 64, 0, bars + B_X + i * 8); }
#pragma unroll
      for (int i = 0; i < 7; i++) { mbar_init(bars + B_KV + i * 8, 1); if (XSPLIT) mbar_init(bars + B_X + 64 + i * 8, 1); }
      asm volatile("fence.mbarrier_init.release.cluster;" ::: "memory");
      if (XSPLIT) {
#pragma unroll
        for (int i = 0; i < XK; i++) load_kv(i);
#pragma unroll
        for (int i = 0; i < 7; i++) { mbar_expect_tx(bars + B_X + 64 + i * 8, 8192); tma3d(base + OFF_X + i * 16384, &m_x, i * 64, rb * 128, 0, bars + B_X + 64 + i * 8); }
      }
#pragma unroll 1
      for (int i = XSPLIT * XK; i < NW0; i++) load_kv(i);
    }
  }
  const int warp = __shfl_sync(0xffffffffu, tid >> 5, 0);
  if (TS && tid == 64) sts32(bars + B_T0, __uint_as_float(clock() + TS));
  if (warp == 1) {
    if (elect()) {
#pragma unroll
      for (int i = 0; i < 16; i++) mbar_init(bars + i * 8, 2);
#pragma unroll
      for (int i = 0; i < 12; i++) mbar_init(bars + B_WQ + i * 8, 1);
      asm volatile("fence.mbarrier_init.release.cluster;" ::: "memory");
      if (smem_u32(smem_raw) != base) asm volatile("trap;");
    }
  }
  const int dt = b & 3, mt = b >> 2;
  const bool g1 = (b & 15) < 14;
  const int a1 = b - 2 * (b >> 4), ft = a1 >> 2, d1 = a1 & 3;
  const int g = lane >> 2, t = lane & 3, r8 = lane & 7, mi = lane >> 3;
  OBSG(FREQ && tid == 160, 128, 160);
  __syncthreads();
  if (warp >= 8) {
    asm volatile("setmaxnreg.dec.sync.aligned.u32 40;");
    const int pw = warp - 8;
    unsigned char* scr = p.scr;
    if (WPF && pw == 2) {
      mbar_wait(bars + B_X + (WPF - 1) * 8, 0);
      if (b < 112 && lane < 28) asm volatile("prefetch.global.L2 [%0];" :: "l"(p.wqkv + (b * 4 + lane / 7) * 2688 + (lane % 7) * 128) : "memory");
      if (lane == 31) asm volatile("prefetch.tensormap [%0];" :: "l"(&m_wq) : "memory");
      __syncwarp();
    }
    if (NW0 < 7 && pw == 3) {
      mbar_wait(bars + B_X, 0);
      if (elect()) {
#pragma unroll 1
        for (int i = NW0; i < 7; i++) load_kv(i);
      }
      __syncwarp();
    }
    auto first_wq = [&]() {
      named_sync(8, 384);
      if (elect()) { load_wq(0, WQA, bars + B_WQ); mbar_arrive(bars + B_XD); }
      __syncwarp();
    };
    {
      const int c0 = pw * 14 + (mi >> 1);
      unsigned char* dst = scr + (pw * HU_T + rb * 2 + (hp >> 2)) * BT + ((hp & 3) * 2 + (mi & 1)) * 1792 + (mi >> 1) * 128 + r8 * 16;
      const uint32_t xs = base + OFF_X + (hp * 16 + (lane & 15)) * 128;
      uint4 H[7];
      named_sync(9, 160);
#pragma unroll
      for (int i = 0; i < 7; i++) H[i] = lds128(xs + ((c0 + 2 * i) >> 3) * 16384 + ((((c0 + 2 * i) & 7) ^ r8) << 4));
      asm volatile("" :: "r"(H[6].w), "r"(H[0].x) : "memory");
      if (pw != WQW) named_arrive(8, 384);
      else if (!WQC || hp < 4) first_wq();
      const uint2 st = lds64(base + OFF_LN + (lane & 15) * 8);
      const float sum = __uint_as_float(st.x), mean = sum * (1.0f / D_), var = ln_var(mean, __uint_as_float(st.y));
      const float m = rbf(mean), r = ln_rstd(var), r2 = ln_rstd(var * r * r);
      const float nc = fmaf(m, (float)D_, -sum) * (1.0f / D_) * (r * r2);
      const uint32_t m2 = pack2(m, m), r2x = pack2(r * r2, r * r2), nc2 = pack2(nc, nc);
      auto f = [&](uint32_t v) { return hfma2(hsub2(v, m2), r2x, nc2); };
#pragma unroll
      for (int i = 0; i < 7; i++) stg128(dst + i * 256, f(H[i].x), f(H[i].y), f(H[i].z), f(H[i].w));
      if (pw != 1) named_arrive(4, 128);
      if (WQC && pw == WQW && hp >= 4) first_wq();
    }
    const int lane = lane_id();
    if (pw == 0) {
      if (elect()) {
        asm volatile("prefetch.tensormap [%0];" :: "l"(&m_w1) : "memory");
        asm volatile("prefetch.tensormap [%0];" :: "l"(&m_w2) : "memory");
        asm volatile("prefetch.tensormap [%0];" :: "l"(&m_res) : "memory");
      }
      __syncwarp();
      const uint32_t e = probe(scr + EPO + CNT_OFF + C_EPOCH * 128) + 1;
      sts32(bars + B_TAG, __uint_as_float((e & 0x3fffu) | ((e << 2) & 0x3fff0000u)));
      named_arrive(1, 96);
      if (WOW == 0 && b < 112) { retile_wo(p.wo, scr, b, lane_id()); named_arrive(15, 64); }
      if (g1) produce_box<0>(base, 0, 32, &m_w1, ft * 64, 0);
      auto load_res = [&]() { if (elect()) { mbar_expect_tx(bars + B_RES, BT); tma3d(base + OFF_Q, &m_res, dt * 112, mt * 64, 0, bars + B_RES); } };
      if (RESP == 0) { mbar_wait(bars + B_ATT, 0); load_res(); }
      mbar_wait(bars + B_WO, 0);
      produce_lin<0>(base, 0, 7, scr + (dt * HU_T + 60) * BT, BT);
      if (NX) {
        produce_box<0>(base, 7, XT, &m_w2, mt * 64, 0);
        if (elect()) {
          mbar_expect_tx(bars + B_XW, NX * 8192);
#pragma unroll 1
          for (int i = 0; i < NX; i++) tma3d(base + OFF_XW + i * 8192, &m_w2, mt * 64, (XS - 7 + i) * 64, 0, bars + B_XW);
        }
        __syncwarp();
        produce_box<0>(base, XT, XS, &m_w2, mt * 64, (XT - 7) * 64);
        mbar_wait(bars + B_XW, 0);
#pragma unroll 1
        for (int it = XS; it < XS + NX; it++) { mbar_wait(bars + B_EMPTY + (it & 7) * 8, (it >> 3) & 1); if (lane == 0) mbar_arrive(bars + (it & 7) * 8); }
        __syncwarp();
        produce_box<0>(base, XS + NX, 35, &m_w2, mt * 64, (XS + NX - 7) * 64);
      } else produce_box<0>(base, 7, 35, &m_w2, mt * 64, 0);
      if (RESP) load_res();
    } else if (pw == 1) {
      named_sync(4, 128);
      const unsigned char* hl = scr + (rb * 2 + (hp >> 2)) * BT + (hp & 3) * 3584 + min(lane, 27) * 128;
      const uint32_t v0 = probe(hl), v1 = probe(hl + HU_T * BT), v2 = probe(hl + 2 * HU_T * BT), v3 = probe(hl + 3 * HU_T * BT);
      if (RB & 2) settle(v0 ^ v1 ^ v2 ^ v3);
      if (elect()) asm volatile("red.relaxed.gpu.global.add.u32 [%0], 1;" :: "l"(scr + CNT_OFF + (C_H + (b & (HL - 1))) * 128) : "memory");
      __syncwarp();
      OBS(lane == 0, 4);
      if (WQC) mbar_wait(bars + B_XD, 0);
      if (WQC > 1 && hp >= 4) __nanosleep(WQC);
      if ((!WQS || !g1) && elect()) load_wq(WQA, 7, bars + B_WQ2);
      __syncwarp();
      if (g1) {
        if (HSL) __nanosleep(HSL);
        spin_ge<HNAP>(scr, C_H + (lane & (HL - 1)), 128 / HL);
        if (WQS && elect()) load_wq(WQA, 7, bars + B_WQ2);
        __syncwarp();
        OBS(lane == 0, 16);
        if (HP) { produce_lin<HP>(base, 0, 8, scr + d1 * HU_T * BT, BT, clock()); produce_lin<0>(base, 8, 32, scr + (d1 * HU_T + 8) * BT, BT); }
        else produce_lin<0>(base, 0, 32, scr + d1 * HU_T * BT, BT);
      }
      mbar_wait(bars + B_O, 0);
      produce_lin<OPP>(base, 0, 7, scr + O_OFF + mt * 57344, 8192, clock());
      const unsigned char* us = scr + (dt * HU_T + 32) * BT;
#pragma unroll
      for (int i = 0; i < NPRE; i++) {
        mbar_wait(bars + B_EMPTY + ((7 + i) & 7) * 8, i > 0);
        if (elect()) mbar_expect_tx(bars + ((7 + i) & 7) * 8, BT);
        __syncwarp();
      }
      spin_ge(scr, C_U + (ALL4 ? lane & 3 : dt) + (mt & (UREP - 1)) * 4, 28);
      if (elect()) {
#pragma unroll
        for (int i = 0; i < NPRE; i++) bulk_g2s(base + ((7 + i) & 7) * SLOT + 8192, us + i * BT, BT, bars + ((7 + i) & 7) * 8);
      }
      const uint32_t tu = clock();
      OBS(lane == 0, 18);
      produce_lin<UP>(base, 7 + NPRE, 15, us + NPRE * BT, BT, tu + NPRE * UP - U0);
      produce_lin<0>(base, 15, 35, us + 8 * BT, BT);
      unsigned tk = 0;
      if (lane == 0) tk = atomicAdd((unsigned*)(scr + CNT_OFF + C_TK * 128), 1u);
      if (__shfl_sync(0xffffffffu, tk, 0) == 127) {
#pragma unroll 1
        for (int i = lane; i < 192; i += 32) *(unsigned*)(scr + CNT_OFF + i * 128) = 0;
        publish(scr + EPO, C_EPOCH);
      }
    } else if (pw == 2) {
      uint32_t tn = clock() + PACE0 + b * STAG;
      if (WOW == 2 && b < 112) { retile_wo(p.wo, scr, b, lane_id()); named_arrive(15, 64); }
      const unsigned char* src = p.w1 + b * 4096 + lane * 128;
#pragma unroll 1
      for (int i = 0; i < 28 + FREQ * 2; i++) {
        while ((int)(clock() - tn) < 0) __nanosleep(20);
        if (i == 14) src = p.w2 + b * 4096 + lane * 128;
        if (i < 28) asm volatile("prefetch.global.L2 [%0];" :: "l"(src) : "memory");
        OBSG(FREQ && lane == 0, 129 + i, 161 + i);
        src += 128 * 4096;
        tn += i < 14 ? PACE1 : PACE2;
      }
    } else {
      if (WOW == 3 && b < 112) retile_wo(p.wo, scr, b, lane_id());
      const int lane = lane_id();
      unsigned char* hg = scr + HALO_OFF + (rb * 8 + hp) * 3584;
      named_sync(1, 96);
      const uint32_t tag = lds64(bars + B_TAG).x;
      if (rb < 15) {
#pragma unroll
        for (int q = 0; q < 7; q += 4) {
          uint4 v[4];
#pragma unroll
          for (int i = q; i < q + 4 && i < 7; i++) v[i - q] = lds128(base + OFF_K + 8 * 3584 + i * 512 + lane * 16 + (i * 32 + lane < 112 && !(lane & 7) ? 1792 : 0));
#pragma unroll
          for (int i = q; i < q + 4 && i < 7; i++) stg128(hg + i * 512 + lane * 16, (lane & 7) == (i * 32 + lane < 112) ? tag : v[i - q].x, v[i - q].y, v[i - q].z, v[i - q].w);
        }
      }
      if (TAG == 1 && rb < 15) publish(scr, C_HALO + rb * 8 + hp);
      OBS(lane == 0, 29);
      if (rb > 0) {
        if (TAG == 1) spin_ge(scr, C_HALO + (rb - 1) * 8 + hp, 1); else __nanosleep(HWAIT);
        const uint32_t la = base + OFF_K + min(lane, 27) * 128;
#pragma unroll 1
        for (int n = 0;; n++) {
          if (elect()) { mbar_expect_tx(bars + B_XW, 3584); bulk_g2s(base + OFF_K, hg - 8 * 3584, 3584, bars + B_XW); }
          __syncwarp();
          mbar_wait(bars + B_XW, n & 1);
          if ((XP & 2) || __all_sync(0xffffffffu, lds64(la + (lane < 14 ? 16 : 0)).x == tag)) break;
          if (n > 1000000) asm volatile("trap;");
        }
        if (!(XP & 2) && lane < 14) { const uint4 v = lds128(la); sts128(la + 1792, v.x, v.y, v.z, v.w); }
      } else {
#pragma unroll
        for (int i = 0; i < 7; i++) sts128(base + OFF_K + i * 512 + lane * 16, 0, 0, 0, 0);
      }
      OBS(lane == 0, 12);
      if (!(XP & 1) || rb == 0) smem_fence();
      __syncwarp();
      if (lane == 0) mbar_arrive(bars + B_HALO);
      __syncwarp();
      if (WOW != 3 && b < 112) named_sync(15, 64);
      if ((RB & 1) && b < 112) {
        settle(probe(scr + (((b & 1) * 2 + (lane >> 4)) * HU_T + 60 + (b >> 4)) * BT + ((b >> 1) & 7) * 1792 + min(lane & 15, 13) * 128));
        publish(scr, C_WO);
      }
      if (RB & 1) mbar_wait(bars + (g1 ? B_GATE + 8 : B_ATT), 0);
      spin_ge(scr, C_WO, 112);
      if (lane == 0) mbar_arrive(bars + B_WO);
      mbar_wait(bars + B_ATT, 0);
      spin_ge(scr, C_O + (mt >> 1), 8);
      OBS(lane == 0, 17);
      if (lane == 0) mbar_arrive(bars + B_O);
    }
  } else {
    asm volatile("setmaxnreg.inc.sync.aligned.u32 232;");
    const int wg = warp >> 2, w4 = warp & 3, th = wg ^ 1;
    const bool rel = (tid & 127) < 2;
    unsigned char* scr = p.scr;
    uint32_t X[28][4];
    float aq[28];
    const uint32_t dlo = (base >> 4) + (512u << 16) + (hp & 1), dlq = dlo + (OFF_WQ >> 4);
    {
      uint32_t xa[4];
#pragma unroll
      for (int k = 0; k < 4; k++) xa[k] = base + OFF_X + (th * 64 + w4 * 16 + (mi >> 1) * 8 + r8) * 128 + (((2 * k + (mi & 1)) ^ r8) << 4);
      float c0[2][4] = {}, c1[2][4] = {};
      uint32_t one[8];
#pragma unroll
      for (int j = 0; j < 8; j++) asm volatile("{\n.reg .u32 y;\nmov.u32 y, %%tid.y;\nmad.lo.u32 %0, y, %1, 0x3f803f80;\n}" : "=r"(one[j]) : "r"(lane + j));
      asm volatile("" : "+l"(scr));
      uint32_t ok = 0;
      const uint32_t bx = bars + B_X + XSPLIT * wg * 64;
      if (HEAT) {
#pragma unroll 1
        for (int n = 0; n < 64 && !ok; n++) { mma16816(c0[0], 0, 0, 0, 0, 0, 0); ok = mbar_try(bars + B_X, 0); }
        if (XSPLIT && wg) ok = 0;
      }
#pragma unroll
      for (int i = 0; i < 8; i++) {
        if (i < 7) {
          if (!ok) mbar_wait(bx + i * 8, 0);
          OBS(tid == 64 && i == 0, 0); OBS(tid == 64 && i == 6, 15);
#pragma unroll
          for (int k = 0; k < 4; k++) ldsm4(X[i * 4 + k], xa[k] + i * 16384);
          if (i < 6) ok = mbar_try(bx + i * 8 + 8, 0);
        }
        if (i > 0) {
#pragma unroll
          for (int k = i * 4 - 4; k < i * 4; k++) {
            mma16816(c0[k & 1], X[k][0], one[(k & 1) * 4], X[k][1], one[(k & 1) * 4 + 1], X[k][0], X[k][1]);
            mma16816(c1[k & 1], X[k][2], one[(k & 1) * 4 + 2], X[k][3], one[(k & 1) * 4 + 3], X[k][2], X[k][3]);
          }
        }
      }
      float st[4];
#pragma unroll
      for (int j = 0; j < 2; j++) {
        st[j] = __shfl_sync(0xffffffffu, (g & 1) ? c0[0][2 * j + 1] + c0[1][2 * j + 1] : c0[0][2 * j] + c0[1][2 * j], (lane & 28) | (g >> 1));
        st[2 + j] = __shfl_sync(0xffffffffu, (g & 1) ? c1[0][2 * j + 1] + c1[1][2 * j + 1] : c1[0][2 * j] + c1[1][2 * j], (lane & 28) | (g >> 1));
      }
      named_arrive(8, 384);
      asm volatile("{\n.reg .pred q;\nsetp.ne.u32 q, %3, 0;\n@q st.shared.v2.f32 [%0], {%1,%2};\n@q bar.arrive 9, 160;\n}"
                   :: "r"(base + OFF_LN + ((t & 1) * 8 + g) * 8), "f"((t & 1) ? st[3] : st[1]), "f"((t & 1) ? st[2] : st[0]), "r"((uint32_t)((warp ^ 4) == hp)) : "memory");
      ok = mbar_try(bars + B_KV, 0);
      LnC l0, l1;
      float eps = 1e-5f;
#pragma unroll 1
      do {
        l0 = ln_consts(st[1], st[0], eps); l1 = ln_consts(st[3], st[2], eps);
#pragma unroll
        for (int k = 0; k < PRE * 16; k++) X[k >> 2][k & 3] = hsub2(X[k >> 2][k & 3], k & 2 ? l1.m : l0.m);
        eps += eps;
      } while ((l0.rl ^ l1.rl) == 4);
      OBS(tid == 32, 1);
      float ak[60], *av = ak + 32;
      const int pp_in = wg ? 6 : 0, pp_out = wg ? 0 : 6;
#pragma unroll
      for (int s = 0; s < 7; s++) {
#pragma unroll
        for (int k = s * 4; k < s * 4 + 4; k++) {
          if (s < PRE) {
            auto f = [&](uint32_t d, const LnC& l) { return hfma2(d, l.rh, hmul2(d, l.rl)); };
            const uint32_t y = f(X[k][1], l0);
            X[k][0] = f(X[k][0], l0); X[k][1] = f(X[k][2], l1); X[k][2] = y; X[k][3] = f(X[k][3], l1);
          } else {
            const uint32_t y = ln_apply(X[k][1], l0);
            X[k][0] = ln_apply(X[k][0], l0); X[k][1] = ln_apply(X[k][2], l1); X[k][2] = y; X[k][3] = ln_apply(X[k][3], l1);
          }
        }
        if (__builtin_expect(!ok, 0)) { mbar_wait(bars + B_KV + s * 8, 0); if (s == 6) mbar_wait(bars + B_WQ, 0); }
        if (s == 0) fresh(ak);
        if (s == 6) { wg_wait<0>(); if ((tid & 127) == 0) mbar_arrive(bars + B_EMPTY + 3 * 8); }
        OBS(KOBS && (tid & 127) == 0, 40 + wg * 32 + s);
        if (PPM == 2 ? (wg ? s < 6 : s > 1) : (wg || s)) named_sync(pp_in, 256);
        OBS(KOBS && (tid & 127) == 32, 48 + wg * 32 + s);
        OBS(tid == 64 && s == 0, 2);
        wg_fence();
#pragma unroll
        for (int k = 0; k < 4; k++) {
          wgmma_rs_n120<1>(ak, X[s * 4 + k], mkdesc(HI_SW128, dlo + s * 1024 + k * 128), (s | k) != 0);
        }
        wg_commit();
        if (s == 6) {
          fresh(aq);
#pragma unroll
          for (int k = 0; k < 4 * QA; k++) {
            if (k == 4 * QA - PQE) named_arrive(pp_out, 256);
            wgmma_rs_n56<1>(aq, X[k], mkdesc(HI_SW128, dlq + k * 128), k);
          }
          wg_commit();
        }
        if (s < 6 || PQE == 0) named_arrive_if(PPM != 2 || (wg ? s != 5 : s != 0), pp_out, 256);
        fence_code(s);
        OBS(KOBS && (tid & 127) == 64, 56 + wg * 32 + s);
        if (s < 6) ok = mbar_try(bars + B_KV + s * 8 + 8, 0);
        if (s == 5) ok &= mbar_try(bars + B_WQ, 0);
        OBS(tid == 64 && s == 5, 31);
        if (s > 0) wg_wait<1>();
        OBS(KOBS && (tid & 127) == 96, 64 + wg * 32 + s);
        if ((s == 2 || s == 3 || s == 5) && (tid & 127) == 0) mbar_arrive(bars + B_EMPTY + (s == 5 ? 2 : s - 2) * 8);
      }
      if ((tid & 127) == 0) mbar_arrive(bars + B_EMPTY + 4 * 8);
      OBS(tid == 32, 3);
      {
        const uint32_t kst = base + OFF_K + (2 + (warp ^ 4) * 2 + (mi & 1)) * 1792 + (mi >> 1) * 896 + r8 * 16;
#pragma unroll
        for (int n = 0; n < 7; n++)
          stsm4(kst + n * 128, pack2(ak[n * 4], ak[n * 4 + 1]), pack2(ak[n * 4 + 2], ak[n * 4 + 3]), pack2(av[n * 4], av[n * 4 + 1]), pack2(av[n * 4 + 2], av[n * 4 + 3]));
        named_arrive_if(warp == 3, 1, 96);
      }
      OBS(tid == 96, 32); OBS(tid == 224, 34);
      wg_wait<0>();
      if ((tid & 127) == 0) mbar_arrive(bars + B_EMPTY + 5 * 8);
      if (!WQM) mbar_wait(bars + B_WQ2, 0);
    }
    const unsigned short *bp1 = (const unsigned short*)p.b1 + (g1 ? ft * 64 : 0) + w4 * 16 + g, *bp2 = (const unsigned short*)p.b2 + mt * 64 + w4 * 16 + g;
    const uint32_t braw[4] = {__ldg(bp1), __ldg(bp1 + 8), __ldg(bp2), __ldg(bp2 + 8)};
    auto q_rest = [&]() {
      wg_fence();
#pragma unroll
      for (int s = QA; s < 7; s++) {
        if (WQM && s == WQA) { mbar_wait(bars + B_WQ2, 0); wg_fence(); }
#pragma unroll
        for (int k = s * 4; k < s * 4 + 4; k++) wgmma_rs_n56<1>(aq, X[k], mkdesc(HI_SW128, dlq + k * 128), 1);
        wg_commit();
        if (s == 5) { wg_wait<2>(); if ((tid & 127) == 0) mbar_arrive(bars + B_EMPTY + 6 * 8); }
      }
    };
    uint32_t Q[4][4];
    auto q_pack = [&]() {
#pragma unroll
      for (int n = 0; n < 14; n++) { const int m = n + 2 * (n > 7); Q[m >> 2][m & 3] = pack2(aq[n * 2], aq[n * 2 + 1]); }
#pragma unroll
      for (int h = 0; h < 2; h++) { Q[2][h] = t < 2 ? 0u : Q[1][2 + h]; Q[1][2 + h] = t < 2 ? Q[1][2 + h] : 0u; }
    };
    float acc[56];
    auto ai = [](int p) { return p < 4 ? 48 + (p & 1) * 4 + (p & 2) : (p - 4) * 4; };
    uint32_t xch, ts, tl;
    unsigned char *ug, *ur, *uc, *outp, *outq;
    auto setup_u = [&]() {
      xch = pin(base + OFF_K + (tid & 127) * 16);
      ug = pin(scr + (d1 * HU_T + 32 + ft) * BT + w4 * 3584 + lane * 4 + wg * 1792);
      const int n = wg ? min(lane, 11) : lane & 15;
      ur = pin(ug + (n < 14 ? n * 128 : (n - 2) * 128 + 1792));
      uc = pin(scr + CNT_OFF + (C_U + d1 + (lane & (UREP - 1)) * 4) * 128);
    };
    auto setup_out = [&]() {
      const uint32_t tb = base + OFF_K + 6144 + warp * 2560;
      ts = pin(tb + mi * 160 + r8 * 16); tl = pin(tb + t * 160 + g * 16);
      unsigned char* o = p.out + (mt * 64 + w4 * 16 + g) * 896 + dt * 224;
      outp = pin(o + th * 7168 + t * 16); outq = pin(o + (t >> 1) * 7168 + 192 + (t & 1) * 16);
    };
    auto give = [&](const float (&a)[56], int id) {
#pragma unroll
      for (int i = 0; i < 48; i += 16) sts128(xch + i * 128, pack2(a[i + 2], a[i + 3]), pack2(a[i + 6], a[i + 7]), pack2(a[i + 10], a[i + 11]), pack2(a[i + 14], a[i + 15]));
      named_arrive(id, 256);
    };
    auto take = [&](uint32_t (&r)[12], int id) {
      named_sync(id, 256);
#pragma unroll
      for (int i = 0; i < 3; i++) { const uint4 v = lds128(xch + i * 2048); r[i * 4] = v.x; r[i * 4 + 1] = v.y; r[i * 4 + 2] = v.z; r[i * 4 + 3] = v.w; }
    };
    float hv[32];
    auto keep_h = [&](int i) {
      const float hb0 = 0.5f * bf_lo(braw[i]), hb1 = 0.5f * bf_lo(braw[i + 1]);
#pragma unroll
      for (int j = 0; j < 32; j++) hv[j] = fmaf(acc[ai(j >> 1) + (j & 1)], 0.5f, j >= 4 && j < 8 ? hb1 : hb0);
    };
    auto take_h = [&](int i) {
      const float hb1 = 0.5f * bf_lo(braw[i + 1]);
      uint32_t r[12];
      take(r, 5);
#pragma unroll
      for (int j = 0; j < 12; j++) { hv[8 + 2 * j] = fmaf(bf_lo(r[j]), 0.5f, hb1); hv[9 + 2 * j] = fmaf(bf_hi(r[j]), 0.5f, hb1); }
    };
    uint4 Xr[4];
    auto get_x = [&]() {
      const uint32_t xr = base + OFF_Q + (w4 * 16 + g) * 224;
      mbar_wait(bars + B_RES, 0);
      Xr[0] = lds128(xr + (t >> 1) * 1792 + 192 + (t & 1) * 16);
#pragma unroll
      for (int i = 1; i < 4; i++) Xr[i] = lds128(xr + th * 1792 + t * 16 + (i - 1) * 64);
    };
    auto gelu = [&](int j) {
      const float h0 = hv[2 * j], h1 = hv[2 * j + 1];
      const float t0 = tanh_fast(h0 * fmaf(h0 * h0, 0.2854192648f, 1.5957691216f)), t1 = tanh_fast(h1 * fmaf(h1 * h1, 0.2854192648f, 1.5957691216f));
      stg32(ug + (ai(j) & 2) * 896 + (ai(j) >> 2) * 128, pack2(fmaf(h0, t0, h0), fmaf(h1, t1, h1)));
    };
    uint32_t Sv[16];
    auto gate = [&](int i) {
      uint32_t R[4];
#pragma unroll
      for (int q = 0; q < 4; q++) {
        const int j = i * 4 + q;
        const float h0 = hv[2 * j], h1 = hv[2 * j + 1];
        R[q] = hmul2(Sv[j], pack2(fmaf(h0, tanh_fast(h0), h0), fmaf(h1, tanh_fast(h1), h1)));
      }
      stsm4(ts + i * 640, R[0], R[1], R[2], R[3]);
    };
    auto leave = [&](int i) {
      __syncwarp();
      const uint4 v = lds128(tl + i * 640), x = Xr[i];
      stg128(i ? outp + (i - 1) * 64 : outq, hadd2(x.x, v.x), hadd2(x.y, v.y), hadd2(x.z, v.z), hadd2(x.w, v.w));
    };
    if (wg == 0) {
      named_sync(0, 256);
      OBS(tid == 96, 14);
      q_rest();
      named_arrive(6, 256);
      wg_wait<0>();
      if (tid == 0) mbar_arrive(bars + B_EMPTY + 7 * 8);
      q_pack();
      const uint32_t qst = base + OFF_Q + 8192 + (mi >> 1) * 1024 + (w4 * 16 + (mi & 1) * 8 + r8) * 16;
#pragma unroll
      for (int n = 0; n < 4; n++) stsm4(qst + n * 2048, Q[n][0], Q[n][1], Q[n][2], Q[n][3]);
      smem_fence();
      named_arrive(7, 256);
      OBS(tid == 32, 5);
      fresh(acc);
      setup_u();
      if (g1) {
        mbar_wait(bars, 0); mbar_wait(bars + 8, 0);
        if (TS) {
          const uint32_t tg = lds64(bars + B_T0).x;
          while ((int)(clock() - tg) < 0);
        }
        named_sync(0, 256);
        gemm_issue<1>(acc, base >> 4, base >> 4, 0);
        OBS(tid == 0, 20);
        gemm_loop<1>(acc, base, 1, 32, rel, 40, 1, tid == 32 ? J1 : tid == 64 ? J2 : tid == 96 ? J3 : -1, bars + B_GATE - 8 + w4 * 8);
        mbar_wait(bars + B_ATT, 0);
        wg_wait<0>();
        OBS(tid == 0, 21);
        give(acc, 5);
        mbar_arrive_if(rel, bars + B_EMPTY + 7 * 8);
        fence_code(30);
        keep_h(0);
#pragma unroll
        for (int j = 0; j < 16; j++) { gelu(j); if (j % GCH == GCH - 1 && j < 15) fence_code(8 + j); }
        if (RB & 16) settle(probe(ur));
        if (w4) named_arrive(2, 256);
        else { named_sync(2, 256); asm volatile("{\n.reg .pred q;\nsetp.lt.u32 q, %1, %2;\n@q red.relaxed.gpu.global.add.u32 [%0], 1;\n}" :: "l"(uc), "r"(lane), "n"(UREP) : "memory"); OBS(tid == 0, 9); }
      } else {
        if (lane == 0 && w4) mbar_arrive(bars + B_GATE - 8 + w4 * 8);
      }
      setup_out();
      if (!RESP) get_x();
      uint32_t r[12];
      take(r, 3);
#pragma unroll
      for (int j = 0; j < 16; j++) Sv[j] = r[j < 4 ? 0 : j - 4];
      asm volatile("" :: "r"(r[0]), "r"(r[11]) : "memory");
      named_arrive(10, 256);
      if (RESP) get_x();
      take_h(2);
    } else {
      const uint32_t dq = ((base + OFF_Q) >> 4) + (64u << 16), dk = (base + OFF_K) >> 4;
      const bool odd = g & 1, early = 2 * t + (g & 1) > g;
      uint32_t selA[5], selB[4];
#pragma unroll
      for (int j = 0; j < 5; j++) { selA[j] = j == w4 + (early ? 0 : 1) ? (odd ? 0x1044u : 0x4410u) : 0x4444u; }
#pragma unroll
      for (int j = 0; j < 4; j++) { selB[j] = j == w4 ? (odd ? 0x3244u : 0x4432u) : 0x4444u; }
      float Sc[2][40], Op[2][2][16];
      uint32_t A[2][5][4];
      auto scores = [&](int T) {
        fresh(Sc[0]); fresh(Sc[1]);
#pragma unroll
        for (int k = 0; k < 2; k++) {
#pragma unroll
          for (int hh = 0; hh < 2; hh++)
            if (T) wgmma_n80<0, 0>(Sc[hh], mkdesc(8, dq + 512 + hh * 256 + k * 128), mkdesc(112, dk + (8u << 16) + 896 + hh * 24 + k * 16), k);
            else wgmma_rs_n80<0>(Sc[hh], Q[hh * 2 + k], mkdesc(112, dk + (8u << 16) + hh * 24 + k * 16), k);
        }
      };
      auto softmax = [&](int T) {
        uint32_t L[2][2];
        auto pick = [&](int w) {
#pragma unroll
          for (int hh = 0; hh < 2; hh++) {
            const float* q = Sc[hh] + w * 8;
            auto at = [&](int i) { return odd ? q[i + 1] : q[i]; };
            L[hh][0] = pack2(early ? at(0) : at(8), early ? at(6) : at(14)); L[hh][1] = pack2(at(4), at(10));
          }
          asm volatile("" ::: "memory");
        };
        if (w4 & 2) { if (w4 & 1) pick(3); else pick(2); } else { if (w4 & 1) pick(1); else pick(0); }
#pragma unroll
        for (int hh = 0; hh < 2; hh++) {
          uint32_t a = hfma2(L[hh][0], SC_HI, hmul2(L[hh][0], SC_LO)), c = hfma2(L[hh][1], SC_HI, hmul2(L[hh][1], SC_LO));
          if (T == 0 && w4 == 0 && rb == 0) { if (early) a = 0xce6ece6eu; c = (c & 0xffff0000u) | 0xce6eu; }
          uint32_t mx = hmax2(a, c);
          mx = hmax2(mx, __shfl_xor_sync(0xffffffffu, mx, 1));
          mx = hmax2(mx, __shfl_xor_sync(0xffffffffu, mx, 2));
          uint32_t pp[2];
#pragma unroll
          for (int h = 0; h < 2; h++) {
            const float m = h ? bf_hi(mx) : bf_lo(mx);
            const float p0 = ex2_fast(((h ? bf_hi(a) : bf_lo(a)) - m) * LOG2E), p1 = ex2_fast(((h ? bf_hi(c) : bf_lo(c)) - m) * LOG2E);
            float sm = p0 + p1;
            sm += __shfl_xor_sync(0xffffffffu, sm, 1);
            sm += __shfl_xor_sync(0xffffffffu, sm, 2);
            const float inv = rcp_fast(sm);
            pp[h] = pack2(p0 * inv, p1 * inv);
          }
#pragma unroll
          for (int j = 0; j < 5; j++) {
            A[hh][j][0] = place(pp[0], selA[j]); A[hh][j][1] = j ? place(pp[1], selB[j ? j - 1 : 0]) : 0u;
            A[hh][j][2] = j < 4 ? place(pp[0], selB[j & 3]) : 0u; A[hh][j][3] = place(pp[1], selA[j]);
          }
        }
      };
      auto values = [&](int T) {
        fresh(Op[T][0]); fresh(Op[T][1]);
#pragma unroll
        for (int j = 0; j < 5; j++)
#pragma unroll
          for (int hh = 0; hh < 2; hh++) {
            wgmma_rs_n32<1>(Op[T][hh], A[hh][j], mkdesc(8, dk + (112u << 16) + 56 + T * 896 + hh * 24 + j * 224), j);
          }
        wg_commit();
      };
      uint32_t Ob[2][14];
      auto pack = [&](int T) {
        const float (&O)[2][16] = Op[T];
#pragma unroll
        for (int n = 0; n < 7; n++)
#pragma unroll
          for (int h = 0; h < 2; h++) {
            if (n < 3) Ob[T][n * 2 + h] = pack2(O[0][n * 4 + 2 * h], O[0][n * 4 + 2 * h + 1]);
            else if (n == 3) Ob[T][n * 2 + h] = pack2(t < 2 ? O[0][12 + 2 * h] : O[1][2 * h], t < 2 ? O[0][13 + 2 * h] : O[1][2 * h + 1]);
            else Ob[T][n * 2 + h] = pack2(O[1][(n - 3) * 4 + 2 * h], O[1][(n - 3) * 4 + 2 * h + 1]);
          }
      };
      smem_fence();
      named_sync(6, 256);
      OBS(tid == 224, 26);
      q_rest();
      named_sync(7, 256);
      wg_fence();
      scores(1);
      wg_commit();
      named_arrive_if(g1, 0, 256);
      wg_wait<2>();
      if (tid == 128) mbar_arrive(bars + B_EMPTY + 7 * 8);
      wg_wait<0>();
      OBS(tid == 160, 10);
      softmax(1);
      q_pack();
      OBS(tid == 160, 30);
      mbar_wait(bars + B_HALO, 0);
      OBS(tid == 160, 7);
      mbar_wait(bars + B_GATE, 0);
      wg_fence();
      scores(0);
      values(1);
      wg_wait<0>();
      OBS(tid == 160, 33);
      unsigned char* og = scr + O_OFF + rb * 2 * 57344 + hp * 7168 + w4 * 256 + lane * 4;
      uint32_t seen[6];
      auto put = [&](int T) {
#pragma unroll
        for (int n = 0; n < 14; n++) { stg32(og + T * 57344 + (n >> 1) * 1024 + (n & 1) * 128, Ob[T][n]); if (n == 5 || n == 11 || n == 13) seen[T * 3 + n / 6] = (RB & 8) ? probe(og + T * 57344 + ((n >> 1) - (n == 13 ? 0 : min(g, 2))) * 1024 + (t & 1) * 128) : 0;
          if (OSLEEP && n % OGRP == OGRP - 1) __nanosleep(OSLEEP); }
      };
      if (OMODE == 1) { pack(1); put(1); }
      softmax(0);
      if (OMODE == 2) { pack(1); put(1); }
      mbar_wait(bars + B_GATE + 8, 0);
      wg_fence();
      values(0);
      if (OMODE == 3) { pack(1); put(1); }
      wg_wait<0>();
      OBS(tid == 160, 35);
      named_sync(11, 128);
      if (tid == 160) mbar_arrive(bars + B_ATT);
      if (OMODE == 0) pack(1);
      pack(0);
      if (J3 > J2) mbar_wait(bars + B_GATE + 16, 0);
      if (OMODE == 0) put(1);
      put(0);
      OBS(tid == 160, 28);
      if (RB & 8) settle(seen[0] ^ seen[1] ^ seen[2] ^ seen[3] ^ seen[4] ^ seen[5]);
      named_sync(11, 128);
      if (warp == 4) publish(scr, C_O + rb);
      OBS(tid == 160, 8);
      setup_u(); setup_out();
      float as[56];
      uint32_t uv = 0;
      if (g1) {
        take_h(0);
        if (!RESP && XE) get_x();
#pragma unroll
        for (int j = 4; j < OPJ; j++) { gelu(j); if (j % GCH == GCH - 1 && j < OPJ - 1) fence_code(40 + j); }
        if ((RB & 16) && !UO) settle(probe(ur));
        if ((RB & 16) && UO) uv = probe(ur);
        else named_arrive(2, 256);
      } else if (!RESP && XE) get_x();
      fresh(as);
      gemm_stage<0>(as, base, 0, 0);
      OBS(tid == 128, 22);
      if ((RB & 16) && UO) { settle(uv); named_arrive_if(g1, 2, 256); }
      gemm_loop<0>(as, base, 1, 7, rel, 104);
      fresh(acc);
      if (SEARLY) { wg_wait<0>(); mbar_arrive_if(rel, bars + B_EMPTY + 6 * 8); give(as, 3); if (!RESP && !XE) get_x(); }
      gemm_stage<1>(acc, base, 7, 0);
      OBS(tid == 128, 24);
      if (!SEARLY) { wg_wait<1>(); mbar_arrive_if(rel, bars + B_EMPTY + 6 * 8); give(as, 3); }
#pragma unroll
      for (int j = 0; j < 16; j++) Sv[j] = pack2(as[ai(j)], as[ai(j) + 1]);
      gemm_loop<1, NX>(acc, base, 8, 35, rel, 65);
      if (RESP) get_x();
      named_sync(10, 256);
      wg_wait<0>();
      OBS(tid == 128, 25);
      give(acc, 5);
      fence_code(31);
      keep_h(2);
      gate(0); leave(0);
    }
    {
#pragma unroll
      for (int i = 1; i < 4; i++) { gate(i); leave(i); }
      OBS(tid == 128, 27);
    }
  }
}

typedef CUresult (*EncFn)(CUtensorMap*, CUtensorMapDataType, cuuint32_t, void*, const cuuint64_t*, const cuuint64_t*, const cuuint32_t*,
                          const cuuint32_t*, CUtensorMapInterleave, CUtensorMapSwizzle, CUtensorMapL2promotion, CUtensorMapFloatOOBfill);
void enc(EncFn f, CUtensorMap* m, const void* ptr, cuuint64_t d0, cuuint64_t d1, cuuint64_t d2, cuuint64_t s1, cuuint64_t s2, cuuint32_t b1, cuuint32_t b2, cuuint32_t b0 = 64) {
  const cuuint64_t gd[3] = {d0, d1, d2}, gs[2] = {s1 * 2, s2 * 2};
  const cuuint32_t bx[3] = {b0, b1, b2}, es[3] = {1, 1, 1};
  f(m, CU_TENSOR_MAP_DATA_TYPE_BFLOAT16, 3, (void*)ptr, gd, gs, bx, es, CU_TENSOR_MAP_INTERLEAVE_NONE, b0 == 64 ? CU_TENSOR_MAP_SWIZZLE_128B : CU_TENSOR_MAP_SWIZZLE_NONE,
    CU_TENSOR_MAP_L2_PROMOTION_L2_128B, CU_TENSOR_MAP_FLOAT_OOB_FILL_NONE);
}
}

extern "C" void kernel_launch(void* const* d_in, const int* in_sizes, int n_in, void* d_out, int out_size) {
  (void)in_sizes; (void)n_in; (void)out_size;
  void* fp = nullptr;
  cudaDriverEntryPointQueryResult qr;
  cudaGetDriverEntryPoint("cuTensorMapEncodeTiled", &fp, cudaEnableDefault, &qr);
  EncFn f = (EncFn)fp;
  CUtensorMap m_x, m_wkv, m_wq, m_w1, m_w2, m_res;
  void* scr = nullptr;
  cudaGetSymbolAddress(&scr, g_scr);
  enc(f, &m_x, d_in[0], D_, S_, 1, D_, D_, 128 >> XSPLIT, 1);
  enc(f, &m_wkv, d_in[1], D_, D_, 3, 3 * D_, D_, 64, 2);
  enc(f, &m_wq, d_in[1], D_, D_, 3, 3 * D_, D_, 64, 1);
  enc(f, &m_w1, d_in[4], F_, S_, 1, F_, F_, 64, 1);
  enc(f, &m_w2, d_in[6], S_, F_, 1, S_, S_, 64, 1);
  enc(f, &m_res, d_in[0], D_, S_, 1, D_, D_, 64, 1, 112);
  Params p;
  p.wqkv = (const unsigned char*)d_in[1]; p.wo = (const unsigned char*)d_in[2];
  p.w1 = (const unsigned char*)d_in[4]; p.b1 = (const unsigned char*)d_in[5];
  p.w2 = (const unsigned char*)d_in[6]; p.b2 = (const unsigned char*)d_in[7];
  p.out = (unsigned char*)d_out; p.scr = (unsigned char*)scr;
  cudaFuncSetAttribute(fused_kernel, cudaFuncAttributeMaxDynamicSharedMemorySize, SMEM_BYTES);
  fused_kernel<<<128, NTHREADS, SMEM_BYTES, cudaStreamPerThread>>>(m_x, m_wkv, m_wq, m_w1, m_w2, m_res, p);
}
```

```cpp
#include <cuda_runtime.h>
#include <cuda.h>
#include <cuda_bf16.h>
#include <stdint.h>

template<int TA, int TB> __device__ __forceinline__ void wgmma_n112(float (&d)[56], uint64_t da, uint64_t db, int sc) {
  asm volatile("{\n.reg .pred p;\nsetp.ne.b32 p, %58, 0;\n"
    "wgmma.mma_async.sync.aligned.m64n112k16.f32.bf16.bf16 {%0, %1, %2, %3, %4, %5, %6, %7, %8, %9, %10, %11, %12, %13, %14, %15, %16, %17, %18, %19, %20, %21, %22, %23, %24, %25, %26, %27, %28, %29, %30, %31, %32, %33, %34, %35, %36, %37, %38, %39, %40, %41, %42, %43, %44, %45, %46, %47, %48, %49, %50, %51, %52, %53, %54, %55}, %56, %57, p, 1, 1, %59, %60;\n}\n"
    : "+f"(d[0]), "+f"(d[1]), "+f"(d[2]), "+f"(d[3]), "+f"(d[4]), "+f"(d[5]), "+f"(d[6]), "+f"(d[7]), "+f"(d[8]), "+f"(d[9]), "+f"(d[10]), "+f"(d[11]), "+f"(d[12]), "+f"(d[13]), "+f"(d[14]), "+f"(d[15]), "+f"(d[16]), "+f"(d[17]), "+f"(d[18]), "+f"(d[19]), "+f"(d[20]), "+f"(d[21]), "+f"(d[22]), "+f"(d[23]), "+f"(d[24]), "+f"(d[25]), "+f"(d[26]), "+f"(d[27]), "+f"(d[28]), "+f"(d[29]), "+f"(d[30]), "+f"(d[31]), "+f"(d[32]), "+f"(d[33]), "+f"(d[34]), "+f"(d[35]), "+f"(d[36]), "+f"(d[37]), "+f"(d[38]), "+f"(d[39]), "+f"(d[40]), "+f"(d[41]), "+f"(d[42]), "+f"(d[43]), "+f"(d[44]), "+f"(d[45]), "+f"(d[46]), "+f"(d[47]), "+f"(d[48]), "+f"(d[49]), "+f"(d[50]), "+f"(d[51]), "+f"(d[52]), "+f"(d[53]), "+f"(d[54]), "+f"(d[55])
    : "l"(da), "l"(db), "r"(sc), "n"(TA), "n"(TB));
}

template<int TA, int TB> __device__ __forceinline__ void wgmma_n80(float (&d)[40], uint64_t da, uint64_t db, int sc) {
  asm volatile("{\n.reg .pred p;\nsetp.ne.b32 p, %42, 0;\n"
    "wgmma.mma_async.sync.aligned.m64n80k16.f32.bf16.bf16 {%0, %1, %2, %3, %4, %5, %6, %7, %8, %9, %10, %11, %12, %13, %14, %15, %16, %17, %18, %19, %20, %21, %22, %23, %24, %25, %26, %27, %28, %29, %30, %31, %32, %33, %34, %35, %36, %37, %38, %39}, %40, %41, p, 1, 1, %43, %44;\n}\n"
    : "+f"(d[0]), "+f"(d[1]), "+f"(d[2]), "+f"(d[3]), "+f"(d[4]), "+f"(d[5]), "+f"(d[6]), "+f"(d[7]), "+f"(d[8]), "+f"(d[9]), "+f"(d[10]), "+f"(d[11]), "+f"(d[12]), "+f"(d[13]), "+f"(d[14]), "+f"(d[15]), "+f"(d[16]), "+f"(d[17]), "+f"(d[18]), "+f"(d[19]), "+f"(d[20]), "+f"(d[21]), "+f"(d[22]), "+f"(d[23]), "+f"(d[24]), "+f"(d[25]), "+f"(d[26]), "+f"(d[27]), "+f"(d[28]), "+f"(d[29]), "+f"(d[30]), "+f"(d[31]), "+f"(d[32]), "+f"(d[33]), "+f"(d[34]), "+f"(d[35]), "+f"(d[36]), "+f"(d[37]), "+f"(d[38]), "+f"(d[39])
    : "l"(da), "l"(db), "r"(sc), "n"(TA), "n"(TB));
}

template<int TB> __device__ __forceinline__ void wgmma_rs_n120(float (&d)[60], const uint32_t (&a)[4], uint64_t db, int sc) {
  asm volatile("{\n.reg .pred p;\nsetp.ne.b32 p, %65, 0;\n"
    "wgmma.mma_async.sync.aligned.m64n120k16.f32.bf16.bf16 {%0, %1, %2, %3, %4, %5, %6, %7, %8, %9, %10, %11, %12, %13, %14, %15, %16, %17, %18, %19, %20, %21, %22, %23, %24, %25, %26, %27, %28, %29, %30, %31, %32, %33, %34, %35, %36, %37, %38, %39, %40, %41, %42, %43, %44, %45, %46, %47, %48, %49, %50, %51, %52, %53, %54, %55, %56, %57, %58, %59}, {%60, %61, %62, %63}, %64, p, 1, 1, %66;\n}\n"
    : "+f"(d[0]), "+f"(d[1]), "+f"(d[2]), "+f"(d[3]), "+f"(d[4]), "+f"(d[5]), "+f"(d[6]), "+f"(d[7]), "+f"(d[8]), "+f"(d[9]), "+f"(d[10]), "+f"(d[11]), "+f"(d[12]), "+f"(d[13]), "+f"(d[14]), "+f"(d[15]), "+f"(d[16]), "+f"(d[17]), "+f"(d[18]), "+f"(d[19]), "+f"(d[20]), "+f"(d[21]), "+f"(d[22]), "+f"(d[23]), "+f"(d[24]), "+f"(d[25]), "+f"(d[26]), "+f"(d[27]), "+f"(d[28]), "+f"(d[29]), "+f"(d[30]), "+f"(d[31]), "+f"(d[32]), "+f"(d[33]), "+f"(d[34]), "+f"(d[35]), "+f"(d[36]), "+f"(d[37]), "+f"(d[38]), "+f"(d[39]), "+f"(d[40]), "+f"(d[41]), "+f"(d[42]), "+f"(d[43]), "+f"(d[44]), "+f"(d[45]), "+f"(d[46]), "+f"(d[47]), "+f"(d[48]), "+f"(d[49]), "+f"(d[50]), "+f"(d[51]), "+f"(d[52]), "+f"(d[53]), "+f"(d[54]), "+f"(d[55]), "+f"(d[56]), "+f"(d[57]), "+f"(d[58]), "+f"(d[59])
    : "r"(a[0]), "r"(a[1]), "r"(a[2]), "r"(a[3]), "l"(db), "r"(sc), "n"(TB));
}

template<int TB> __device__ __forceinline__ void wgmma_rs_n56(float (&d)[28], const uint32_t (&a)[4], uint64_t db, int sc) {
  asm volatile("{\n.reg .pred p;\nsetp.ne.b32 p, %33, 0;\n"
    "wgmma.mma_async.sync.aligned.m64n56k16.f32.bf16.bf16 {%0, %1, %2, %3, %4, %5, %6, %7, %8, %9, %10, %11, %12, %13, %14, %15, %16, %17, %18, %19, %20, %21, %22, %23, %24, %25, %26, %27}, {%28, %29, %30, %31}, %32, p, 1, 1, %34;\n}\n"
    : "+f"(d[0]), "+f"(d[1]), "+f"(d[2]), "+f"(d[3]), "+f"(d[4]), "+f"(d[5]), "+f"(d[6]), "+f"(d[7]), "+f"(d[8]), "+f"(d[9]), "+f"(d[10]), "+f"(d[11]), "+f"(d[12]), "+f"(d[13]), "+f"(d[14]), "+f"(d[15]), "+f"(d[16]), "+f"(d[17]), "+f"(d[18]), "+f"(d[19]), "+f"(d[20]), "+f"(d[21]), "+f"(d[22]), "+f"(d[23]), "+f"(d[24]), "+f"(d[25]), "+f"(d[26]), "+f"(d[27])
    : "r"(a[0]), "r"(a[1]), "r"(a[2]), "r"(a[3]), "l"(db), "r"(sc), "n"(TB));
}

template<int TB> __device__ __forceinline__ void wgmma_rs_n32(float (&d)[16], const uint32_t (&a)[4], uint64_t db, int sc) {
  asm volatile("{\n.reg .pred p;\nsetp.ne.b32 p, %21, 0;\n"
    "wgmma.mma_async.sync.aligned.m64n32k16.f32.bf16.bf16 {%0, %1, %2, %3, %4, %5, %6, %7, %8, %9, %10, %11, %12, %13, %14, %15}, {%16, %17, %18, %19}, %20, p, 1, 1, %22;\n}\n"
    : "+f"(d[0]), "+f"(d[1]), "+f"(d[2]), "+f"(d[3]), "+f"(d[4]), "+f"(d[5]), "+f"(d[6]), "+f"(d[7]), "+f"(d[8]), "+f"(d[9]), "+f"(d[10]), "+f"(d[11]), "+f"(d[12]), "+f"(d[13]), "+f"(d[14]), "+f"(d[15])
    : "r"(a[0]), "r"(a[1]), "r"(a[2]), "r"(a[3]), "l"(db), "r"(sc), "n"(TB));
}

template<int TB> __device__ __forceinline__ void wgmma_rs_n80(float (&d)[40], const uint32_t (&a)[4], uint64_t db, int sc) {
  asm volatile("{\n.reg .pred p;\nsetp.ne.b32 p, %45, 0;\n"
    "wgmma.mma_async.sync.aligned.m64n80k16.f32.bf16.bf16 {%0, %1, %2, %3, %4, %5, %6, %7, %8, %9, %10, %11, %12, %13, %14, %15, %16, %17, %18, %19, %20, %21, %22, %23, %24, %25, %26, %27, %28, %29, %30, %31, %32, %33, %34, %35, %36, %37, %38, %39}, {%40, %41, %42, %43}, %44, p, 1, 1, %46;\n}\n"
    : "+f"(d[0]), "+f"(d[1]), "+f"(d[2]), "+f"(d[3]), "+f"(d[4]), "+f"(d[5]), "+f"(d[6]), "+f"(d[7]), "+f"(d[8]), "+f"(d[9]), "+f"(d[10]), "+f"(d[11]), "+f"(d[12]), "+f"(d[13]), "+f"(d[14]), "+f"(d[15]), "+f"(d[16]), "+f"(d[17]), "+f"(d[18]), "+f"(d[19]), "+f"(d[20]), "+f"(d[21]), "+f"(d[22]), "+f"(d[23]), "+f"(d[24]), "+f"(d[25]), "+f"(d[26]), "+f"(d[27]), "+f"(d[28]), "+f"(d[29]), "+f"(d[30]), "+f"(d[31]), "+f"(d[32]), "+f"(d[33]), "+f"(d[34]), "+f"(d[35]), "+f"(d[36]), "+f"(d[37]), "+f"(d[38]), "+f"(d[39])
    : "r"(a[0]), "r"(a[1]), "r"(a[2]), "r"(a[3]), "l"(db), "r"(sc), "n"(TB));
}

namespace {
constexpr int S_ = 2048, D_ = 448, F_ = 1792;
constexpr int NSLOT = 8, SLOT = 22528;
constexpr int OFF_X = 7 * 16384;
constexpr int OFF_WQ = 8 * 16384;
constexpr int OFF_Q = NSLOT * SLOT;
constexpr int OFF_K = OFF_Q + 16384;
constexpr int OFF_XW = OFF_K + 6144;
constexpr int OFF_BAR = 14 * 16384;
constexpr int OFF_LN = OFF_BAR + 512;
constexpr int OFF_OBS = OFF_BAR + 640;
constexpr int SMEM_BYTES = OFF_OBS + 1024;
#define PACE0 0
#define PACE1 540
#define PACE2 650
#define WARM 3
#define NW0 2
#define HEAT 1
#define T0 0
#define TP 250
#define J3 0
#define J1 9
#define J2 14
#define EARLY 4
#define PPE 4
#define PQE 2
#define LANDOBS 0
#define TRUNC 0
#define KOBS 0
#define PRE 1
#define QA 2
#define HEARLY 0
#define OSLEEP 20
#define PROBE 1
#define WOP 0
#define OGRP 2
#define OMODE 3
#define GCH 4
#define GLAG 2
#define GSLOW 0
#define RH 32
#define NOST 0
#define GOBS 0
#define HP 0
#define OPP 0
#define STAG 0
#define RESP 0
#define XE 1
#define NX 0
#define XS 15
#define XT 9
#define NPRE 1
#define U0 0
#define ALL4 0
#define UREP 1
#define TS 3170
#define PPM 1
#define WPF 7
#define XSPLIT 1
#define XK 1
#define TAG 1
#define HWAIT 300
#define RB 31
#define UO 0
#define FSM 1
#define XP 0
#define HREP 1
#define HSL 200
#define WOW 3
#define WQA 4
#define WQC 0
#define WQW 3
#define HNAP 0
#define HL 1
#define WQS 0
#define WQM 0
#define EPO 4
#define OHOLD 0
#define UPH 1
#define UCH 7
#define U2W 0
#define U2S 0
#define OGAP 0
#define OLAST 0
#define MU 0
#define P2 224
#define UP 170
#define POLL "relaxed"
#define OPJ 16
#define SEARLY 0
#define EXACT 0
#define SOBS 0
#define FREQ 0
#define OBS(c, i) do {} while (0)
#define OBSG(c, i, j) do {} while (0)
constexpr int NTHREADS = 384;
constexpr float SCALE = 0.18898223650461361f, LOG2E = 1.4426950408889634f;
constexpr uint32_t SC_HI = 0x3e423e42u, SC_LO = 0xb9f7b9f7u;
constexpr int BT = 14336;

constexpr int HU_T = 67;
constexpr int O_OFF = 4 * HU_T * BT;
constexpr int HALO_OFF = O_OFF + 32 * 7 * 8192;
constexpr int CNT_OFF = HALO_OFF + 128 * 3584;
constexpr int SCR_BYTES = CNT_OFF + 193 * 128;
constexpr int C_WO = 0, C_TK = 1, C_U = 160, C_O = 8, C_H = 176, C_HALO = 32, C_EPOCH = EPO ? C_H : 192;
__device__ __align__(1024) unsigned char g_scr[SCR_BYTES];

__device__ __forceinline__ uint32_t smem_u32(const void* p) { return (uint32_t)__cvta_generic_to_shared(p); }
__device__ __forceinline__ void mbar_init(uint32_t bar, uint32_t cnt) { asm volatile("mbarrier.init.shared::cta.b64 [%0], %1;" :: "r"(bar), "r"(cnt)); }
__device__ __forceinline__ void mbar_expect_tx(uint32_t bar, uint32_t bytes) { asm volatile("mbarrier.arrive.expect_tx.shared::cta.b64 _, [%0], %1;" :: "r"(bar), "r"(bytes) : "memory"); }
__device__ __forceinline__ void mbar_arrive_if(uint32_t c, uint32_t bar) { asm volatile("{\n.reg .pred q;\nsetp.ne.u32 q, %1, 0;\n@q mbarrier.arrive.shared::cta.b64 _, [%0];\n}" :: "r"(bar), "r"(c) : "memory"); }
__device__ __forceinline__ void mbar_arrive(uint32_t bar) { asm volatile("mbarrier.arrive.shared::cta.b64 _, [%0];" :: "r"(bar) : "memory"); }
__device__ __forceinline__ void mbar_wait(uint32_t bar, uint32_t parity) {
  asm volatile("{\n.reg .pred p;\n.reg .u32 n;\nmov.u32 n, 0;\nLAB_WAIT:\n"
               "mbarrier.try_wait.parity.shared::cta.b64 p, [%0], %1;\n@p bra DONE;\n"
               "add.u32 n, n, 1;\nsetp.lt.u32 p, n, 400000;\n@p bra LAB_WAIT;\ntrap;\nDONE:\n}" :: "r"(bar), "r"(parity) : "memory");
}
__device__ __forceinline__ uint32_t mbar_try(uint32_t bar, uint32_t parity) {
  uint32_t ok;
  asm volatile("{\n.reg .pred p;\nmbarrier.test_wait.parity.shared::cta.b64 p, [%1], %2;\nselp.u32 %0, 1, 0, p;\n}" : "=r"(ok) : "r"(bar), "r"(parity) : "memory");
  return ok;
}
__device__ __forceinline__ void tma3d(uint32_t dst, const CUtensorMap* m, int c0, int c1, int c2, uint32_t bar) {
  asm volatile("cp.async.bulk.tensor.3d.shared::cluster.global.mbarrier::complete_tx::bytes [%0], [%1, {%3, %4, %5}], [%2];"
               :: "r"(dst), "l"(m), "r"(bar), "r"(c0), "r"(c1), "r"(c2) : "memory");
}
__device__ __forceinline__ void bulk_g2s(uint32_t dst, const void* src, uint32_t bytes, uint32_t bar) {
  asm volatile("cp.async.bulk.shared::cluster.global.mbarrier::complete_tx::bytes [%0], [%1], %2, [%3];" :: "r"(dst), "l"(src), "r"(bytes), "r"(bar) : "memory");
}
__device__ __forceinline__ void wg_fence() { asm volatile("wgmma.fence.sync.aligned;" ::: "memory"); }
__device__ __forceinline__ void wg_commit() { asm volatile("wgmma.commit_group.sync.aligned;" ::: "memory"); }
template <int N> __device__ __forceinline__ void wg_wait() { asm volatile("wgmma.wait_group.sync.aligned %0;" :: "n"(N) : "memory"); }
__device__ __forceinline__ void smem_fence() { asm volatile("fence.proxy.async.shared::cta;" ::: "memory"); }
__device__ __forceinline__ void stg128(void* p, uint32_t a, uint32_t b, uint32_t c, uint32_t d) { asm volatile("st.global.v4.u32 [%0], {%1,%2,%3,%4};" :: "l"(p), "r"(a), "r"(b), "r"(c), "r"(d) : "memory"); }
__device__ __forceinline__ void stg32(void* p, uint32_t v) { asm volatile("st.global.u32 [%0], %1;" :: "l"(p), "r"(v) : "memory"); }
__device__ __forceinline__ uint4 ldg128(const void* p) { uint4 v; asm volatile("ld.global.nc.L1::no_allocate.v4.u32 {%0,%1,%2,%3}, [%4];" : "=r"(v.x), "=r"(v.y), "=r"(v.z), "=r"(v.w) : "l"(p)); return v; }
__device__ __forceinline__ void publish(unsigned char* scr, int i) {
  asm volatile("{\n.reg .pred q;\nelect.sync _|q, 0xffffffff;\n@q red.relaxed.gpu.global.inc.u32 [%0], 0xffffffff;\n}" :: "l"(scr + CNT_OFF + i * 128) : "memory");
}
__device__ __forceinline__ uint32_t probe(const unsigned char* p) { uint32_t v; asm volatile("ld.relaxed.gpu.global.u32 %0, [%1];" : "=r"(v) : "l"(p) : "memory"); return v; }
__device__ __forceinline__ void settle(uint32_t v) {
  asm volatile("{\n.reg .pred q;\nsetp.eq.u32 q, %0, 0x7fc1dead;\n@q st.volatile.shared.u32 [%1], %0;\n}" :: "r"(v), "r"(1024 + OFF_BAR + 376) : "memory");
  __syncwarp();
}
__device__ __forceinline__ uint32_t spin_ge(unsigned char* scr, int i, unsigned target) {
  uint32_t v;
  asm volatile("{\n.reg .pred p;\n.reg .u32 n;\nmov.u32 n, 0;\nLAB_SPIN:\n"
               "ld.relaxed.gpu.global.u32 %0, [%1];\nsetp.ge.u32 p, %0, %2;\nvote.sync.all.pred p, p, 0xffffffff;\n@p bra DONE;\n"
               "add.u32 n, n, 1;\nsetp.lt.u32 p, n, 4000000;\n@p bra LAB_SPIN;\ntrap;\nDONE:\n}" : "=&r"(v) : "l"(scr + CNT_OFF + i * 128), "r"(target) : "memory");
  return v;
}
__device__ __forceinline__ int lane_id() { int l; asm volatile("mov.u32 %0, %%laneid;" : "=r"(l)); return l; }
__device__ __forceinline__ uint32_t pin(uint32_t v) { return __shfl_xor_sync(0xffffffffu, v, blockIdx.y); }
__device__ __forceinline__ unsigned char* pin(unsigned char* p) { return (unsigned char*)(((uint64_t)pin((uint32_t)((uint64_t)p >> 32)) << 32) | pin((uint32_t)(uint64_t)p)); }
__device__ __forceinline__ uint32_t gtime() { uint32_t g; asm volatile("mov.u32 %0, %%globaltimer_lo;" : "=r"(g)); return g; }
__device__ __forceinline__ bool elect() {
  uint32_t r; asm volatile("{\n.reg .pred p;\nelect.sync _|p, 0xffffffff;\nselp.u32 %0, 1, 0, p;\n}" : "=r"(r)); return r != 0;
}
__device__ __forceinline__ uint4 lds128(uint32_t a) { uint4 v; asm volatile("ld.shared.v4.u32 {%0,%1,%2,%3}, [%4];" : "=r"(v.x), "=r"(v.y), "=r"(v.z), "=r"(v.w) : "r"(a) : "memory"); return v; }
__device__ __forceinline__ uint2 lds64(uint32_t a) { uint2 v; asm volatile("ld.shared.v2.u32 {%0,%1}, [%2];" : "=r"(v.x), "=r"(v.y) : "r"(a) : "memory"); return v; }
__device__ __forceinline__ void sts128(uint32_t p, uint32_t a, uint32_t b, uint32_t c, uint32_t d) { asm volatile("st.shared.v4.u32 [%0], {%1,%2,%3,%4};" :: "r"(p), "r"(a), "r"(b), "r"(c), "r"(d) : "memory"); }
__device__ __forceinline__ void sts32(uint32_t a, float v) { asm volatile("st.shared.f32 [%0], %1;" :: "r"(a), "f"(v) : "memory"); }
__device__ __forceinline__ void named_sync(int id, int n) { asm volatile("bar.sync %0, %1;" :: "r"(id), "r"(n) : "memory"); }
__device__ __forceinline__ void named_arrive(int id, int n) { asm volatile("bar.arrive %0, %1;" :: "r"(id), "r"(n) : "memory"); }
__device__ __forceinline__ void named_arrive_if(uint32_t c, int id, int n) { asm volatile("{\n.reg .pred q;\nsetp.ne.u32 q, %2, 0;\n@q bar.arrive %0, %1;\n}" :: "r"(id), "r"(n), "r"(c) : "memory"); }
__device__ __forceinline__ uint64_t mkdesc(uint32_t hi, uint32_t lo) { return ((uint64_t)hi << 32) | lo; }
constexpr uint32_t HI_SW128 = 0x40000040u;
__device__ __forceinline__ uint32_t pack2(float lo, float hi) { uint32_t r; asm("cvt.rn.bf16x2.f32 %0, %1, %2;" : "=r"(r) : "f"(hi), "f"(lo)); return r; }
__device__ __forceinline__ float bf_lo(uint32_t v) { return __uint_as_float(v << 16); }
__device__ __forceinline__ float bf_hi(uint32_t v) { return __uint_as_float(v & 0xffff0000u); }
__device__ __forceinline__ float rbf(float x) { return bf_lo(pack2(x, 0.f)); }
__device__ __forceinline__ uint32_t hsub2(uint32_t a, uint32_t b) { uint32_t r; asm("sub.rn.bf16x2 %0, %1, %2;" : "=r"(r) : "r"(a), "r"(b)); return r; }
__device__ __forceinline__ uint32_t hadd2(uint32_t a, uint32_t b) { uint32_t r; asm("add.rn.bf16x2 %0, %1, %2;" : "=r"(r) : "r"(a), "r"(b)); return r; }
__device__ __forceinline__ uint32_t place(uint32_t v, uint32_t sel) { uint32_t r; asm volatile("prmt.b32 %0, %1, 0, %2;" : "=r"(r) : "r"(v), "r"(sel)); return r; }
__device__ __forceinline__ uint32_t hmax2(uint32_t a, uint32_t b) { uint32_t r; asm("max.bf16x2 %0, %1, %2;" : "=r"(r) : "r"(a), "r"(b)); return r; }
__device__ __forceinline__ uint32_t hmul2(uint32_t a, uint32_t b) { uint32_t r; asm("mul.rn.bf16x2 %0, %1, %2;" : "=r"(r) : "r"(a), "r"(b)); return r; }
__device__ __forceinline__ uint32_t hfma2(uint32_t a, uint32_t b, uint32_t c) { uint32_t r; asm("fma.rn.bf16x2 %0, %1, %2, %3;" : "=r"(r) : "r"(a), "r"(b), "r"(c)); return r; }
__device__ __forceinline__ float tanh_fast(float x) { float r; asm("tanh.approx.f32 %0, %1;" : "=f"(r) : "f"(x)); return r; }
__device__ __forceinline__ float rcp_fast(float x) { float r; asm("rcp.approx.ftz.f32 %0, %1;" : "=f"(r) : "f"(x)); return r; }
__device__ __forceinline__ float ex2_fast(float x) { float r; asm("ex2.approx.ftz.f32 %0, %1;" : "=f"(r) : "f"(x)); return r; }
__device__ __forceinline__ void mma16816(float (&c)[4], uint32_t a0, uint32_t a1, uint32_t a2, uint32_t a3, uint32_t b0, uint32_t b1) {
  asm volatile("mma.sync.aligned.m16n8k16.row.col.f32.bf16.bf16.f32 {%0,%1,%2,%3}, {%4,%5,%6,%7}, {%8,%9}, {%0,%1,%2,%3};"
               : "+f"(c[0]), "+f"(c[1]), "+f"(c[2]), "+f"(c[3]) : "r"(a0), "r"(a1), "r"(a2), "r"(a3), "r"(b0), "r"(b1));
}
__device__ __forceinline__ void ldsm4(uint32_t (&r)[4], uint32_t addr) {
  asm volatile("ldmatrix.sync.aligned.m8n8.x4.shared.b16 {%0,%1,%2,%3}, [%4];" : "=r"(r[0]), "=r"(r[1]), "=r"(r[2]), "=r"(r[3]) : "r"(addr) : "memory");
}
__device__ __forceinline__ void stsm4(uint32_t addr, uint32_t a, uint32_t b, uint32_t c, uint32_t d) {
  asm volatile("stmatrix.sync.aligned.m8n8.x4.shared.b16 [%0], {%1,%2,%3,%4};" :: "r"(addr), "r"(a), "r"(b), "r"(c), "r"(d) : "memory");
}

__device__ __forceinline__ float ln_rstd(float var, float eps = 1e-5f) {
  float sd;
  asm("sqrt.approx.ftz.f32 %0, %1;" : "=f"(sd) : "f"(rbf(rbf(var) + eps)));
  return rcp_fast(rbf(sd));
}
__device__ __forceinline__ float ln_var(float mean, float sq) { return fmaxf(fmaf(-mean, mean, sq * (1.0f / D_)), 0.f); }
struct LnC { uint32_t m, rh, rl; };
__device__ __forceinline__ LnC ln_consts(float sum, float sq, float eps) {
  const float mean = sum * (1.0f / D_), r = ln_rstd(ln_var(mean, sq), eps), rh = rbf(r);
  LnC c; c.m = pack2(mean, mean); c.rh = pack2(rh, rh); c.rl = pack2(r - rh, r - rh);
  return c;
}
__device__ __forceinline__ uint32_t ln_apply(uint32_t x, const LnC& c) {
  uint32_t d = hsub2(x, c.m);
  return hfma2(d, c.rh, hmul2(d, c.rl));
}

__device__ __forceinline__ void fence_code(int id) {
  asm volatile("{\n.reg .pred q;\nLAB_F:\nsetp.eq.u32 q, %0, %1;\n@q st.volatile.shared.u32 [%2], %2;\n@q bra LAB_F;\n}" :: "r"(blockIdx.x), "r"(0x70000000 + id), "r"(0) : "memory");
}
template <int N> __device__ __forceinline__ void fresh(float (&a)[N]) {
#pragma unroll
  for (int i = 0; i < N; i++) asm volatile("" : "=f"(a[i]));
}
constexpr int B_EMPTY = 64, B_X = 384, B_KV = 192, B_WQ = 248, B_HALO = 256, B_RES = 264, B_ATT = 272, B_GATE = 280, B_WO = 304, B_O = 312, B_XW = 320, B_WQ2 = 328, B_XD = 336, B_QD = 344, B_UD = 352, B_U1 = 128, B_U2 = 136, B_TAG = 360, B_T0 = 368;

template <int TA>
__device__ __forceinline__ void gemm_issue(float (&acc)[56], uint32_t la, uint32_t lo, int sc) {
  wg_fence();
#pragma unroll
  for (int k = 0; k < 4; k++)
    wgmma_n112<TA, 1>(acc, mkdesc(TA ? HI_SW128 : 8, la + (TA ? 512u << 16 : 64u << 16) + k * 128), mkdesc(8, lo + (112u << 16) + 512 + k * 224), sc | k);
  wg_commit();
}
template <int TA>
__device__ __forceinline__ void gemm_stage(float (&acc)[56], uint32_t base, int it, int sc) {
  mbar_wait(base + OFF_BAR + (it & 7) * 8, (it >> 3) & 1);
  const uint32_t lo = (base >> 4) + (it & 7) * (SLOT >> 4);
  gemm_issue<TA>(acc, lo, lo, sc);
}
template <int TA, int EXTRA = 0>
__device__ __forceinline__ void gemm_loop(float (&acc)[56], uint32_t base, int it, int end, bool rel, int oi, uint32_t ok = 0, int gate_it = -1, uint32_t gate = 0) {
#pragma unroll 1
  for (; it < end;) {
    if (__builtin_expect(!ok, 0)) mbar_wait(base + OFF_BAR + (it & 7) * 8, (it >> 3) & 1);
    const uint32_t lo = (base >> 4) + (it & 7) * (SLOT >> 4);
    gemm_issue<TA>(acc, (unsigned)(it - XS) < EXTRA ? ((base + OFF_XW) >> 4) + (it - XS) * 512 : lo, lo, 1);
    OBS(SOBS && rel, oi + it);
    it++;
    ok = mbar_try(base + OFF_BAR + (it & 7) * 8, (it >> 3) & 1);
    wg_wait<1>();
    if (rel || it == gate_it) mbar_arrive(rel ? base + OFF_BAR + B_EMPTY + ((it - 2) & 7) * 8 : gate);
  }
}
template <int PER>
__device__ __forceinline__ void produce_box(uint32_t base, int it, int end, const CUtensorMap* mp, int c0, int c1, uint32_t tn = 0) {
#pragma unroll 1
  for (; it < end; it++) {
    const uint32_t fb = base + OFF_BAR + (it & 7) * 8;
    mbar_wait(fb + B_EMPTY, (it >> 3) & 1);
    if (PER) { while ((int)(clock() - tn) < 0); tn += PER; }
    if (elect()) { mbar_expect_tx(fb, 8192); tma3d(base + (it & 7) * SLOT, mp, c0, c1, 0, fb); }
    c1 += 64;
  }
}
template <int PER>
__device__ __forceinline__ void produce_lin(uint32_t base, int it, int end, const unsigned char* src, uint32_t bytes, uint32_t tn = 0) {
#pragma unroll 1
  for (; it < end; it++) {
    const uint32_t fb = base + OFF_BAR + (it & 7) * 8;
    mbar_wait(fb + B_EMPTY, (it >> 3) & 1);
    if (PER) { while ((int)(clock() - tn) < 0); tn += PER; }
    if (elect()) { mbar_expect_tx(fb, bytes); bulk_g2s(base + (it & 7) * SLOT + (bytes & 2048) * 4, src, bytes, fb); }
    src += bytes;
  }
}

__device__ __forceinline__ void retile_wo(const unsigned char* wo, unsigned char* scr, int u, int lane) {
  const int r8 = lane & 7, mi = lane >> 3;
  const unsigned char* src = wo + ((u >> 1) * 8 + r8) * 896 + ((u & 1) * 28 + mi) * 16;
  unsigned char* dst = scr + ((u & 1) * 2 * HU_T + 60 + (u >> 4)) * BT + ((u >> 1) & 7) * 1792 + mi * 128 + r8 * 16;
  uint4 v[7];
#pragma unroll
  for (int i = 0; i < 7; i++) v[i] = ldg128(src + i * 64);
#pragma unroll
  for (int i = 0; i < 7; i++) stg128(dst + i * 512 + ((i * 4 + mi) / 14) * (HU_T * BT - 1792), v[i].x, v[i].y, v[i].z, v[i].w);
  if (!(RB & 1)) publish(scr, C_WO);
}

struct Params {
  const unsigned char *wqkv, *wo, *w1, *b1, *w2, *b2;
  unsigned char *out, *scr;
};

__global__ void __launch_bounds__(NTHREADS, 1)
fused_kernel(const __grid_constant__ CUtensorMap m_x, const __grid_constant__ CUtensorMap m_wkv, const __grid_constant__ CUtensorMap m_wq,
             const __grid_constant__ CUtensorMap m_w1, const __grid_constant__ CUtensorMap m_w2, const __grid_constant__ CUtensorMap m_res, const Params p) {
  extern __shared__ __align__(1024) unsigned char smem_raw[];
  constexpr uint32_t base = 1024, bars = base + OFF_BAR;
  const int tid = threadIdx.x, lane = tid & 31, b = blockIdx.x;
  const int rb = (b >> 2) & 15, hp = ((b >> 6) << 2) | (b & 3);
  const int wcol = hp * 56 - (hp & 1) * 8;
  auto load_wq = [&](int s0, int s1, uint32_t bar) {
    mbar_expect_tx(bar, (s1 - s0) * 8192);
#pragma unroll 1
    for (int s = s0; s < s1; s++) tma3d(base + OFF_WQ + s * 8192, &m_wq, wcol, s * 64, 0, bar);
  };
  auto load_kv = [&](int s) { mbar_expect_tx(bars + B_KV + s * 8, 16384); tma3d(base + s * 16384, &m_wkv, wcol, s * 64, 1, bars + B_KV + s * 8); };
  if (tid < 32) {
    if (elect()) {
#pragma unroll
      for (int i = 0; i < 7; i++) mbar_init(bars + B_X + i * 8, 1);
      asm volatile("fence.mbarrier_init.release.cluster;" ::: "memory");
#pragma unroll
      for (int i = 0; i < 7; i++) { mbar_expect_tx(bars + B_X + i * 8, 16384 >> XSPLIT); tma3d(base + OFF_X + i * 16384 + XSPLIT * 8192, &m_x, i * 64, rb * 128 + XSPLIT * 64, 0, bars + B_X + i * 8); }
#pragma unroll
      for (int i = 0; i < 7; i++) { mbar_init(bars + B_KV + i * 8, 1); if (XSPLIT) mbar_init(bars + B_X + 64 + i * 8, 1); }
      asm volatile("fence.mbarrier_init.release.cluster;" ::: "memory");
      if (XSPLIT) {
#pragma unroll
        for (int i = 0; i < XK; i++) load_kv(i);
#pragma unroll
        for (int i = 0; i < 7; i++) { mbar_expect_tx(bars + B_X + 64 + i * 8, 8192); tma3d(base + OFF_X + i * 16384, &m_x, i * 64, rb * 128, 0, bars + B_X + 64 + i * 8); }
      }
#pragma unroll 1
      for (int i = XSPLIT * XK; i < NW0; i++) load_kv(i);
    }
  }
  const int warp = __shfl_sync(0xffffffffu, tid >> 5, 0);
  if (warp == 1) {
    if (elect()) {
#pragma unroll
      for (int i = 0; i < 18; i++) mbar_init(bars + i * 8, i < 16 ? 2 : 1);
#pragma unroll
      for (int i = 0; i < 14; i++) mbar_init(bars + B_WQ + i * 8, 1);
      asm volatile("fence.mbarrier_init.release.cluster;" ::: "memory");
      if (smem_u32(smem_raw) != base) asm volatile("trap;");
    }
  }
  const int dt = b & 3, mt = b >> 2;
  const bool g1 = (b & 15) < 14;
  const int a1 = b - 2 * (b >> 4), ft = a1 >> 2, d1 = a1 & 3;
  const int g = lane >> 2, t = lane & 3, r8 = lane & 7, mi = lane >> 3;
  OBSG(FREQ && tid == 160, 128, 160);
  __syncthreads();
  if (warp >= 8) {
    asm volatile("setmaxnreg.dec.sync.aligned.u32 40;");
    const int pw = warp - 8;
    unsigned char* scr = p.scr;
    if (WPF && pw == 2) {
      mbar_wait(bars + B_X + (WPF - 1) * 8, 0);
      if (b < 112 && lane < 28) asm volatile("prefetch.global.L2 [%0];" :: "l"(p.wqkv + (b * 4 + lane / 7) * 2688 + (lane % 7) * 128) : "memory");
      if (lane == 31) asm volatile("prefetch.tensormap [%0];" :: "l"(&m_wq) : "memory");
      __syncwarp();
    }
    if (NW0 < 7 && pw == 3) {
      mbar_wait(bars + B_X, 0);
      if (elect()) {
#pragma unroll 1
        for (int i = NW0; i < 7; i++) load_kv(i);
      }
      __syncwarp();
    }
    auto first_wq = [&]() {
      named_sync(8, 384);
      if (elect()) {
        if (TS && g1) asm volatile("red.relaxed.gpu.global.max.u32 [%0], %1;" :: "l"(scr + CNT_OFF + C_H * 128 + 8), "r"(gtime()) : "memory");
        load_wq(0, WQA, bars + B_WQ); mbar_arrive(bars + B_XD);
      }
      __syncwarp();
    };
    {
      const int c0 = pw * 14 + (mi >> 1);
      unsigned char* dst = scr + (pw * HU_T + rb * 2 + (hp >> 2)) * BT + ((hp & 3) * 2 + (mi & 1)) * 1792 + (mi >> 1) * 128 + r8 * 16;
      const uint32_t xs = base + OFF_X + (hp * 16 + (lane & 15)) * 128;
      uint4 H[7];
      named_sync(9, 160);
#pragma unroll
      for (int i = 0; i < 7; i++) H[i] = lds128(xs + ((c0 + 2 * i) >> 3) * 16384 + ((((c0 + 2 * i) & 7) ^ r8) << 4));
      asm volatile("" :: "r"(H[6].w), "r"(H[0].x) : "memory");
      if (pw != WQW) named_arrive(8, 384);
      else if (!WQC || hp < 4) first_wq();
      const uint2 st = lds64(base + OFF_LN + (lane & 15) * 8);
      const float sum = __uint_as_float(st.x), mean = sum * (1.0f / D_), var = ln_var(mean, __uint_as_float(st.y));
      const float m = rbf(mean), r = ln_rstd(var), r2 = ln_rstd(var * r * r);
      const float nc = fmaf(m, (float)D_, -sum) * (1.0f / D_) * (r * r2);
      const uint32_t m2 = pack2(m, m), r2x = pack2(r * r2, r * r2), nc2 = pack2(nc, nc);
      auto f = [&](uint32_t v) { return hfma2(hsub2(v, m2), r2x, nc2); };
#pragma unroll
      for (int i = 0; i < 7; i++) stg128(dst + i * 256, f(H[i].x), f(H[i].y), f(H[i].z), f(H[i].w));
      if (pw != 1) named_arrive(4, 128);
      if (WQC && pw == WQW && hp >= 4) first_wq();
    }
    const int lane = lane_id();
    if (pw == 0) {
      if (elect()) {
        asm volatile("prefetch.tensormap [%0];" :: "l"(&m_w1) : "memory");
        asm volatile("prefetch.tensormap [%0];" :: "l"(&m_w2) : "memory");
        asm volatile("prefetch.tensormap [%0];" :: "l"(&m_res) : "memory");
      }
      __syncwarp();
      const uint32_t e = probe(scr + EPO + CNT_OFF + C_EPOCH * 128) + 1;
      sts32(bars + B_TAG, __uint_as_float((e & 0x3fffu) | ((e << 2) & 0x3fff0000u)));
      named_arrive(1, 96);
      if (WOW == 0 && b < 112) { retile_wo(p.wo, scr, b, lane_id()); named_arrive(15, 64); }
      if (g1) produce_box<0>(base, 0, 32, &m_w1, ft * 64, 0);
      auto load_res = [&]() { if (elect()) { mbar_expect_tx(bars + B_RES, BT); tma3d(base + OFF_Q, &m_res, dt * 112, mt * 64, 0, bars + B_RES); } };
      if (RESP == 0) { mbar_wait(bars + B_ATT, 0); load_res(); }
      mbar_wait(bars + B_WO, 0);
      produce_lin<0>(base, 0, 7, scr + (dt * HU_T + 60) * BT, BT);
      if (NX) {
        produce_box<0>(base, 7, XT, &m_w2, mt * 64, 0);
        if (elect()) {
          mbar_expect_tx(bars + B_XW, NX * 8192);
#pragma unroll 1
          for (int i = 0; i < NX; i++) tma3d(base + OFF_XW + i * 8192, &m_w2, mt * 64, (XS - 7 + i) * 64, 0, bars + B_XW);
        }
        __syncwarp();
        produce_box<0>(base, XT, XS, &m_w2, mt * 64, (XT - 7) * 64);
        mbar_wait(bars + B_XW, 0);
#pragma unroll 1
        for (int it = XS; it < XS + NX; it++) { mbar_wait(bars + B_EMPTY + (it & 7) * 8, (it >> 3) & 1); if (lane == 0) mbar_arrive(bars + (it & 7) * 8); }
        __syncwarp();
        produce_box<0>(base, XS + NX, 35, &m_w2, mt * 64, (XS + NX - 7) * 64);
      } else if (UPH) {
#pragma unroll 1
        for (int h = 0; h < 2; h++) {
#pragma unroll 1
          for (int it = 7 + h * 14, c2 = 0; it < 21 + h * 14; it++, c2 += 8) {
            const uint32_t fb = bars + (it & 7) * 8;
            mbar_wait(fb + B_EMPTY, (it >> 3) & 1);
            if (elect()) { mbar_expect_tx(fb, 8192); tma3d(base + (it & 7) * SLOT, &m_w2, mt * 64, h * 8, c2, fb); }
          }
        }
      } else produce_box<0>(base, 7, 35, &m_w2, mt * 64, 0);
      if (RESP == 1) load_res();
    } else if (pw == 1) {
      named_sync(4, 128);
      const unsigned char* hl = scr + (rb * 2 + (hp >> 2)) * BT + (hp & 3) * 3584 + min(lane, 27) * 128;
      const uint32_t v0 = probe(hl), v1 = probe(hl + HU_T * BT), v2 = probe(hl + 2 * HU_T * BT), v3 = probe(hl + 3 * HU_T * BT);
      if (RB & 2) settle(v0 ^ v1 ^ v2 ^ v3);
      if (elect()) asm volatile("red.relaxed.gpu.global.add.u32 [%0], 1;" :: "l"(scr + CNT_OFF + (C_H + (b & (HL - 1))) * 128) : "memory");
      __syncwarp();
      OBS(lane == 0, 4);
      if (WQC) mbar_wait(bars + B_XD, 0);
      if (WQC > 1 && hp >= 4) __nanosleep(WQC);
      if ((!WQS || !g1) && elect()) load_wq(WQA, 7, bars + B_WQ2);
      __syncwarp();
      if (g1) {
        if (HSL) __nanosleep(HSL);
        const uint32_t v = spin_ge(scr + (lane & 1) * 8, C_H, lane & 1 ? 0 : 128);
        if (TS && lane == 1) sts32(bars + B_T0, __uint_as_float(v + TS));
        if (WQS && elect()) load_wq(WQA, 7, bars + B_WQ2);
        __syncwarp();
        OBS(lane == 0, 16);
        if (HP) { produce_lin<HP>(base, 0, 8, scr + d1 * HU_T * BT, BT, clock()); produce_lin<0>(base, 8, 32, scr + (d1 * HU_T + 8) * BT, BT); }
        else produce_lin<0>(base, 0, 32, scr + d1 * HU_T * BT, BT);
      }
      mbar_wait(bars + B_O, 0);
      if (OHOLD && g1 && mbar_try(bars + B_EMPTY + OHOLD * 8, 0)) mbar_wait(bars + B_UD, 0);
      produce_lin<OPP>(base, 0, 7, scr + O_OFF + mt * 57344, 8192, clock());
      const unsigned char* us = scr + (dt * HU_T + 32) * BT;
#pragma unroll
      for (int i = 0; i < NPRE; i++) {
        mbar_wait(bars + B_EMPTY + ((7 + i) & 7) * 8, i > 0);
        if (elect()) mbar_expect_tx(bars + ((7 + i) & 7) * 8, BT);
        __syncwarp();
      }
      spin_ge(scr, C_U + (ALL4 ? lane & 3 : dt) + (mt & (UREP - 1)) * 4, 28);
      if (elect()) {
#pragma unroll
        for (int i = 0; i < NPRE; i++) bulk_g2s(base + ((7 + i) & 7) * SLOT + 8192, us + i * BT, BT, bars + ((7 + i) & 7) * 8);
      }
      if (UPH && lane == 0) mbar_arrive(bars + B_U1);
      const uint32_t tu = clock();
      OBS(lane == 0, 18);
      produce_lin<UP>(base, 7 + NPRE, 15, us + NPRE * BT, BT, tu + NPRE * UP - U0);
#pragma unroll 1
      for (int h = 0; h < 2; h++) {
        if (UPH && h) mbar_wait(bars + B_U2, 0);
        produce_lin<0>(base, 15 + h * 6, 21 + h * 14, us + (8 + h * 6) * BT, BT);
      }
      unsigned tk = 0;
      if (lane == 0) tk = atomicAdd((unsigned*)(scr + CNT_OFF + C_TK * 128), 1u);
      if (__shfl_sync(0xffffffffu, tk, 0) == 127) {
#pragma unroll 1
        for (int i = lane; i < 192; i += 32) *(unsigned*)(scr + CNT_OFF + i * 128) = 0;
        *(unsigned*)(scr + CNT_OFF + C_H * 128 + 8) = 0;
        publish(scr + EPO, C_EPOCH);
      }
    } else if (pw == 2) {
      uint32_t tn = clock() + PACE0 + b * STAG;
      if (WOW == 2 && b < 112) { retile_wo(p.wo, scr, b, lane_id()); named_arrive(15, 64); }
      const unsigned char* src = p.w1 + b * 4096 + lane * 128;
#pragma unroll 1
      for (int i = 0; i < 28 + FREQ * 2; i++) {
        while ((int)(clock() - tn) < 0) __nanosleep(20);
        if (!UPH && i == 14) src = p.w2 + b * 4096 + lane * 128;
        if (UPH && (i == 14 || i == 21)) src = p.w2 + ((b >> 3) * 16 + (b & 7) + (i & 1) * 8) * 4096 + lane * 128;
        if (i < 28) asm volatile("prefetch.global.L2 [%0];" :: "l"(src) : "memory");
        OBSG(FREQ && lane == 0, 129 + i, 161 + i);
        src += (!UPH || i < 14 ? 128 : 256) * 4096;
        tn += i < 14 ? PACE1 : PACE2;
      }
    } else {
      if (WOW == 3 && b < 112) retile_wo(p.wo, scr, b, lane_id());
      const int lane = lane_id();
      unsigned char* hg = scr + HALO_OFF + (rb * 8 + hp) * 3584;
      named_sync(1, 96);
      const uint32_t tag = lds64(bars + B_TAG).x;
      if (rb < 15) {
#pragma unroll
        for (int q = 0; q < 7; q += 4) {
          uint4 v[4];
#pragma unroll
          for (int i = q; i < q + 4 && i < 7; i++) v[i - q] = lds128(base + OFF_K + 8 * 3584 + i * 512 + lane * 16 + (i * 32 + lane < 112 && !(lane & 7) ? 1792 : 0));
#pragma unroll
          for (int i = q; i < q + 4 && i < 7; i++) stg128(hg + i * 512 + lane * 16, (lane & 7) == (i * 32 + lane < 112) ? tag : v[i - q].x, v[i - q].y, v[i - q].z, v[i - q].w);
        }
      }
      if (TAG == 1 && rb < 15) publish(scr, C_HALO + rb * 8 + hp);
      OBS(lane == 0, 29);
      if (rb > 0) {
        if (TAG == 1) spin_ge(scr, C_HALO + (rb - 1) * 8 + hp, 1); else __nanosleep(HWAIT);
        const uint32_t la = base + OFF_K + min(lane, 27) * 128;
#pragma unroll 1
        for (int n = 0;; n++) {
          if (elect()) { mbar_expect_tx(bars + B_XW, 3584); bulk_g2s(base + OFF_K, hg - 8 * 3584, 3584, bars + B_XW); }
          __syncwarp();
          mbar_wait(bars + B_XW, n & 1);
          if ((XP & 2) || __all_sync(0xffffffffu, lds64(la + (lane < 14 ? 16 : 0)).x == tag)) break;
          if (n > 1000000) asm volatile("trap;");
        }
        if (!(XP & 2) && lane < 14) { const uint4 v = lds128(la); sts128(la + 1792, v.x, v.y, v.z, v.w); }
      } else {
#pragma unroll
        for (int i = 0; i < 7; i++) sts128(base + OFF_K + i * 512 + lane * 16, 0, 0, 0, 0);
      }
      OBS(lane == 0, 12);
      if (!(XP & 1) || rb == 0) smem_fence();
      __syncwarp();
      if (lane == 0) mbar_arrive(bars + B_HALO);
      __syncwarp();
      if (WOW != 3 && b < 112) named_sync(15, 64);
      if ((RB & 1) && b < 112) {
        settle(probe(scr + (((b & 1) * 2 + (lane >> 4)) * HU_T + 60 + (b >> 4)) * BT + ((b >> 1) & 7) * 1792 + min(lane & 15, 13) * 128));
        publish(scr, C_WO);
      }
      if (RESP >= 2) {
        mbar_wait(bars + B_QD, 0);
        if (elect()) { mbar_expect_tx(bars + B_RES, BT); tma3d(base + OFF_Q, &m_res, dt * 112, mt * 64, 0, bars + B_RES); }
        __syncwarp();
      }
      if (RB & 1) mbar_wait(bars + (g1 ? B_GATE + 8 : B_ATT), 0);
      spin_ge(scr, C_WO, 112);
      if (lane == 0) mbar_arrive(bars + B_WO);
      mbar_wait(bars + B_ATT, 0);
      spin_ge(scr, C_O + (mt >> 1), 8);
      OBS(lane == 0, 17);
      if (lane == 0) mbar_arrive(bars + B_O);
      if (UPH) {
        mbar_wait(bars + B_U1, 0);
        if (U2S) __nanosleep(U2S);
        spin_ge(scr, C_U + 4 + dt, 28);
        OBS(lane == 0, 11);
        if (lane == 0) mbar_arrive(bars + B_U2);
      }
    }
  } else {
    asm volatile("setmaxnreg.inc.sync.aligned.u32 232;");
    const int wg = warp >> 2, w4 = warp & 3, th = wg ^ 1;
    const bool rel = (tid & 127) < 2;
    unsigned char* scr = p.scr;
    uint32_t X[28][4];
    float aq[28];
    const uint32_t dlo = (base >> 4) + (512u << 16) + (hp & 1), dlq = dlo + (OFF_WQ >> 4);
    {
      uint32_t xa[4];
#pragma unroll
      for (int k = 0; k < 4; k++) xa[k] = base + OFF_X + (th * 64 + w4 * 16 + (mi >> 1) * 8 + r8) * 128 + (((2 * k + (mi & 1)) ^ r8) << 4);
      float c0[2][4] = {}, c1[2][4] = {};
      uint32_t one[8];
#pragma unroll
      for (int j = 0; j < 8; j++) asm volatile("{\n.reg .u32 y;\nmov.u32 y, %%tid.y;\nmad.lo.u32 %0, y, %1, 0x3f803f80;\n}" : "=r"(one[j]) : "r"(lane + j));
      asm volatile("" : "+l"(scr));
      uint32_t ok = 0;
      const uint32_t bx = bars + B_X + XSPLIT * wg * 64;
      if (HEAT) {
#pragma unroll 1
        for (int n = 0; n < 64 && !ok; n++) { mma16816(c0[0], 0, 0, 0, 0, 0, 0); ok = mbar_try(bars + B_X, 0); }
        if (XSPLIT && wg) ok = 0;
      }
#pragma unroll
      for (int i = 0; i < 8; i++) {
        if (i < 7) {
          if (!ok) mbar_wait(bx + i * 8, 0);
          OBS(tid == 64 && i == 0, 0); OBS(tid == 64 && i == 6, 15);
#pragma unroll
          for (int k = 0; k < 4; k++) ldsm4(X[i * 4 + k], xa[k] + i * 16384);
          if (i < 6) ok = mbar_try(bx + i * 8 + 8, 0);
        }
        if (i > 0) {
#pragma unroll
          for (int k = i * 4 - 4; k < i * 4; k++) {
            mma16816(c0[k & 1], X[k][0], one[(k & 1) * 4], X[k][1], one[(k & 1) * 4 + 1], X[k][0], X[k][1]);
            mma16816(c1[k & 1], X[k][2], one[(k & 1) * 4 + 2], X[k][3], one[(k & 1) * 4 + 3], X[k][2], X[k][3]);
          }
        }
      }
      float st[4];
#pragma unroll
      for (int j = 0; j < 2; j++) {
        st[j] = __shfl_sync(0xffffffffu, (g & 1) ? c0[0][2 * j + 1] + c0[1][2 * j + 1] : c0[0][2 * j] + c0[1][2 * j], (lane & 28) | (g >> 1));
        st[2 + j] = __shfl_sync(0xffffffffu, (g & 1) ? c1[0][2 * j + 1] + c1[1][2 * j + 1] : c1[0][2 * j] + c1[1][2 * j], (lane & 28) | (g >> 1));
      }
      named_arrive(8, 384);
      asm volatile("{\n.reg .pred q;\nsetp.ne.u32 q, %3, 0;\n@q st.shared.v2.f32 [%0], {%1,%2};\n@q bar.arrive 9, 160;\n}"
                   :: "r"(base + OFF_LN + ((t & 1) * 8 + g) * 8), "f"((t & 1) ? st[3] : st[1]), "f"((t & 1) ? st[2] : st[0]), "r"((uint32_t)((warp ^ 4) == hp)) : "memory");
      ok = mbar_try(bars + B_KV, 0);
      LnC l0, l1;
      float eps = 1e-5f;
#pragma unroll 1
      do {
        l0 = ln_consts(st[1], st[0], eps); l1 = ln_consts(st[3], st[2], eps);
#pragma unroll
        for (int k = 0; k < PRE * 16; k++) X[k >> 2][k & 3] = hsub2(X[k >> 2][k & 3], k & 2 ? l1.m : l0.m);
        eps += eps;
      } while ((l0.rl ^ l1.rl) == 4);
      OBS(tid == 32, 1);
      float ak[60], *av = ak + 32;
      const int pp_in = wg ? 6 : 0, pp_out = wg ? 0 : 6;
#pragma unroll
      for (int s = 0; s < 7; s++) {
#pragma unroll
        for (int k = s * 4; k < s * 4 + 4; k++) {
          if (s < PRE) {
            auto f = [&](uint32_t d, const LnC& l) { return hfma2(d, l.rh, hmul2(d, l.rl)); };
            const uint32_t y = f(X[k][1], l0);
            X[k][0] = f(X[k][0], l0); X[k][1] = f(X[k][2], l1); X[k][2] = y; X[k][3] = f(X[k][3], l1);
          } else {
            const uint32_t y = ln_apply(X[k][1], l0);
            X[k][0] = ln_apply(X[k][0], l0); X[k][1] = ln_apply(X[k][2], l1); X[k][2] = y; X[k][3] = ln_apply(X[k][3], l1);
          }
        }
        if (__builtin_expect(!ok, 0)) { mbar_wait(bars + B_KV + s * 8, 0); if (s == 6) mbar_wait(bars + B_WQ, 0); }
        if (s == 0) fresh(ak);
        if (s == 6) { wg_wait<0>(); if ((tid & 127) == 0) mbar_arrive(bars + B_EMPTY + 3 * 8); }
        OBS(KOBS && (tid & 127) == 0, 40 + wg * 32 + s);
        if (PPM == 2 ? (wg ? s < 6 : s > 1) : (wg || s)) named_sync(pp_in, 256);
        OBS(KOBS && (tid & 127) == 32, 48 + wg * 32 + s);
        OBS(tid == 64 && s == 0, 2);
        wg_fence();
#pragma unroll
        for (int k = 0; k < 4; k++) {
          wgmma_rs_n120<1>(ak, X[s * 4 + k], mkdesc(HI_SW128, dlo + s * 1024 + k * 128), (s | k) != 0);
        }
        wg_commit();
        if (s == 6) {
          fresh(aq);
#pragma unroll
          for (int k = 0; k < 4 * QA; k++) {
            if (k == 4 * QA - PQE) named_arrive(pp_out, 256);
            wgmma_rs_n56<1>(aq, X[k], mkdesc(HI_SW128, dlq + k * 128), k);
          }
          wg_commit();
        }
        if (s < 6 || PQE == 0) named_arrive_if(PPM != 2 || (wg ? s != 5 : s != 0), pp_out, 256);
        fence_code(s);
        OBS(KOBS && (tid & 127) == 64, 56 + wg * 32 + s);
        if (s < 6) ok = mbar_try(bars + B_KV + s * 8 + 8, 0);
        if (s == 5) ok &= mbar_try(bars + B_WQ, 0);
        OBS(tid == 64 && s == 5, 31);
        if (s > 0) wg_wait<1>();
        OBS(KOBS && (tid & 127) == 96, 64 + wg * 32 + s);
        if ((s == 2 || s == 3 || s == 5) && (tid & 127) == 0) mbar_arrive(bars + B_EMPTY + (s == 5 ? 2 : s - 2) * 8);
      }
      if ((tid & 127) == 0) mbar_arrive(bars + B_EMPTY + 4 * 8);
      OBS(tid == 32, 3);
      {
        const uint32_t kst = base + OFF_K + (2 + (warp ^ 4) * 2 + (mi & 1)) * 1792 + (mi >> 1) * 896 + r8 * 16;
#pragma unroll
        for (int n = 0; n < 7; n++)
          stsm4(kst + n * 128, pack2(ak[n * 4], ak[n * 4 + 1]), pack2(ak[n * 4 + 2], ak[n * 4 + 3]), pack2(av[n * 4], av[n * 4 + 1]), pack2(av[n * 4 + 2], av[n * 4 + 3]));
        named_arrive_if(warp == 3, 1, 96);
      }
      OBS(tid == 96, 32); OBS(tid == 224, 34);
      wg_wait<0>();
      if ((tid & 127) == 0) mbar_arrive(bars + B_EMPTY + 5 * 8);
      if (!WQM) mbar_wait(bars + B_WQ2, 0);
    }
    const unsigned short *bp1 = (const unsigned short*)p.b1 + (g1 ? ft * 64 : 0) + w4 * 16 + g, *bp2 = (const unsigned short*)p.b2 + mt * 64 + w4 * 16 + g;
    const uint32_t braw[4] = {__ldg(bp1), __ldg(bp1 + 8), __ldg(bp2), __ldg(bp2 + 8)};
    auto q_rest = [&]() {
      wg_fence();
#pragma unroll
      for (int s = QA; s < 7; s++) {
        if (WQM && s == WQA) { mbar_wait(bars + B_WQ2, 0); wg_fence(); }
#pragma unroll
        for (int k = s * 4; k < s * 4 + 4; k++) wgmma_rs_n56<1>(aq, X[k], mkdesc(HI_SW128, dlq + k * 128), 1);
        wg_commit();
        if (s == 5) { wg_wait<2>(); if ((tid & 127) == 0) mbar_arrive(bars + B_EMPTY + 6 * 8); }
      }
    };
    uint32_t Q[4][4];
    auto q_pack = [&]() {
#pragma unroll
      for (int n = 0; n < 14; n++) { const int m = n + 2 * (n > 7); Q[m >> 2][m & 3] = pack2(aq[n * 2], aq[n * 2 + 1]); }
#pragma unroll
      for (int h = 0; h < 2; h++) { Q[2][h] = t < 2 ? 0u : Q[1][2 + h]; Q[1][2 + h] = t < 2 ? Q[1][2 + h] : 0u; }
    };
    float acc[56];
    auto ai = [](int p) { return p < 4 ? 48 + (p & 1) * 4 + (p & 2) : (p - 4) * 4; };
    uint32_t xch, ts, tl;
    unsigned char *ug, *ur, *uc, *outp, *outq;
    auto setup_u = [&]() {
      xch = pin(base + OFF_K + (tid & 127) * 16);
      ug = pin(UPH ? scr + (d1 * HU_T + 32 + (ft >> 1)) * BT + ((ft & 1) * 4 + w4) * 1792 + lane * 4 : scr + (d1 * HU_T + 32 + ft) * BT + w4 * 3584 + lane * 4 + wg * 1792);
      const int n = UPH ? min(lane, 13) : wg ? min(lane, 11) : lane & 15;
      ur = pin(ug + (n < 14 ? n * 128 : (n - 2) * 128 + 1792));
      uc = pin(scr + CNT_OFF + (C_U + d1 + (lane & (UREP - 1)) * 4) * 128);
    };
    auto setup_out = [&]() {
      const uint32_t tb = base + OFF_K + 6144 + warp * 2560;
      ts = pin(tb + mi * 160 + r8 * 16); tl = pin(tb + t * 160 + g * 16);
      unsigned char* o = p.out + (mt * 64 + w4 * 16 + g) * 896 + dt * 224;
      outp = pin(o + th * 7168 + t * 16); outq = pin(o + (t >> 1) * 7168 + 192 + (t & 1) * 16);
    };
    auto give = [&](const float (&a)[56], int id) {
#pragma unroll
      for (int i = 0; i < 48; i += 16) sts128(xch + i * 128, pack2(a[i + 2], a[i + 3]), pack2(a[i + 6], a[i + 7]), pack2(a[i + 10], a[i + 11]), pack2(a[i + 14], a[i + 15]));
      named_arrive(id, 256);
    };
    auto take = [&](uint32_t (&r)[12], int id) {
      named_sync(id, 256);
#pragma unroll
      for (int i = 0; i < 3; i++) { const uint4 v = lds128(xch + i * 2048); r[i * 4] = v.x; r[i * 4 + 1] = v.y; r[i * 4 + 2] = v.z; r[i * 4 + 3] = v.w; }
    };
    float hv[32];
    auto keep_h = [&](int i) {
      const float hb0 = 0.5f * bf_lo(braw[i]), hb1 = 0.5f * bf_lo(braw[i + 1]);
#pragma unroll
      for (int j = 0; j < 32; j++) hv[j] = fmaf(acc[ai(j >> 1) + (j & 1)], 0.5f, j >= 4 && j < 8 ? hb1 : hb0);
    };
    auto take_h = [&](int i) {
      const float hb1 = 0.5f * bf_lo(braw[i + 1]);
      uint32_t r[12];
      take(r, 5);
#pragma unroll
      for (int j = 0; j < 12; j++) { hv[8 + 2 * j] = fmaf(bf_lo(r[j]), 0.5f, hb1); hv[9 + 2 * j] = fmaf(bf_hi(r[j]), 0.5f, hb1); }
    };
    uint4 Xr[4];
    auto get_x = [&]() {
      const uint32_t xr = base + OFF_Q + (w4 * 16 + g) * 224;
      mbar_wait(bars + B_RES, 0);
      Xr[0] = lds128(xr + (t >> 1) * 1792 + 192 + (t & 1) * 16);
#pragma unroll
      for (int i = 1; i < 4; i++) Xr[i] = lds128(xr + th * 1792 + t * 16 + (i - 1) * 64);
    };
    auto gelu = [&](int j) {
      const float h0 = hv[2 * j], h1 = hv[2 * j + 1];
      const float t0 = tanh_fast(h0 * fmaf(h0 * h0, 0.2854192648f, 1.5957691216f)), t1 = tanh_fast(h1 * fmaf(h1 * h1, 0.2854192648f, 1.5957691216f));
      stg32(ug + (ai(j) & 2) * 896 + (ai(j) >> 2) * 128, pack2(fmaf(h0, t0, h0), fmaf(h1, t1, h1)));
    };
    uint32_t Sv[16];
    auto gate = [&](int i) {
      uint32_t R[4];
#pragma unroll
      for (int q = 0; q < 4; q++) {
        const int j = i * 4 + q;
        const float h0 = hv[2 * j], h1 = hv[2 * j + 1];
        R[q] = hmul2(Sv[j], pack2(fmaf(h0, tanh_fast(h0), h0), fmaf(h1, tanh_fast(h1), h1)));
      }
      stsm4(ts + i * 640, R[0], R[1], R[2], R[3]);
    };
    auto leave = [&](int i) {
      __syncwarp();
      const uint4 v = lds128(tl + i * 640), x = Xr[i];
      stg128(i ? outp + (i - 1) * 64 : outq, hadd2(x.x, v.x), hadd2(x.y, v.y), hadd2(x.z, v.z), hadd2(x.w, v.w));
    };
    if (wg == 0) {
      named_sync(0, 256);
      OBS(tid == 96, 14);
      q_rest();
      named_arrive(6, 256);
      wg_wait<0>();
      if (tid == 0) mbar_arrive(bars + B_EMPTY + 7 * 8);
      q_pack();
      const uint32_t qst = base + OFF_Q + 8192 + (mi >> 1) * 1024 + (w4 * 16 + (mi & 1) * 8 + r8) * 16;
#pragma unroll
      for (int n = 0; n < 4; n++) stsm4(qst + n * 2048, Q[n][0], Q[n][1], Q[n][2], Q[n][3]);
      smem_fence();
      named_arrive(7, 256);
      OBS(tid == 32, 5);
      fresh(acc);
      setup_u();
      if (g1) {
        mbar_wait(bars, 0); mbar_wait(bars + 8, 0);
        if (TS) {
          const uint32_t tg = lds64(bars + B_T0).x;
          while (tg - gtime() - 1 < 1000u);
        }
        named_sync(0, 256);
        gemm_issue<1>(acc, base >> 4, base >> 4, 0);
        OBS(tid == 0, 20);
        gemm_loop<1>(acc, base, 1, 32, rel, 40, 1, tid == 32 ? J1 : tid == 64 ? J2 : tid == 96 ? J3 : -1, bars + B_GATE - 8 + w4 * 8);
        if (!UPH) mbar_wait(bars + B_ATT, 0);
        wg_wait<0>();
        OBS(tid == 0, 21);
        named_arrive(5, 256);
        mbar_arrive_if(rel, bars + B_EMPTY + 7 * 8);
#pragma unroll
        for (int h = 0; h < 2; h++) {
          const float hb = 0.5f * bf_lo(braw[h]);
#pragma unroll
          for (int n = 0; n < 14; n++) {
            const float h0 = fmaf(acc[4 * n + 2 * h], 0.5f, hb), h1 = fmaf(acc[4 * n + 2 * h + 1], 0.5f, hb);
            const float t0 = tanh_fast(h0 * fmaf(h0 * h0, 0.2854192648f, 1.5957691216f)), t1 = tanh_fast(h1 * fmaf(h1 * h1, 0.2854192648f, 1.5957691216f));
            stg32(ug + h * 14 * BT + n * 128, pack2(fmaf(h0, t0, h0), fmaf(h1, t1, h1)));
            if (n % UCH == UCH - 1 && n < 13) fence_code(8 + h * 16 + n);
          }
          const uint32_t v = (RB & 16) ? probe(ur + h * 14 * BT) : 0;
          if (h == 0 && OHOLD) mbar_arrive_if(tid == 32, bars + B_UD);
          if (h == 0 && UO) named_arrive(12, 256);
          settle(v);
          if (h == 0 && !UO) named_arrive(12, 256);
          if (w4) named_arrive(13 + h, 128);
          else { named_sync(13 + h, 128); publish(uc - CNT_OFF, h * 4); OBS(tid == 0, h ? 13 : 9); }
          if (h == 0 && U2W) __nanosleep(U2W);
          fence_code(40 + h);
        }
      } else {
        if (lane == 0 && w4) mbar_arrive(bars + B_GATE - 8 + w4 * 8);
      }
      setup_out();
      if (RESP != 1) get_x();
      uint32_t r[12];
      take(r, 3);
#pragma unroll
      for (int j = 0; j < 16; j++) Sv[j] = r[j < 4 ? 0 : j - 4];
      asm volatile("" :: "r"(r[0]), "r"(r[11]) : "memory");
      named_arrive(10, 256);
      if (RESP == 1) get_x();
      take_h(2);
    } else {
      const uint32_t dq = ((base + OFF_Q) >> 4) + (64u << 16), dk = (base + OFF_K) >> 4;
      const bool odd = g & 1, early = 2 * t + (g & 1) > g;
      uint32_t selA[5], selB[4];
#pragma unroll
      for (int j = 0; j < 5; j++) { selA[j] = j == w4 + (early ? 0 : 1) ? (odd ? 0x1044u : 0x4410u) : 0x4444u; }
#pragma unroll
      for (int j = 0; j < 4; j++) { selB[j] = j == w4 ? (odd ? 0x3244u : 0x4432u) : 0x4444u; }
      float Sc[2][40], Op[2][2][16];
      uint32_t A[2][5][4];
      auto scores = [&](int T) {
        fresh(Sc[0]); fresh(Sc[1]);
#pragma unroll
        for (int k = 0; k < 2; k++) {
#pragma unroll
          for (int hh = 0; hh < 2; hh++)
            if (T) wgmma_n80<0, 0>(Sc[hh], mkdesc(8, dq + 512 + hh * 256 + k * 128), mkdesc(112, dk + (8u << 16) + 896 + hh * 24 + k * 16), k);
            else wgmma_rs_n80<0>(Sc[hh], Q[hh * 2 + k], mkdesc(112, dk + (8u << 16) + hh * 24 + k * 16), k);
        }
      };
      auto softmax = [&](int T) {
        uint32_t L[2][2];
        auto pick = [&](int w) {
#pragma unroll
          for (int hh = 0; hh < 2; hh++) {
            const float* q = Sc[hh] + w * 8;
            auto at = [&](int i) { return odd ? q[i + 1] : q[i]; };
            L[hh][0] = pack2(early ? at(0) : at(8), early ? at(6) : at(14)); L[hh][1] = pack2(at(4), at(10));
          }
          asm volatile("" ::: "memory");
        };
        if (w4 & 2) { if (w4 & 1) pick(3); else pick(2); } else { if (w4 & 1) pick(1); else pick(0); }
#pragma unroll
        for (int hh = 0; hh < 2; hh++) {
          uint32_t a = hfma2(L[hh][0], SC_HI, hmul2(L[hh][0], SC_LO)), c = hfma2(L[hh][1], SC_HI, hmul2(L[hh][1], SC_LO));
          if (T == 0 && w4 == 0 && rb == 0) { if (early) a = 0xce6ece6eu; c = (c & 0xffff0000u) | 0xce6eu; }
          uint32_t mx = hmax2(a, c);
          mx = hmax2(mx, __shfl_xor_sync(0xffffffffu, mx, 1));
          mx = hmax2(mx, __shfl_xor_sync(0xffffffffu, mx, 2));
          uint32_t pp[2];
#pragma unroll
          for (int h = 0; h < 2; h++) {
            const float m = h ? bf_hi(mx) : bf_lo(mx);
            const float p0 = ex2_fast(((h ? bf_hi(a) : bf_lo(a)) - m) * LOG2E), p1 = ex2_fast(((h ? bf_hi(c) : bf_lo(c)) - m) * LOG2E);
            float sm = p0 + p1;
            sm += __shfl_xor_sync(0xffffffffu, sm, 1);
            sm += __shfl_xor_sync(0xffffffffu, sm, 2);
            const float inv = rcp_fast(sm);
            pp[h] = pack2(p0 * inv, p1 * inv);
          }
#pragma unroll
          for (int j = 0; j < 5; j++) {
            A[hh][j][0] = place(pp[0], selA[j]); A[hh][j][1] = j ? place(pp[1], selB[j ? j - 1 : 0]) : 0u;
            A[hh][j][2] = j < 4 ? place(pp[0], selB[j & 3]) : 0u; A[hh][j][3] = place(pp[1], selA[j]);
          }
        }
      };
      auto values = [&](int T) {
        fresh(Op[T][0]); fresh(Op[T][1]);
#pragma unroll
        for (int j = 0; j < 5; j++)
#pragma unroll
          for (int hh = 0; hh < 2; hh++) {
            wgmma_rs_n32<1>(Op[T][hh], A[hh][j], mkdesc(8, dk + (112u << 16) + 56 + T * 896 + hh * 24 + j * 224), j);
          }
        wg_commit();
      };
      uint32_t Ob[2][14];
      auto pack = [&](int T) {
        const float (&O)[2][16] = Op[T];
#pragma unroll
        for (int n = 0; n < 7; n++)
#pragma unroll
          for (int h = 0; h < 2; h++) {
            if (n < 3) Ob[T][n * 2 + h] = pack2(O[0][n * 4 + 2 * h], O[0][n * 4 + 2 * h + 1]);
            else if (n == 3) Ob[T][n * 2 + h] = pack2(t < 2 ? O[0][12 + 2 * h] : O[1][2 * h], t < 2 ? O[0][13 + 2 * h] : O[1][2 * h + 1]);
            else Ob[T][n * 2 + h] = pack2(O[1][(n - 3) * 4 + 2 * h], O[1][(n - 3) * 4 + 2 * h + 1]);
          }
      };
      smem_fence();
      named_sync(6, 256);
      OBS(tid == 224, 26);
      q_rest();
      named_sync(7, 256);
      wg_fence();
      scores(1);
      wg_commit();
      named_arrive_if(g1, 0, 256);
      wg_wait<2>();
      if (tid == 128) mbar_arrive(bars + B_EMPTY + 7 * 8);
      wg_wait<0>();
      OBS(tid == 160, 10);
      softmax(1);
      q_pack();
      OBS(tid == 160, 30);
      mbar_wait(bars + B_HALO, 0);
      OBS(tid == 160, 7);
      if (RESP >= 2) named_sync(11, 128);
      mbar_wait(bars + B_GATE, 0);
      wg_fence();
      scores(0);
      values(1);
      if (RESP == 2) mbar_arrive_if(tid == 192, bars + B_QD);
      wg_wait<0>();
      OBS(tid == 160, 33);
      unsigned char* og = scr + O_OFF + rb * 2 * 57344 + hp * 7168 + w4 * 256 + lane * 4;
      uint32_t seen[6], tn = 0;
      auto put = [&](int T) {
#pragma unroll
        for (int n = 0; n < 14; n++) { stg32(og + T * 57344 + (n >> 1) * 1024 + (n & 1) * 128, Ob[T][n]); if (n == 5 || n == 11 || n == 13) seen[T * 3 + n / 6] = (RB & 8) ? probe(og + T * 57344 + ((n >> 1) - (n == 13 ? 0 : min(g, 2))) * 1024 + (t & 1) * 128) : 0;
          if (OGAP && n % 2 == 1 && (T || n < 13)) { tn += OGAP; while ((int)(clock() - tn) < 0) __nanosleep(16); }
          else if (!OGAP && n % OGRP == OGRP - 1 && (T || n < 13 || !OLAST)) __nanosleep(OSLEEP); }
      };
      if (OMODE == 1) { pack(1); put(1); }
      softmax(0);
      if (OMODE == 2) { pack(1); put(1); }
      mbar_wait(bars + B_GATE + 8, 0);
      wg_fence();
      values(0);
      if (RESP == 3) mbar_arrive_if(tid == 192, bars + B_QD);
      if (OMODE == 3) { if (OGAP) tn = clock(); pack(1); put(1); }
      wg_wait<0>();
      OBS(tid == 160, 35);
      named_sync(11, 128);
      if (tid == 160) mbar_arrive(bars + B_ATT);
      if (OMODE == 0) pack(1);
      pack(0);
      if (J3 > J2) mbar_wait(bars + B_GATE + 16, 0);
      if (OMODE == 0) put(1);
      put(0);
      OBS(tid == 160, 28);
      if (RB & 8) settle(seen[0] ^ seen[1] ^ seen[2] ^ seen[3] ^ seen[4] ^ seen[5]);
      named_sync(11, 128);
      if (warp == 4) publish(scr, C_O + rb);
      OBS(tid == 160, 8);
      setup_u(); setup_out();
      float as[56];
      uint32_t uv = 0;
      if (g1) named_sync(5, 256);
      if (RESP != 1) get_x();
      mbar_wait(bars, 0);
      if (g1) { named_sync(12, 256); if (UO > 1) { const uint32_t c = clock(); while ((uint32_t)clock() - c < UO); } }
      fresh(as);
      gemm_issue<0>(as, base >> 4, base >> 4, 0);
      OBS(tid == 128, 22);
      gemm_loop<0>(as, base, 1, 7, rel, 104);
      fresh(acc);
      if (SEARLY) { wg_wait<0>(); mbar_arrive_if(rel, bars + B_EMPTY + 6 * 8); give(as, 3); if (RESP != 1 && !XE) get_x(); }
      gemm_stage<1>(acc, base, 7, 0);
      OBS(tid == 128, 24);
      if (!SEARLY) { wg_wait<1>(); mbar_arrive_if(rel, bars + B_EMPTY + 6 * 8); give(as, 3); }
#pragma unroll
      for (int j = 0; j < 16; j++) Sv[j] = pack2(as[ai(j)], as[ai(j) + 1]);
      gemm_loop<1, NX>(acc, base, 8, 35, rel, 65);
      if (RESP == 1) get_x();
      named_sync(10, 256);
      wg_wait<0>();
      OBS(tid == 128, 25);
      give(acc, 5);
      fence_code(31);
      keep_h(2);
      gate(0); leave(0);
    }
    {
#pragma unroll
      for (int i = 1; i < 4; i++) { gate(i); leave(i); }
      OBS(tid == 128, 27);
    }
  }
}

typedef CUresult (*EncFn)(CUtensorMap*, CUtensorMapDataType, cuuint32_t, void*, const cuuint64_t*, const cuuint64_t*, const cuuint32_t*,
                          const cuuint32_t*, CUtensorMapInterleave, CUtensorMapSwizzle, CUtensorMapL2promotion, CUtensorMapFloatOOBfill);
void enc(EncFn f, CUtensorMap* m, const void* ptr, cuuint64_t d0, cuuint64_t d1, cuuint64_t d2, cuuint64_t s1, cuuint64_t s2, cuuint32_t b1, cuuint32_t b2, cuuint32_t b0 = 64) {
  const cuuint64_t gd[3] = {d0, d1, d2}, gs[2] = {s1 * 2, s2 * 2};
  const cuuint32_t bx[3] = {b0, b1, b2}, es[3] = {1, 1, 1};
  f(m, CU_TENSOR_MAP_DATA_TYPE_BFLOAT16, 3, (void*)ptr, gd, gs, bx, es, CU_TENSOR_MAP_INTERLEAVE_NONE, b0 == 64 ? CU_TENSOR_MAP_SWIZZLE_128B : CU_TENSOR_MAP_SWIZZLE_NONE,
    CU_TENSOR_MAP_L2_PROMOTION_L2_128B, CU_TENSOR_MAP_FLOAT_OOB_FILL_NONE);
}
}

extern "C" void kernel_launch(void* const* d_in, const int* in_sizes, int n_in, void* d_out, int out_size) {
  (void)in_sizes; (void)n_in; (void)out_size;
  void* fp = nullptr;
  cudaDriverEntryPointQueryResult qr;
  cudaGetDriverEntryPoint("cuTensorMapEncodeTiled", &fp, cudaEnableDefault, &qr);
  EncFn f = (EncFn)fp;
  CUtensorMap m_x, m_wkv, m_wq, m_w1, m_w2, m_res;
  void* scr = nullptr;
  cudaGetSymbolAddress(&scr, g_scr);
  enc(f, &m_x, d_in[0], D_, S_, 1, D_, D_, 128 >> XSPLIT, 1);
  enc(f, &m_wkv, d_in[1], D_, D_, 3, 3 * D_, D_, 64, 2);
  enc(f, &m_wq, d_in[1], D_, D_, 3, 3 * D_, D_, 64, 1);
  enc(f, &m_w1, d_in[4], F_, S_, 1, F_, F_, 64, 1);
  if (UPH) enc(f, &m_w2, d_in[6], S_, 16, F_ / 16, S_, 16 * S_, 8, 8);
  else enc(f, &m_w2, d_in[6], S_, F_, 1, S_, S_, 64, 1);
  enc(f, &m_res, d_in[0], D_, S_, 1, D_, D_, 64, 1, 112);
  Params p;
  p.wqkv = (const unsigned char*)d_in[1]; p.wo = (const unsigned char*)d_in[2];
  p.w1 = (const unsigned char*)d_in[4]; p.b1 = (const unsigned char*)d_in[5];
  p.w2 = (const unsigned char*)d_in[6]; p.b2 = (const unsigned char*)d_in[7];
  p.out = (unsigned char*)d_out; p.scr = (unsigned char*)scr;
  cudaFuncSetAttribute(fused_kernel, cudaFuncAttributeMaxDynamicSharedMemorySize, SMEM_BYTES);
  fused_kernel<<<128, NTHREADS, SMEM_BYTES, cudaStreamPerThread>>>(m_x, m_wkv, m_wq, m_w1, m_w2, m_res, p);
}
```

```cpp
#include <cuda_runtime.h>
#include <cuda.h>
#include <cuda_bf16.h>
#include <stdint.h>

template<int TA, int TB> __device__ __forceinline__ void wgmma_n112(float (&d)[56], uint64_t da, uint64_t db, int sc) {
  asm volatile("{\n.reg .pred p;\nsetp.ne.b32 p, %58, 0;\n"
    "wgmma.mma_async.sync.aligned.m64n112k16.f32.bf16.bf16 {%0, %1, %2, %3, %4, %5, %6, %7, %8, %9, %10, %11, %12, %13, %14, %15, %16, %17, %18, %19, %20, %21, %22, %23, %24, %25, %26, %27, %28, %29, %30, %31, %32, %33, %34, %35, %36, %37, %38, %39, %40, %41, %42, %43, %44, %45, %46, %47, %48, %49, %50, %51, %52, %53, %54, %55}, %56, %57, p, 1, 1, %59, %60;\n}\n"
    : "+f"(d[0]), "+f"(d[1]), "+f"(d[2]), "+f"(d[3]), "+f"(d[4]), "+f"(d[5]), "+f"(d[6]), "+f"(d[7]), "+f"(d[8]), "+f"(d[9]), "+f"(d[10]), "+f"(d[11]), "+f"(d[12]), "+f"(d[13]), "+f"(d[14]), "+f"(d[15]), "+f"(d[16]), "+f"(d[17]), "+f"(d[18]), "+f"(d[19]), "+f"(d[20]), "+f"(d[21]), "+f"(d[22]), "+f"(d[23]), "+f"(d[24]), "+f"(d[25]), "+f"(d[26]), "+f"(d[27]), "+f"(d[28]), "+f"(d[29]), "+f"(d[30]), "+f"(d[31]), "+f"(d[32]), "+f"(d[33]), "+f"(d[34]), "+f"(d[35]), "+f"(d[36]), "+f"(d[37]), "+f"(d[38]), "+f"(d[39]), "+f"(d[40]), "+f"(d[41]), "+f"(d[42]), "+f"(d[43]), "+f"(d[44]), "+f"(d[45]), "+f"(d[46]), "+f"(d[47]), "+f"(d[48]), "+f"(d[49]), "+f"(d[50]), "+f"(d[51]), "+f"(d[52]), "+f"(d[53]), "+f"(d[54]), "+f"(d[55])
    : "l"(da), "l"(db), "r"(sc), "n"(TA), "n"(TB));
}

template<int TA, int TB> __device__ __forceinline__ void wgmma_n80(float (&d)[40], uint64_t da, uint64_t db, int sc) {
  asm volatile("{\n.reg .pred p;\nsetp.ne.b32 p, %42, 0;\n"
    "wgmma.mma_async.sync.aligned.m64n80k16.f32.bf16.bf16 {%0, %1, %2, %3, %4, %5, %6, %7, %8, %9, %10, %11, %12, %13, %14, %15, %16, %17, %18, %19, %20, %21, %22, %23, %24, %25, %26, %27, %28, %29, %30, %31, %32, %33, %34, %35, %36, %37, %38, %39}, %40, %41, p, 1, 1, %43, %44;\n}\n"
    : "+f"(d[0]), "+f"(d[1]), "+f"(d[2]), "+f"(d[3]), "+f"(d[4]), "+f"(d[5]), "+f"(d[6]), "+f"(d[7]), "+f"(d[8]), "+f"(d[9]), "+f"(d[10]), "+f"(d[11]), "+f"(d[12]), "+f"(d[13]), "+f"(d[14]), "+f"(d[15]), "+f"(d[16]), "+f"(d[17]), "+f"(d[18]), "+f"(d[19]), "+f"(d[20]), "+f"(d[21]), "+f"(d[22]), "+f"(d[23]), "+f"(d[24]), "+f"(d[25]), "+f"(d[26]), "+f"(d[27]), "+f"(d[28]), "+f"(d[29]), "+f"(d[30]), "+f"(d[31]), "+f"(d[32]), "+f"(d[33]), "+f"(d[34]), "+f"(d[35]), "+f"(d[36]), "+f"(d[37]), "+f"(d[38]), "+f"(d[39])
    : "l"(da), "l"(db), "r"(sc), "n"(TA), "n"(TB));
}

template<int TB> __device__ __forceinline__ void wgmma_rs_n120(float (&d)[60], const uint32_t (&a)[4], uint64_t db, int sc) {
  asm volatile("{\n.reg .pred p;\nsetp.ne.b32 p, %65, 0;\n"
    "wgmma.mma_async.sync.aligned.m64n120k16.f32.bf16.bf16 {%0, %1, %2, %3, %4, %5, %6, %7, %8, %9, %10, %11, %12, %13, %14, %15, %16, %17, %18, %19, %20, %21, %22, %23, %24, %25, %26, %27, %28, %29, %30, %31, %32, %33, %34, %35, %36, %37, %38, %39, %40, %41, %42, %43, %44, %45, %46, %47, %48, %49, %50, %51, %52, %53, %54, %55, %56, %57, %58, %59}, {%60, %61, %62, %63}, %64, p, 1, 1, %66;\n}\n"
    : "+f"(d[0]), "+f"(d[1]), "+f"(d[2]), "+f"(d[3]), "+f"(d[4]), "+f"(d[5]), "+f"(d[6]), "+f"(d[7]), "+f"(d[8]), "+f"(d[9]), "+f"(d[10]), "+f"(d[11]), "+f"(d[12]), "+f"(d[13]), "+f"(d[14]), "+f"(d[15]), "+f"(d[16]), "+f"(d[17]), "+f"(d[18]), "+f"(d[19]), "+f"(d[20]), "+f"(d[21]), "+f"(d[22]), "+f"(d[23]), "+f"(d[24]), "+f"(d[25]), "+f"(d[26]), "+f"(d[27]), "+f"(d[28]), "+f"(d[29]), "+f"(d[30]), "+f"(d[31]), "+f"(d[32]), "+f"(d[33]), "+f"(d[34]), "+f"(d[35]), "+f"(d[36]), "+f"(d[37]), "+f"(d[38]), "+f"(d[39]), "+f"(d[40]), "+f"(d[41]), "+f"(d[42]), "+f"(d[43]), "+f"(d[44]), "+f"(d[45]), "+f"(d[46]), "+f"(d[47]), "+f"(d[48]), "+f"(d[49]), "+f"(d[50]), "+f"(d[51]), "+f"(d[52]), "+f"(d[53]), "+f"(d[54]), "+f"(d[55]), "+f"(d[56]), "+f"(d[57]), "+f"(d[58]), "+f"(d[59])
    : "r"(a[0]), "r"(a[1]), "r"(a[2]), "r"(a[3]), "l"(db), "r"(sc), "n"(TB));
}

template<int TB> __device__ __forceinline__ void wgmma_rs_n56(float (&d)[28], const uint32_t (&a)[4], uint64_t db, int sc) {
  asm volatile("{\n.reg .pred p;\nsetp.ne.b32 p, %33, 0;\n"
    "wgmma.mma_async.sync.aligned.m64n56k16.f32.bf16.bf16 {%0, %1, %2, %3, %4, %5, %6, %7, %8, %9, %10, %11, %12, %13, %14, %15, %16, %17, %18, %19, %20, %21, %22, %23, %24, %25, %26, %27}, {%28, %29, %30, %31}, %32, p, 1, 1, %34;\n}\n"
    : "+f"(d[0]), "+f"(d[1]), "+f"(d[2]), "+f"(d[3]), "+f"(d[4]), "+f"(d[5]), "+f"(d[6]), "+f"(d[7]), "+f"(d[8]), "+f"(d[9]), "+f"(d[10]), "+f"(d[11]), "+f"(d[12]), "+f"(d[13]), "+f"(d[14]), "+f"(d[15]), "+f"(d[16]), "+f"(d[17]), "+f"(d[18]), "+f"(d[19]), "+f"(d[20]), "+f"(d[21]), "+f"(d[22]), "+f"(d[23]), "+f"(d[24]), "+f"(d[25]), "+f"(d[26]), "+f"(d[27])
    : "r"(a[0]), "r"(a[1]), "r"(a[2]), "r"(a[3]), "l"(db), "r"(sc), "n"(TB));
}

template<int TB> __device__ __forceinline__ void wgmma_rs_n32(float (&d)[16], const uint32_t (&a)[4], uint64_t db, int sc) {
  asm volatile("{\n.reg .pred p;\nsetp.ne.b32 p, %21, 0;\n"
    "wgmma.mma_async.sync.aligned.m64n32k16.f32.bf16.bf16 {%0, %1, %2, %3, %4, %5, %6, %7, %8, %9, %10, %11, %12, %13, %14, %15}, {%16, %17, %18, %19}, %20, p, 1, 1, %22;\n}\n"
    : "+f"(d[0]), "+f"(d[1]), "+f"(d[2]), "+f"(d[3]), "+f"(d[4]), "+f"(d[5]), "+f"(d[6]), "+f"(d[7]), "+f"(d[8]), "+f"(d[9]), "+f"(d[10]), "+f"(d[11]), "+f"(d[12]), "+f"(d[13]), "+f"(d[14]), "+f"(d[15])
    : "r"(a[0]), "r"(a[1]), "r"(a[2]), "r"(a[3]), "l"(db), "r"(sc), "n"(TB));
}

template<int TB> __device__ __forceinline__ void wgmma_rs_n80(float (&d)[40], const uint32_t (&a)[4], uint64_t db, int sc) {
  asm volatile("{\n.reg .pred p;\nsetp.ne.b32 p, %45, 0;\n"
    "wgmma.mma_async.sync.aligned.m64n80k16.f32.bf16.bf16 {%0, %1, %2, %3, %4, %5, %6, %7, %8, %9, %10, %11, %12, %13, %14, %15, %16, %17, %18, %19, %20, %21, %22, %23, %24, %25, %26, %27, %28, %29, %30, %31, %32, %33, %34, %35, %36, %37, %38, %39}, {%40, %41, %42, %43}, %44, p, 1, 1, %46;\n}\n"
    : "+f"(d[0]), "+f"(d[1]), "+f"(d[2]), "+f"(d[3]), "+f"(d[4]), "+f"(d[5]), "+f"(d[6]), "+f"(d[7]), "+f"(d[8]), "+f"(d[9]), "+f"(d[10]), "+f"(d[11]), "+f"(d[12]), "+f"(d[13]), "+f"(d[14]), "+f"(d[15]), "+f"(d[16]), "+f"(d[17]), "+f"(d[18]), "+f"(d[19]), "+f"(d[20]), "+f"(d[21]), "+f"(d[22]), "+f"(d[23]), "+f"(d[24]), "+f"(d[25]), "+f"(d[26]), "+f"(d[27]), "+f"(d[28]), "+f"(d[29]), "+f"(d[30]), "+f"(d[31]), "+f"(d[32]), "+f"(d[33]), "+f"(d[34]), "+f"(d[35]), "+f"(d[36]), "+f"(d[37]), "+f"(d[38]), "+f"(d[39])
    : "r"(a[0]), "r"(a[1]), "r"(a[2]), "r"(a[3]), "l"(db), "r"(sc), "n"(TB));
}

namespace {
constexpr int S_ = 2048, D_ = 448, F_ = 1792;
constexpr int NSLOT = 8, SLOT = 22528;
constexpr int OFF_X = 7 * 16384;
constexpr int OFF_WQ = 8 * 16384;
constexpr int OFF_Q = NSLOT * SLOT;
constexpr int OFF_K = OFF_Q + 16384;
constexpr int OFF_BAR = 14 * 16384;
constexpr int OFF_LN = OFF_BAR + 512;
constexpr int OFF_OBS = OFF_BAR + 640;
constexpr int SMEM_BYTES = OFF_OBS + 1024;
#define PACE1 540
#define PACE2 650
#define J1 9
#define J2 14
#define TS 3170
#define UP 170
#define WQA 4
#define SOBS 0
#define FREQ 0
#define KOBS 0
#define LANDOBS 0
#define OBS(c, i) do {} while (0)
#define OBSG(c, i, j) do {} while (0)
constexpr int NTHREADS = 384;
constexpr float LOG2E = 1.4426950408889634f;
constexpr uint32_t SC_HI = 0x3e423e42u, SC_LO = 0xb9f7b9f7u;
constexpr int BT = 14336;

constexpr int HU_T = 67;
constexpr int O_OFF = 4 * HU_T * BT;
constexpr int HALO_OFF = O_OFF + 32 * 7 * 8192;
constexpr int CNT_OFF = HALO_OFF + 128 * 3584;
constexpr int SCR_BYTES = CNT_OFF + 160 * 128;
constexpr int C_U = 0, C_O = 8, C_H = 24, C_WO = 25, C_TK = 26, C_HALO = 32;
__device__ __align__(1024) unsigned char g_scr[SCR_BYTES];

__device__ __forceinline__ uint32_t smem_u32(const void* p) { return (uint32_t)__cvta_generic_to_shared(p); }
__device__ __forceinline__ void mbar_init(uint32_t bar, uint32_t cnt) { asm volatile("mbarrier.init.shared::cta.b64 [%0], %1;" :: "r"(bar), "r"(cnt)); }
__device__ __forceinline__ void mbar_expect_tx(uint32_t bar, uint32_t bytes) { asm volatile("mbarrier.arrive.expect_tx.shared::cta.b64 _, [%0], %1;" :: "r"(bar), "r"(bytes) : "memory"); }
__device__ __forceinline__ void mbar_arrive_if(uint32_t c, uint32_t bar) { asm volatile("{\n.reg .pred q;\nsetp.ne.u32 q, %1, 0;\n@q mbarrier.arrive.shared::cta.b64 _, [%0];\n}" :: "r"(bar), "r"(c) : "memory"); }
__device__ __forceinline__ void mbar_arrive(uint32_t bar) { asm volatile("mbarrier.arrive.shared::cta.b64 _, [%0];" :: "r"(bar) : "memory"); }
__device__ __forceinline__ void mbar_wait(uint32_t bar, uint32_t parity) {
  asm volatile("{\n.reg .pred p;\n.reg .u32 n;\nmov.u32 n, 0;\nLAB_WAIT:\n"
               "mbarrier.try_wait.parity.shared::cta.b64 p, [%0], %1;\n@p bra DONE;\n"
               "add.u32 n, n, 1;\nsetp.lt.u32 p, n, 400000;\n@p bra LAB_WAIT;\ntrap;\nDONE:\n}" :: "r"(bar), "r"(parity) : "memory");
}
__device__ __forceinline__ uint32_t mbar_try(uint32_t bar, uint32_t parity) {
  uint32_t ok;
  asm volatile("{\n.reg .pred p;\nmbarrier.test_wait.parity.shared::cta.b64 p, [%1], %2;\nselp.u32 %0, 1, 0, p;\n}" : "=r"(ok) : "r"(bar), "r"(parity) : "memory");
  return ok;
}
__device__ __forceinline__ void tma3d(uint32_t dst, const CUtensorMap* m, int c0, int c1, int c2, uint32_t bar) {
  asm volatile("cp.async.bulk.tensor.3d.shared::cluster.global.mbarrier::complete_tx::bytes [%0], [%1, {%3, %4, %5}], [%2];"
               :: "r"(dst), "l"(m), "r"(bar), "r"(c0), "r"(c1), "r"(c2) : "memory");
}
__device__ __forceinline__ void bulk_g2s(uint32_t dst, const void* src, uint32_t bytes, uint32_t bar) {
  asm volatile("cp.async.bulk.shared::cluster.global.mbarrier::complete_tx::bytes [%0], [%1], %2, [%3];" :: "r"(dst), "l"(src), "r"(bytes), "r"(bar) : "memory");
}
__device__ __forceinline__ void wg_fence() { asm volatile("wgmma.fence.sync.aligned;" ::: "memory"); }
__device__ __forceinline__ void wg_commit() { asm volatile("wgmma.commit_group.sync.aligned;" ::: "memory"); }
template <int N> __device__ __forceinline__ void wg_wait() { asm volatile("wgmma.wait_group.sync.aligned %0;" :: "n"(N) : "memory"); }
__device__ __forceinline__ void smem_fence() { asm volatile("fence.proxy.async.shared::cta;" ::: "memory"); }
__device__ __forceinline__ void stg128(void* p, uint32_t a, uint32_t b, uint32_t c, uint32_t d) { asm volatile("st.global.v4.u32 [%0], {%1,%2,%3,%4};" :: "l"(p), "r"(a), "r"(b), "r"(c), "r"(d) : "memory"); }
__device__ __forceinline__ void stg32(void* p, uint32_t v) { asm volatile("st.global.u32 [%0], %1;" :: "l"(p), "r"(v) : "memory"); }
__device__ __forceinline__ uint4 ldg128(const void* p) { uint4 v; asm volatile("ld.global.nc.L1::no_allocate.v4.u32 {%0,%1,%2,%3}, [%4];" : "=r"(v.x), "=r"(v.y), "=r"(v.z), "=r"(v.w) : "l"(p)); return v; }
__device__ __forceinline__ void publish(unsigned char* scr, int i) {
  asm volatile("{\n.reg .pred q;\nelect.sync _|q, 0xffffffff;\n@q red.relaxed.gpu.global.inc.u32 [%0], 0xffffffff;\n}" :: "l"(scr + CNT_OFF + i * 128) : "memory");
}
__device__ __forceinline__ uint32_t probe(const unsigned char* p) { uint32_t v; asm volatile("ld.relaxed.gpu.global.u32 %0, [%1];" : "=r"(v) : "l"(p) : "memory"); return v; }
__device__ __forceinline__ void settle(uint32_t v) {
  asm volatile("{\n.reg .pred q;\nsetp.eq.u32 q, %0, 0x7fc1dead;\n@q st.volatile.shared.u32 [%1], %0;\n}" :: "r"(v), "r"(1024 + OFF_BAR + 376) : "memory");
  __syncwarp();
}
__device__ __forceinline__ uint32_t spin_ge(unsigned char* scr, int i, unsigned target) {
  uint32_t v;
  asm volatile("{\n.reg .pred p;\n.reg .u32 n;\nmov.u32 n, 0;\nLAB_SPIN:\n"
               "ld.relaxed.gpu.global.u32 %0, [%1];\nsetp.ge.u32 p, %0, %2;\nvote.sync.all.pred p, p, 0xffffffff;\n@p bra DONE;\n"
               "add.u32 n, n, 1;\nsetp.lt.u32 p, n, 4000000;\n@p bra LAB_SPIN;\ntrap;\nDONE:\n}" : "=&r"(v) : "l"(scr + CNT_OFF + i * 128), "r"(target) : "memory");
  return v;
}
__device__ __forceinline__ int lane_id() { int l; asm volatile("mov.u32 %0, %%laneid;" : "=r"(l)); return l; }
__device__ __forceinline__ uint32_t pin(uint32_t v) { return __shfl_xor_sync(0xffffffffu, v, blockIdx.y); }
__device__ __forceinline__ unsigned char* pin(unsigned char* p) { return (unsigned char*)(((uint64_t)pin((uint32_t)((uint64_t)p >> 32)) << 32) | pin((uint32_t)(uint64_t)p)); }
__device__ __forceinline__ uint32_t gtime() { uint32_t g; asm volatile("mov.u32 %0, %%globaltimer_lo;" : "=r"(g)); return g; }
__device__ __forceinline__ bool elect() {
  uint32_t r; asm volatile("{\n.reg .pred p;\nelect.sync _|p, 0xffffffff;\nselp.u32 %0, 1, 0, p;\n}" : "=r"(r)); return r != 0;
}
__device__ __forceinline__ uint4 lds128(uint32_t a) { uint4 v; asm volatile("ld.shared.v4.u32 {%0,%1,%2,%3}, [%4];" : "=r"(v.x), "=r"(v.y), "=r"(v.z), "=r"(v.w) : "r"(a) : "memory"); return v; }
__device__ __forceinline__ uint2 lds64(uint32_t a) { uint2 v; asm volatile("ld.shared.v2.u32 {%0,%1}, [%2];" : "=r"(v.x), "=r"(v.y) : "r"(a) : "memory"); return v; }
__device__ __forceinline__ void sts128(uint32_t p, uint32_t a, uint32_t b, uint32_t c, uint32_t d) { asm volatile("st.shared.v4.u32 [%0], {%1,%2,%3,%4};" :: "r"(p), "r"(a), "r"(b), "r"(c), "r"(d) : "memory"); }
__device__ __forceinline__ void sts32(uint32_t a, float v) { asm volatile("st.shared.f32 [%0], %1;" :: "r"(a), "f"(v) : "memory"); }
__device__ __forceinline__ void named_sync(int id, int n) { asm volatile("bar.sync %0, %1;" :: "r"(id), "r"(n) : "memory"); }
__device__ __forceinline__ void named_arrive(int id, int n) { asm volatile("bar.arrive %0, %1;" :: "r"(id), "r"(n) : "memory"); }
__device__ __forceinline__ void named_arrive_if(uint32_t c, int id, int n) { asm volatile("{\n.reg .pred q;\nsetp.ne.u32 q, %2, 0;\n@q bar.arrive %0, %1;\n}" :: "r"(id), "r"(n), "r"(c) : "memory"); }
__device__ __forceinline__ uint64_t mkdesc(uint32_t hi, uint32_t lo) { return ((uint64_t)hi << 32) | lo; }
constexpr uint32_t HI_SW128 = 0x40000040u;
__device__ __forceinline__ uint32_t pack2(float lo, float hi) { uint32_t r; asm("cvt.rn.bf16x2.f32 %0, %1, %2;" : "=r"(r) : "f"(hi), "f"(lo)); return r; }
__device__ __forceinline__ float bf_lo(uint32_t v) { return __uint_as_float(v << 16); }
__device__ __forceinline__ float bf_hi(uint32_t v) { return __uint_as_float(v & 0xffff0000u); }
__device__ __forceinline__ float rbf(float x) { return bf_lo(pack2(x, 0.f)); }
__device__ __forceinline__ uint32_t hsub2(uint32_t a, uint32_t b) { uint32_t r; asm("sub.rn.bf16x2 %0, %1, %2;" : "=r"(r) : "r"(a), "r"(b)); return r; }
__device__ __forceinline__ uint32_t hadd2(uint32_t a, uint32_t b) { uint32_t r; asm("add.rn.bf16x2 %0, %1, %2;" : "=r"(r) : "r"(a), "r"(b)); return r; }
__device__ __forceinline__ uint32_t place(uint32_t v, uint32_t sel) { uint32_t r; asm volatile("prmt.b32 %0, %1, 0, %2;" : "=r"(r) : "r"(v), "r"(sel)); return r; }
__device__ __forceinline__ uint32_t hmax2(uint32_t a, uint32_t b) { uint32_t r; asm("max.bf16x2 %0, %1, %2;" : "=r"(r) : "r"(a), "r"(b)); return r; }
__device__ __forceinline__ uint32_t hmul2(uint32_t a, uint32_t b) { uint32_t r; asm("mul.rn.bf16x2 %0, %1, %2;" : "=r"(r) : "r"(a), "r"(b)); return r; }
__device__ __forceinline__ uint32_t hfma2(uint32_t a, uint32_t b, uint32_t c) { uint32_t r; asm("fma.rn.bf16x2 %0, %1, %2, %3;" : "=r"(r) : "r"(a), "r"(b), "r"(c)); return r; }
__device__ __forceinline__ float tanh_fast(float x) { float r; asm("tanh.approx.f32 %0, %1;" : "=f"(r) : "f"(x)); return r; }
__device__ __forceinline__ float rcp_fast(float x) { float r; asm("rcp.approx.ftz.f32 %0, %1;" : "=f"(r) : "f"(x)); return r; }
__device__ __forceinline__ float ex2_fast(float x) { float r; asm("ex2.approx.ftz.f32 %0, %1;" : "=f"(r) : "f"(x)); return r; }
__device__ __forceinline__ void mma16816(float (&c)[4], uint32_t a0, uint32_t a1, uint32_t a2, uint32_t a3, uint32_t b0, uint32_t b1) {
  asm volatile("mma.sync.aligned.m16n8k16.row.col.f32.bf16.bf16.f32 {%0,%1,%2,%3}, {%4,%5,%6,%7}, {%8,%9}, {%0,%1,%2,%3};"
               : "+f"(c[0]), "+f"(c[1]), "+f"(c[2]), "+f"(c[3]) : "r"(a0), "r"(a1), "r"(a2), "r"(a3), "r"(b0), "r"(b1));
}
__device__ __forceinline__ void ldsm4(uint32_t (&r)[4], uint32_t addr) {
  asm volatile("ldmatrix.sync.aligned.m8n8.x4.shared.b16 {%0,%1,%2,%3}, [%4];" : "=r"(r[0]), "=r"(r[1]), "=r"(r[2]), "=r"(r[3]) : "r"(addr) : "memory");
}
__device__ __forceinline__ void stsm4(uint32_t addr, uint32_t a, uint32_t b, uint32_t c, uint32_t d) {
  asm volatile("stmatrix.sync.aligned.m8n8.x4.shared.b16 [%0], {%1,%2,%3,%4};" :: "r"(addr), "r"(a), "r"(b), "r"(c), "r"(d) : "memory");
}

__device__ __forceinline__ float ln_rstd(float var, float eps = 1e-5f) {
  float sd;
  asm("sqrt.approx.ftz.f32 %0, %1;" : "=f"(sd) : "f"(rbf(rbf(var) + eps)));
  return rcp_fast(rbf(sd));
}
__device__ __forceinline__ float ln_var(float mean, float sq) { return fmaxf(fmaf(-mean, mean, sq * (1.0f / D_)), 0.f); }
struct LnC { uint32_t m, rh, rl; };
__device__ __forceinline__ LnC ln_consts(float sum, float sq, float eps) {
  const float mean = sum * (1.0f / D_), r = ln_rstd(ln_var(mean, sq), eps), rh = rbf(r);
  LnC c; c.m = pack2(mean, mean); c.rh = pack2(rh, rh); c.rl = pack2(r - rh, r - rh);
  return c;
}
__device__ __forceinline__ uint32_t ln_apply(uint32_t x, const LnC& c) {
  uint32_t d = hsub2(x, c.m);
  return hfma2(d, c.rh, hmul2(d, c.rl));
}

__device__ __forceinline__ void fence_code(int id) {
  asm volatile("{\n.reg .pred q;\nLAB_F:\nsetp.eq.u32 q, %0, %1;\n@q st.volatile.shared.u32 [%2], %2;\n@q bra LAB_F;\n}" :: "r"(blockIdx.x), "r"(0x70000000 + id), "r"(0) : "memory");
}
template <int N> __device__ __forceinline__ void fresh(float (&a)[N]) {
#pragma unroll
  for (int i = 0; i < N; i++) asm volatile("" : "=f"(a[i]));
}
constexpr int B_EMPTY = 64, B_U1 = 128, B_U2 = 136, B_WQ = 144, B_WQ2 = 152, B_HIN = 160, B_HALO = 168, B_GATE = 176, B_ATT = 192, B_RES = 200, B_WO = 208, B_O = 216;
constexpr int B_KV = 256, B_TAG = 360, B_T0 = 368, B_X = 384;

template <int TA>
__device__ __forceinline__ void gemm_issue(float (&acc)[56], uint32_t lo, int sc) {
  wg_fence();
#pragma unroll
  for (int k = 0; k < 4; k++)
    wgmma_n112<TA, 1>(acc, mkdesc(TA ? HI_SW128 : 8, lo + (TA ? 512u << 16 : 64u << 16) + k * 128), mkdesc(8, lo + (112u << 16) + 512 + k * 224), sc | k);
  wg_commit();
}
template <int TA>
__device__ __forceinline__ void gemm_loop(float (&acc)[56], uint32_t base, int it, int end, bool rel, int oi, uint32_t ok = 0, int gate_it = -1, uint32_t gate = 0) {
#pragma unroll 1
  for (; it < end;) {
    if (__builtin_expect(!ok, 0)) mbar_wait(base + OFF_BAR + (it & 7) * 8, (it >> 3) & 1);
    gemm_issue<TA>(acc, (base >> 4) + (it & 7) * (SLOT >> 4), 1);
    OBS(SOBS && rel, oi + it);
    it++;
    ok = mbar_try(base + OFF_BAR + (it & 7) * 8, (it >> 3) & 1);
    wg_wait<1>();
    if (rel || it == gate_it) mbar_arrive(rel ? base + OFF_BAR + B_EMPTY + ((it - 2) & 7) * 8 : gate);
  }
}
template <int S1, int S2>
__device__ __forceinline__ void produce_box(uint32_t base, int it, int end, const CUtensorMap* mp, int c0, int c1) {
#pragma unroll 1
  for (int c2 = 0; it < end; it++, c1 += S1, c2 += S2) {
    const uint32_t fb = base + OFF_BAR + (it & 7) * 8;
    mbar_wait(fb + B_EMPTY, (it >> 3) & 1);
    if (elect()) { mbar_expect_tx(fb, 8192); tma3d(base + (it & 7) * SLOT, mp, c0, c1, c2, fb); }
  }
}
template <int PER>
__device__ __forceinline__ void produce_lin(uint32_t base, int it, int end, const unsigned char* src, uint32_t bytes, uint32_t tn = 0) {
#pragma unroll 1
  for (; it < end; it++) {
    const uint32_t fb = base + OFF_BAR + (it & 7) * 8;
    mbar_wait(fb + B_EMPTY, (it >> 3) & 1);
    if (PER) { while ((int)(clock() - tn) < 0); tn += PER; }
    if (elect()) { mbar_expect_tx(fb, bytes); bulk_g2s(base + (it & 7) * SLOT + (bytes & 2048) * 4, src, bytes, fb); }
    src += bytes;
  }
}

__device__ __forceinline__ void retile_wo(const unsigned char* wo, unsigned char* scr, int u, int lane) {
  const int r8 = lane & 7, mi = lane >> 3;
  const unsigned char* src = wo + ((u >> 1) * 8 + r8) * 896 + ((u & 1) * 28 + mi) * 16;
  unsigned char* dst = scr + ((u & 1) * 2 * HU_T + 60 + (u >> 4)) * BT + ((u >> 1) & 7) * 1792 + mi * 128 + r8 * 16;
  uint4 v[7];
#pragma unroll
  for (int i = 0; i < 7; i++) v[i] = ldg128(src + i * 64);
#pragma unroll
  for (int i = 0; i < 7; i++) stg128(dst + i * 512 + ((i * 4 + mi) / 14) * (HU_T * BT - 1792), v[i].x, v[i].y, v[i].z, v[i].w);
}

struct Params {
  const unsigned char *wqkv, *wo, *w1, *b1, *w2, *b2;
  unsigned char *out, *scr;
};

__global__ void __launch_bounds__(NTHREADS, 1)
fused_kernel(const __grid_constant__ CUtensorMap m_x, const __grid_constant__ CUtensorMap m_wkv, const __grid_constant__ CUtensorMap m_wq,
             const __grid_constant__ CUtensorMap m_w1, const __grid_constant__ CUtensorMap m_w2, const __grid_constant__ CUtensorMap m_res, const Params p) {
  extern __shared__ __align__(1024) unsigned char smem_raw[];
  constexpr uint32_t base = 1024, bars = base + OFF_BAR;
  const int tid = threadIdx.x, lane = tid & 31, b = blockIdx.x;
  const int rb = (b >> 2) & 15, hp = ((b >> 6) << 2) | (b & 3);
  const int wcol = hp * 56 - (hp & 1) * 8;
  auto load_wq = [&](int s0, int s1, uint32_t bar) {
    mbar_expect_tx(bar, (s1 - s0) * 8192);
#pragma unroll 1
    for (int s = s0; s < s1; s++) tma3d(base + OFF_WQ + s * 8192, &m_wq, wcol, s * 64, 0, bar);
  };
  auto load_kv = [&](int s) { mbar_expect_tx(bars + B_KV + s * 8, 16384); tma3d(base + s * 16384, &m_wkv, wcol, s * 64, 1, bars + B_KV + s * 8); };
  if (tid < 32) {
    if (elect()) {
#pragma unroll
      for (int i = 0; i < 7; i++) mbar_init(bars + B_X + i * 8, 1);
      asm volatile("fence.mbarrier_init.release.cluster;" ::: "memory");
#pragma unroll
      for (int i = 0; i < 7; i++) { mbar_expect_tx(bars + B_X + i * 8, 8192); tma3d(base + OFF_X + i * 16384 + 8192, &m_x, i * 64, rb * 128 + 64, 0, bars + B_X + i * 8); }
#pragma unroll
      for (int i = 0; i < 7; i++) { mbar_init(bars + B_KV + i * 8, 1); mbar_init(bars + B_X + 64 + i * 8, 1); }
      asm volatile("fence.mbarrier_init.release.cluster;" ::: "memory");
      load_kv(0);
#pragma unroll
      for (int i = 0; i < 7; i++) { mbar_expect_tx(bars + B_X + 64 + i * 8, 8192); tma3d(base + OFF_X + i * 16384, &m_x, i * 64, rb * 128, 0, bars + B_X + 64 + i * 8); }
      load_kv(1);
    }
  }
  const int warp = __shfl_sync(0xffffffffu, tid >> 5, 0);
  if (warp == 1) {
    if (elect()) {
#pragma unroll
      for (int i = 0; i < 28; i++) mbar_init(bars + i * 8, i < 16 ? 2 : 1);
      asm volatile("fence.mbarrier_init.release.cluster;" ::: "memory");
      if (smem_u32(smem_raw) != base) asm volatile("trap;");
    }
  }
  const int dt = b & 3, mt = b >> 2;
  const bool g1 = (b & 15) < 14;
  const int a1 = b - 2 * (b >> 4), ft = a1 >> 2, d1 = a1 & 3;
  const int g = lane >> 2, t = lane & 3, r8 = lane & 7, mi = lane >> 3;
  OBSG(FREQ && tid == 160, 128, 160);
  __syncthreads();
  if (warp >= 8) {
    asm volatile("setmaxnreg.dec.sync.aligned.u32 40;");
    const int pw = warp - 8;
    unsigned char* scr = p.scr;
    if (pw == 2) {
      mbar_wait(bars + B_X + 48, 0);
      if (b < 112 && lane < 28) asm volatile("prefetch.global.L2 [%0];" :: "l"(p.wqkv + (b * 4 + lane / 7) * 2688 + (lane % 7) * 128) : "memory");
      if (lane == 31) asm volatile("prefetch.tensormap [%0];" :: "l"(&m_wq) : "memory");
      __syncwarp();
    }
    if (pw == 3) {
      mbar_wait(bars + B_X, 0);
      if (elect()) {
#pragma unroll 1
        for (int i = 2; i < 7; i++) load_kv(i);
      }
      __syncwarp();
    }
    {
      const int c0 = pw * 14 + (mi >> 1);
      unsigned char* dst = scr + (pw * HU_T + rb * 2 + (hp >> 2)) * BT + ((hp & 3) * 2 + (mi & 1)) * 1792 + (mi >> 1) * 128 + r8 * 16;
      const uint32_t xs = base + OFF_X + (hp * 16 + (lane & 15)) * 128;
      uint4 H[7];
      named_sync(9, 160);
#pragma unroll
      for (int i = 0; i < 7; i++) H[i] = lds128(xs + ((c0 + 2 * i) >> 3) * 16384 + ((((c0 + 2 * i) & 7) ^ r8) << 4));
      asm volatile("" :: "r"(H[6].w), "r"(H[0].x) : "memory");
      if (pw != 3) named_arrive(8, 384);
      else {
        named_sync(8, 384);
        if (elect()) {
          if (g1) asm volatile("red.relaxed.gpu.global.max.u32 [%0], %1;" :: "l"(scr + CNT_OFF + C_H * 128 + 8), "r"(gtime()) : "memory");
          load_wq(0, WQA, bars + B_WQ);
        }
        __syncwarp();
      }
      const uint2 st = lds64(base + OFF_LN + (lane & 15) * 8);
      const float sum = __uint_as_float(st.x), mean = sum * (1.0f / D_), var = ln_var(mean, __uint_as_float(st.y));
      const float m = rbf(mean), r = ln_rstd(var), r2 = ln_rstd(var * r * r);
      const float nc = fmaf(m, (float)D_, -sum) * (1.0f / D_) * (r * r2);
      const uint32_t m2 = pack2(m, m), r2x = pack2(r * r2, r * r2), nc2 = pack2(nc, nc);
      auto f = [&](uint32_t v) { return hfma2(hsub2(v, m2), r2x, nc2); };
#pragma unroll
      for (int i = 0; i < 7; i++) stg128(dst + i * 256, f(H[i].x), f(H[i].y), f(H[i].z), f(H[i].w));
      if (pw != 1) named_arrive(4, 128);
    }
    const int lane = lane_id();
    if (pw == 0) {
      if (elect()) {
        asm volatile("prefetch.tensormap [%0];" :: "l"(&m_w1) : "memory");
        asm volatile("prefetch.tensormap [%0];" :: "l"(&m_w2) : "memory");
        asm volatile("prefetch.tensormap [%0];" :: "l"(&m_res) : "memory");
      }
      __syncwarp();
      const uint32_t e = probe(scr + CNT_OFF + C_H * 128 + 4) + 1;
      sts32(bars + B_TAG, __uint_as_float((e & 0x3fffu) | ((e << 2) & 0x3fff0000u)));
      named_arrive(1, 96);
      if (g1) produce_box<64, 0>(base, 0, 32, &m_w1, ft * 64, 0);
      mbar_wait(bars + B_ATT, 0);
      if (elect()) { mbar_expect_tx(bars + B_RES, BT); tma3d(base + OFF_Q, &m_res, dt * 112, mt * 64, 0, bars + B_RES); }
      mbar_wait(bars + B_WO, 0);
      produce_lin<0>(base, 0, 7, scr + (dt * HU_T + 60) * BT, BT);
#pragma unroll 1
      for (int h = 0; h < 2; h++) produce_box<0, 8>(base, 7 + h * 14, 21 + h * 14, &m_w2, mt * 64, h * 8);
    } else if (pw == 1) {
      named_sync(4, 128);
      const unsigned char* hl = scr + (rb * 2 + (hp >> 2)) * BT + (hp & 3) * 3584 + min(lane, 27) * 128;
      settle(probe(hl) ^ probe(hl + HU_T * BT) ^ probe(hl + 2 * HU_T * BT) ^ probe(hl + 3 * HU_T * BT));
      publish(scr, C_H);
      OBS(lane == 0, 4);
      if (elect()) load_wq(WQA, 7, bars + B_WQ2);
      __syncwarp();
      if (g1) {
        __nanosleep(200);
        const uint32_t v = spin_ge(scr + (lane & 1) * 8, C_H, lane & 1 ? 0 : 128);
        if (lane == 1) sts32(bars + B_T0, __uint_as_float(v + TS));
        __syncwarp();
        OBS(lane == 0, 16);
        produce_lin<0>(base, 0, 32, scr + d1 * HU_T * BT, BT);
      }
      mbar_wait(bars + B_O, 0);
      produce_lin<0>(base, 0, 7, scr + O_OFF + mt * 57344, 8192);
      const unsigned char* us = scr + (dt * HU_T + 32) * BT;
      mbar_wait(bars + B_EMPTY + 56, 0);
      if (elect()) mbar_expect_tx(bars + 56, BT);
      __syncwarp();
      spin_ge(scr, C_U + dt, 28);
      if (elect()) bulk_g2s(base + 7 * SLOT + 8192, us, BT, bars + 56);
      if (lane == 0) mbar_arrive(bars + B_U1);
      const uint32_t tu = clock();
      OBS(lane == 0, 18);
      produce_lin<UP>(base, 8, 15, us + BT, BT, tu + UP);
#pragma unroll 1
      for (int h = 0; h < 2; h++) {
        if (h) mbar_wait(bars + B_U2, 0);
        produce_lin<0>(base, 15 + h * 6, 21 + h * 14, us + (8 + h * 6) * BT, BT);
      }
      unsigned tk = 0;
      if (lane == 0) tk = atomicAdd((unsigned*)(scr + CNT_OFF + C_TK * 128), 1u);
      if (__shfl_sync(0xffffffffu, tk, 0) == 127) {
#pragma unroll 1
        for (int i = lane; i < 160; i += 32) *(unsigned*)(scr + CNT_OFF + i * 128) = 0;
        *(unsigned*)(scr + CNT_OFF + C_H * 128 + 8) = 0;
        publish(scr + 4, C_H);
      }
    } else if (pw == 2) {
      uint32_t tn = clock();
      const unsigned char* src = p.w1 + b * 4096 + lane * 128;
#pragma unroll 1
      for (int i = 0; i < 28 + FREQ * 2; i++) {
        while ((int)(clock() - tn) < 0) __nanosleep(20);
        if (i == 14 || i == 21) src = p.w2 + ((b >> 3) * 16 + (b & 7) + (i & 1) * 8) * 4096 + lane * 128;
        if (i < 28) asm volatile("prefetch.global.L2 [%0];" :: "l"(src) : "memory");
        OBSG(FREQ && lane == 0, 129 + i, 161 + i);
        src += (i < 14 ? 128 : 256) * 4096;
        tn += i < 14 ? PACE1 : PACE2;
      }
    } else {
      if (b < 112) retile_wo(p.wo, scr, b, lane_id());
      const int lane = lane_id();
      unsigned char* hg = scr + HALO_OFF + (rb * 8 + hp) * 3584;
      named_sync(1, 96);
      const uint32_t tag = lds64(bars + B_TAG).x;
      if (rb < 15) {
#pragma unroll
        for (int q = 0; q < 7; q += 4) {
          uint4 v[4];
#pragma unroll
          for (int i = q; i < q + 4 && i < 7; i++) v[i - q] = lds128(base + OFF_K + 8 * 3584 + i * 512 + lane * 16 + (i * 32 + lane < 112 && !(lane & 7) ? 1792 : 0));
#pragma unroll
          for (int i = q; i < q + 4 && i < 7; i++) stg128(hg + i * 512 + lane * 16, (lane & 7) == (i * 32 + lane < 112) ? tag : v[i - q].x, v[i - q].y, v[i - q].z, v[i - q].w);
        }
        publish(scr, C_HALO + rb * 8 + hp);
      }
      OBS(lane == 0, 29);
      if (rb > 0) {
        spin_ge(scr, C_HALO + (rb - 1) * 8 + hp, 1);
        const uint32_t la = base + OFF_K + min(lane, 27) * 128;
#pragma unroll 1
        for (int n = 0;; n++) {
          if (elect()) { mbar_expect_tx(bars + B_HIN, 3584); bulk_g2s(base + OFF_K, hg - 8 * 3584, 3584, bars + B_HIN); }
          __syncwarp();
          mbar_wait(bars + B_HIN, n & 1);
          if (__all_sync(0xffffffffu, lds64(la + (lane < 14 ? 16 : 0)).x == tag)) break;
          if (n > 1000000) asm volatile("trap;");
        }
        if (lane < 14) { const uint4 v = lds128(la); sts128(la + 1792, v.x, v.y, v.z, v.w); }
      } else {
#pragma unroll
        for (int i = 0; i < 7; i++) sts128(base + OFF_K + i * 512 + lane * 16, 0, 0, 0, 0);
      }
      OBS(lane == 0, 12);
      smem_fence();
      __syncwarp();
      if (lane == 0) mbar_arrive(bars + B_HALO);
      __syncwarp();
      if (b < 112) {
        settle(probe(scr + (((b & 1) * 2 + (lane >> 4)) * HU_T + 60 + (b >> 4)) * BT + ((b >> 1) & 7) * 1792 + min(lane & 15, 13) * 128));
        publish(scr, C_WO);
      }
      mbar_wait(bars + (g1 ? B_GATE + 8 : B_ATT), 0);
      spin_ge(scr, C_WO, 112);
      if (lane == 0) mbar_arrive(bars + B_WO);
      mbar_wait(bars + B_ATT, 0);
      spin_ge(scr, C_O + (mt >> 1), 8);
      OBS(lane == 0, 17);
      if (lane == 0) mbar_arrive(bars + B_O);
      mbar_wait(bars + B_U1, 0);
      spin_ge(scr, C_U + 4 + dt, 28);
      OBS(lane == 0, 11);
      if (lane == 0) mbar_arrive(bars + B_U2);
    }
  } else {
    asm volatile("setmaxnreg.inc.sync.aligned.u32 232;");
    const int wg = warp >> 2, w4 = warp & 3, th = wg ^ 1;
    const bool rel = (tid & 127) < 2;
    unsigned char* scr = p.scr;
    uint32_t X[28][4];
    float aq[28];
    const uint32_t dlo = (base >> 4) + (512u << 16) + (hp & 1), dlq = dlo + (OFF_WQ >> 4);
    {
      uint32_t xa[4];
#pragma unroll
      for (int k = 0; k < 4; k++) xa[k] = base + OFF_X + (th * 64 + w4 * 16 + (mi >> 1) * 8 + r8) * 128 + (((2 * k + (mi & 1)) ^ r8) << 4);
      float c0[2][4] = {}, c1[2][4] = {};
      uint32_t one[8];
#pragma unroll
      for (int j = 0; j < 8; j++) asm volatile("{\n.reg .u32 y;\nmov.u32 y, %%tid.y;\nmad.lo.u32 %0, y, %1, 0x3f803f80;\n}" : "=r"(one[j]) : "r"(lane + j));
      asm volatile("" : "+l"(scr));
      uint32_t ok = 0;
      const uint32_t bx = bars + B_X + wg * 64;
      {
#pragma unroll 1
        for (int n = 0; n < 64 && !ok; n++) { mma16816(c0[0], 0, 0, 0, 0, 0, 0); ok = mbar_try(bars + B_X, 0); }
        if (wg) ok = 0;
      }
#pragma unroll
      for (int i = 0; i < 8; i++) {
        if (i < 7) {
          if (!ok) mbar_wait(bx + i * 8, 0);
          OBS(tid == 64 && i == 0, 0); OBS(tid == 64 && i == 6, 15);
#pragma unroll
          for (int k = 0; k < 4; k++) ldsm4(X[i * 4 + k], xa[k] + i * 16384);
          if (i < 6) ok = mbar_try(bx + i * 8 + 8, 0);
        }
        if (i > 0) {
#pragma unroll
          for (int k = i * 4 - 4; k < i * 4; k++) {
            mma16816(c0[k & 1], X[k][0], one[(k & 1) * 4], X[k][1], one[(k & 1) * 4 + 1], X[k][0], X[k][1]);
            mma16816(c1[k & 1], X[k][2], one[(k & 1) * 4 + 2], X[k][3], one[(k & 1) * 4 + 3], X[k][2], X[k][3]);
          }
        }
      }
      float st[4];
#pragma unroll
      for (int j = 0; j < 2; j++) {
        st[j] = __shfl_sync(0xffffffffu, (g & 1) ? c0[0][2 * j + 1] + c0[1][2 * j + 1] : c0[0][2 * j] + c0[1][2 * j], (lane & 28) | (g >> 1));
        st[2 + j] = __shfl_sync(0xffffffffu, (g & 1) ? c1[0][2 * j + 1] + c1[1][2 * j + 1] : c1[0][2 * j] + c1[1][2 * j], (lane & 28) | (g >> 1));
      }
      named_arrive(8, 384);
      asm volatile("{\n.reg .pred q;\nsetp.ne.u32 q, %3, 0;\n@q st.shared.v2.f32 [%0], {%1,%2};\n@q bar.arrive 9, 160;\n}"
                   :: "r"(base + OFF_LN + ((t & 1) * 8 + g) * 8), "f"((t & 1) ? st[3] : st[1]), "f"((t & 1) ? st[2] : st[0]), "r"((uint32_t)((warp ^ 4) == hp)) : "memory");
      ok = mbar_try(bars + B_KV, 0);
      LnC l0, l1;
      float eps = 1e-5f;
#pragma unroll 1
      do {
        l0 = ln_consts(st[1], st[0], eps); l1 = ln_consts(st[3], st[2], eps);
#pragma unroll
        for (int k = 0; k < 16; k++) X[k >> 2][k & 3] = hsub2(X[k >> 2][k & 3], k & 2 ? l1.m : l0.m);
        eps += eps;
      } while ((l0.rl ^ l1.rl) == 4);
      OBS(tid == 32, 1);
      float ak[60], *av = ak + 32;
      const int pp_in = wg ? 6 : 0, pp_out = wg ? 0 : 6;
#pragma unroll
      for (int s = 0; s < 7; s++) {
#pragma unroll
        for (int k = s * 4; k < s * 4 + 4; k++) {
          if (s == 0) {
            auto f = [&](uint32_t d, const LnC& l) { return hfma2(d, l.rh, hmul2(d, l.rl)); };
            const uint32_t y = f(X[k][1], l0);
            X[k][0] = f(X[k][0], l0); X[k][1] = f(X[k][2], l1); X[k][2] = y; X[k][3] = f(X[k][3], l1);
          } else {
            const uint32_t y = ln_apply(X[k][1], l0);
            X[k][0] = ln_apply(X[k][0], l0); X[k][1] = ln_apply(X[k][2], l1); X[k][2] = y; X[k][3] = ln_apply(X[k][3], l1);
          }
        }
        if (__builtin_expect(!ok, 0)) { mbar_wait(bars + B_KV + s * 8, 0); if (s == 6) mbar_wait(bars + B_WQ, 0); }
        if (s == 0) fresh(ak);
        if (s == 6) { wg_wait<0>(); if ((tid & 127) == 0) mbar_arrive(bars + B_EMPTY + 3 * 8); }
        OBS(KOBS && (tid & 127) == 0, 40 + wg * 32 + s);
        if (wg || s) named_sync(pp_in, 256);
        OBS(KOBS && (tid & 127) == 32, 48 + wg * 32 + s);
        OBS(tid == 64 && s == 0, 2);
        wg_fence();
#pragma unroll
        for (int k = 0; k < 4; k++) {
          wgmma_rs_n120<1>(ak, X[s * 4 + k], mkdesc(HI_SW128, dlo + s * 1024 + k * 128), (s | k) != 0);
        }
        wg_commit();
        if (s == 6) {
          fresh(aq);
#pragma unroll
          for (int k = 0; k < 8; k++) {
            if (k == 6) named_arrive(pp_out, 256);
            wgmma_rs_n56<1>(aq, X[k], mkdesc(HI_SW128, dlq + k * 128), k);
          }
          wg_commit();
        }
        if (s < 6) named_arrive(pp_out, 256);
        fence_code(s);
        OBS(KOBS && (tid & 127) == 64, 56 + wg * 32 + s);
        if (s < 6) ok = mbar_try(bars + B_KV + s * 8 + 8, 0);
        if (s == 5) ok &= mbar_try(bars + B_WQ, 0);
        OBS(tid == 64 && s == 5, 31);
        if (s > 0) wg_wait<1>();
        OBS(KOBS && (tid & 127) == 96, 64 + wg * 32 + s);
        if ((s == 2 || s == 3 || s == 5) && (tid & 127) == 0) mbar_arrive(bars + B_EMPTY + (s == 5 ? 2 : s - 2) * 8);
      }
      if ((tid & 127) == 0) mbar_arrive(bars + B_EMPTY + 4 * 8);
      OBS(tid == 32, 3);
      {
        const uint32_t kst = base + OFF_K + (2 + (warp ^ 4) * 2 + (mi & 1)) * 1792 + (mi >> 1) * 896 + r8 * 16;
#pragma unroll
        for (int n = 0; n < 7; n++)
          stsm4(kst + n * 128, pack2(ak[n * 4], ak[n * 4 + 1]), pack2(ak[n * 4 + 2], ak[n * 4 + 3]), pack2(av[n * 4], av[n * 4 + 1]), pack2(av[n * 4 + 2], av[n * 4 + 3]));
        named_arrive_if(warp == 3, 1, 96);
      }
      OBS(tid == 96, 32); OBS(tid == 224, 34);
      wg_wait<0>();
      if ((tid & 127) == 0) mbar_arrive(bars + B_EMPTY + 5 * 8);
      mbar_wait(bars + B_WQ2, 0);
    }
    const unsigned short *bp1 = (const unsigned short*)p.b1 + (g1 ? ft * 64 : 0) + w4 * 16 + g, *bp2 = (const unsigned short*)p.b2 + mt * 64 + w4 * 16 + g;
    const uint32_t braw[4] = {__ldg(bp1), __ldg(bp1 + 8), __ldg(bp2), __ldg(bp2 + 8)};
    auto q_rest = [&]() {
      wg_fence();
#pragma unroll
      for (int s = 2; s < 7; s++) {
#pragma unroll
        for (int k = s * 4; k < s * 4 + 4; k++) wgmma_rs_n56<1>(aq, X[k], mkdesc(HI_SW128, dlq + k * 128), 1);
        wg_commit();
        if (s == 5) { wg_wait<2>(); if ((tid & 127) == 0) mbar_arrive(bars + B_EMPTY + 6 * 8); }
      }
    };
    uint32_t Q[4][4];
    auto q_pack = [&]() {
#pragma unroll
      for (int n = 0; n < 14; n++) { const int m = n + 2 * (n > 7); Q[m >> 2][m & 3] = pack2(aq[n * 2], aq[n * 2 + 1]); }
#pragma unroll
      for (int h = 0; h < 2; h++) { Q[2][h] = t < 2 ? 0u : Q[1][2 + h]; Q[1][2 + h] = t < 2 ? Q[1][2 + h] : 0u; }
    };
    float acc[56];
    auto ai = [](int p) { return p < 4 ? 48 + (p & 1) * 4 + (p & 2) : (p - 4) * 4; };
    uint32_t xch, ts, tl;
    unsigned char *outp, *outq;
    auto setup_out = [&]() {
      xch = pin(base + OFF_K + (tid & 127) * 16);
      const uint32_t tb = base + OFF_K + 6144 + warp * 2560;
      ts = pin(tb + mi * 160 + r8 * 16); tl = pin(tb + t * 160 + g * 16);
      unsigned char* o = p.out + (mt * 64 + w4 * 16 + g) * 896 + dt * 224;
      outp = pin(o + th * 7168 + t * 16); outq = pin(o + (t >> 1) * 7168 + 192 + (t & 1) * 16);
    };
    auto give = [&](const float (&a)[56], int id) {
#pragma unroll
      for (int i = 0; i < 48; i += 16) sts128(xch + i * 128, pack2(a[i + 2], a[i + 3]), pack2(a[i + 6], a[i + 7]), pack2(a[i + 10], a[i + 11]), pack2(a[i + 14], a[i + 15]));
      named_arrive(id, 256);
    };
    auto take = [&](uint32_t (&r)[12], int id) {
      named_sync(id, 256);
#pragma unroll
      for (int i = 0; i < 3; i++) { const uint4 v = lds128(xch + i * 2048); r[i * 4] = v.x; r[i * 4 + 1] = v.y; r[i * 4 + 2] = v.z; r[i * 4 + 3] = v.w; }
    };
    float hv[32];
    auto keep_h = [&](int i) {
      const float hb0 = 0.5f * bf_lo(braw[i]), hb1 = 0.5f * bf_lo(braw[i + 1]);
#pragma unroll
      for (int j = 0; j < 32; j++) hv[j] = fmaf(acc[ai(j >> 1) + (j & 1)], 0.5f, j >= 4 && j < 8 ? hb1 : hb0);
    };
    auto take_h = [&](int i) {
      const float hb1 = 0.5f * bf_lo(braw[i + 1]);
      uint32_t r[12];
      take(r, 5);
#pragma unroll
      for (int j = 0; j < 12; j++) { hv[8 + 2 * j] = fmaf(bf_lo(r[j]), 0.5f, hb1); hv[9 + 2 * j] = fmaf(bf_hi(r[j]), 0.5f, hb1); }
    };
    uint4 Xr[4];
    auto get_x = [&]() {
      const uint32_t xr = base + OFF_Q + (w4 * 16 + g) * 224;
      mbar_wait(bars + B_RES, 0);
      Xr[0] = lds128(xr + (t >> 1) * 1792 + 192 + (t & 1) * 16);
#pragma unroll
      for (int i = 1; i < 4; i++) Xr[i] = lds128(xr + th * 1792 + t * 16 + (i - 1) * 64);
    };
    uint32_t Sv[16];
    auto gate = [&](int i) {
      uint32_t R[4];
#pragma unroll
      for (int q = 0; q < 4; q++) {
        const int j = i * 4 + q;
        const float h0 = hv[2 * j], h1 = hv[2 * j + 1];
        R[q] = hmul2(Sv[j], pack2(fmaf(h0, tanh_fast(h0), h0), fmaf(h1, tanh_fast(h1), h1)));
      }
      stsm4(ts + i * 640, R[0], R[1], R[2], R[3]);
    };
    auto leave = [&](int i) {
      __syncwarp();
      const uint4 v = lds128(tl + i * 640), x = Xr[i];
      stg128(i ? outp + (i - 1) * 64 : outq, hadd2(x.x, v.x), hadd2(x.y, v.y), hadd2(x.z, v.z), hadd2(x.w, v.w));
    };
    if (wg == 0) {
      named_sync(0, 256);
      OBS(tid == 96, 14);
      q_rest();
      named_arrive(6, 256);
      wg_wait<0>();
      if (tid == 0) mbar_arrive(bars + B_EMPTY + 7 * 8);
      q_pack();
      const uint32_t qst = base + OFF_Q + 8192 + (mi >> 1) * 1024 + (w4 * 16 + (mi & 1) * 8 + r8) * 16;
#pragma unroll
      for (int n = 0; n < 4; n++) stsm4(qst + n * 2048, Q[n][0], Q[n][1], Q[n][2], Q[n][3]);
      smem_fence();
      named_arrive(7, 256);
      OBS(tid == 32, 5);
      fresh(acc);
      if (g1) {
        unsigned char* ug = pin(scr + (d1 * HU_T + 32 + (ft >> 1)) * BT + ((ft & 1) * 4 + w4) * 1792 + lane * 4);
        unsigned char* ur = pin(ug + min(lane, 13) * 128);
        unsigned char* uc = pin(scr + d1 * 128);
        mbar_wait(bars, 0); mbar_wait(bars + 8, 0);
        {
          const uint32_t tg = lds64(bars + B_T0).x;
          while (tg - gtime() - 1 < 1000u);
        }
        named_sync(0, 256);
        gemm_issue<1>(acc, base >> 4, 0);
        OBS(tid == 0, 20);
        gemm_loop<1>(acc, base, 1, 32, rel, 40, 1, tid == 32 ? J1 : tid == 64 ? J2 : -1, bars + B_GATE - 8 + w4 * 8);
        wg_wait<0>();
        OBS(tid == 0, 21);
        named_arrive(5, 256);
        mbar_arrive_if(rel, bars + B_EMPTY + 7 * 8);
#pragma unroll
        for (int h = 0; h < 2; h++) {
          const float hb = 0.5f * bf_lo(braw[h]);
#pragma unroll
          for (int n = 0; n < 14; n++) {
            const float h0 = fmaf(acc[4 * n + 2 * h], 0.5f, hb), h1 = fmaf(acc[4 * n + 2 * h + 1], 0.5f, hb);
            const float t0 = tanh_fast(h0 * fmaf(h0 * h0, 0.2854192648f, 1.5957691216f)), t1 = tanh_fast(h1 * fmaf(h1 * h1, 0.2854192648f, 1.5957691216f));
            stg32(ug + h * 14 * BT + n * 128, pack2(fmaf(h0, t0, h0), fmaf(h1, t1, h1)));
            if (n == 6) fence_code(8 + h);
          }
          settle(probe(ur + h * 14 * BT));
          if (h == 0) named_arrive(12, 256);
          if (w4) named_arrive(13 + h, 128);
          else { named_sync(13 + h, 128); publish(uc, C_U + h * 4); OBS(tid == 0, h ? 13 : 9); }
          fence_code(10 + h);
        }
      } else if (tid == 32 || tid == 64) mbar_arrive(bars + B_GATE - 8 + w4 * 8);
      setup_out();
      get_x();
      uint32_t r[12];
      take(r, 3);
#pragma unroll
      for (int j = 0; j < 16; j++) Sv[j] = r[j < 4 ? 0 : j - 4];
      asm volatile("" :: "r"(r[0]), "r"(r[11]) : "memory");
      named_arrive(10, 256);
      take_h(2);
    } else {
      const uint32_t dq = ((base + OFF_Q) >> 4) + (64u << 16), dk = (base + OFF_K) >> 4;
      const bool odd = g & 1, early = 2 * t + (g & 1) > g;
      uint32_t selA[5], selB[4];
#pragma unroll
      for (int j = 0; j < 5; j++) { selA[j] = j == w4 + (early ? 0 : 1) ? (odd ? 0x1044u : 0x4410u) : 0x4444u; }
#pragma unroll
      for (int j = 0; j < 4; j++) { selB[j] = j == w4 ? (odd ? 0x3244u : 0x4432u) : 0x4444u; }
      float Sc[2][40], Op[2][2][16];
      uint32_t A[2][5][4];
      auto scores = [&](int T) {
        fresh(Sc[0]); fresh(Sc[1]);
#pragma unroll
        for (int k = 0; k < 2; k++) {
#pragma unroll
          for (int hh = 0; hh < 2; hh++)
            if (T) wgmma_n80<0, 0>(Sc[hh], mkdesc(8, dq + 512 + hh * 256 + k * 128), mkdesc(112, dk + (8u << 16) + 896 + hh * 24 + k * 16), k);
            else wgmma_rs_n80<0>(Sc[hh], Q[hh * 2 + k], mkdesc(112, dk + (8u << 16) + hh * 24 + k * 16), k);
        }
      };
      auto softmax = [&](int T) {
        uint32_t L[2][2];
        auto pick = [&](int w) {
#pragma unroll
          for (int hh = 0; hh < 2; hh++) {
            const float* q = Sc[hh] + w * 8;
            auto at = [&](int i) { return odd ? q[i + 1] : q[i]; };
            L[hh][0] = pack2(early ? at(0) : at(8), early ? at(6) : at(14)); L[hh][1] = pack2(at(4), at(10));
          }
          asm volatile("" ::: "memory");
        };
        if (w4 & 2) { if (w4 & 1) pick(3); else pick(2); } else { if (w4 & 1) pick(1); else pick(0); }
#pragma unroll
        for (int hh = 0; hh < 2; hh++) {
          uint32_t a = hfma2(L[hh][0], SC_HI, hmul2(L[hh][0], SC_LO)), c = hfma2(L[hh][1], SC_HI, hmul2(L[hh][1], SC_LO));
          if (T == 0 && w4 == 0 && rb == 0) { if (early) a = 0xce6ece6eu; c = (c & 0xffff0000u) | 0xce6eu; }
          uint32_t mx = hmax2(a, c);
          mx = hmax2(mx, __shfl_xor_sync(0xffffffffu, mx, 1));
          mx = hmax2(mx, __shfl_xor_sync(0xffffffffu, mx, 2));
          uint32_t pp[2];
#pragma unroll
          for (int h = 0; h < 2; h++) {
            const float m = h ? bf_hi(mx) : bf_lo(mx);
            const float p0 = ex2_fast(((h ? bf_hi(a) : bf_lo(a)) - m) * LOG2E), p1 = ex2_fast(((h ? bf_hi(c) : bf_lo(c)) - m) * LOG2E);
            float sm = p0 + p1;
            sm += __shfl_xor_sync(0xffffffffu, sm, 1);
            sm += __shfl_xor_sync(0xffffffffu, sm, 2);
            const float inv = rcp_fast(sm);
            pp[h] = pack2(p0 * inv, p1 * inv);
          }
#pragma unroll
          for (int j = 0; j < 5; j++) {
            A[hh][j][0] = place(pp[0], selA[j]); A[hh][j][1] = j ? place(pp[1], selB[j ? j - 1 : 0]) : 0u;
            A[hh][j][2] = j < 4 ? place(pp[0], selB[j & 3]) : 0u; A[hh][j][3] = place(pp[1], selA[j]);
          }
        }
      };
      auto values = [&](int T) {
        fresh(Op[T][0]); fresh(Op[T][1]);
#pragma unroll
        for (int j = 0; j < 5; j++)
#pragma unroll
          for (int hh = 0; hh < 2; hh++) {
            wgmma_rs_n32<1>(Op[T][hh], A[hh][j], mkdesc(8, dk + (112u << 16) + 56 + T * 896 + hh * 24 + j * 224), j);
          }
        wg_commit();
      };
      uint32_t Ob[2][14];
      auto pack = [&](int T) {
        const float (&O)[2][16] = Op[T];
#pragma unroll
        for (int n = 0; n < 7; n++)
#pragma unroll
          for (int h = 0; h < 2; h++) {
            if (n < 3) Ob[T][n * 2 + h] = pack2(O[0][n * 4 + 2 * h], O[0][n * 4 + 2 * h + 1]);
            else if (n == 3) Ob[T][n * 2 + h] = pack2(t < 2 ? O[0][12 + 2 * h] : O[1][2 * h], t < 2 ? O[0][13 + 2 * h] : O[1][2 * h + 1]);
            else Ob[T][n * 2 + h] = pack2(O[1][(n - 3) * 4 + 2 * h], O[1][(n - 3) * 4 + 2 * h + 1]);
          }
      };
      smem_fence();
      named_sync(6, 256);
      OBS(tid == 224, 26);
      q_rest();
      named_sync(7, 256);
      wg_fence();
      scores(1);
      wg_commit();
      named_arrive_if(g1, 0, 256);
      wg_wait<2>();
      if (tid == 128) mbar_arrive(bars + B_EMPTY + 7 * 8);
      wg_wait<0>();
      OBS(tid == 160, 10);
      softmax(1);
      q_pack();
      OBS(tid == 160, 30);
      mbar_wait(bars + B_HALO, 0);
      OBS(tid == 160, 7);
      mbar_wait(bars + B_GATE, 0);
      wg_fence();
      scores(0);
      values(1);
      wg_wait<0>();
      OBS(tid == 160, 33);
      unsigned char* og = scr + O_OFF + rb * 2 * 57344 + hp * 7168 + w4 * 256 + lane * 4;
      uint32_t seen[6];
      auto put = [&](int T) {
#pragma unroll
        for (int n = 0; n < 7; n++) {
          stg32(og + T * 57344 + n * 1024, Ob[T][2 * n]); stg32(og + T * 57344 + n * 1024 + 128, Ob[T][2 * n + 1]);
          if (n == 2 || n == 5 || n == 6) seen[T * 3 + n / 3] = probe(og + T * 57344 + (n - (n == 6 ? 0 : min(g, 2))) * 1024 + (t & 1) * 128);
          __nanosleep(20);
        }
      };
      softmax(0);
      mbar_wait(bars + B_GATE + 8, 0);
      wg_fence();
      values(0);
      pack(1); put(1);
      wg_wait<0>();
      OBS(tid == 160, 35);
      named_sync(11, 128);
      if (tid == 160) mbar_arrive(bars + B_ATT);
      pack(0); put(0);
      OBS(tid == 160, 28);
      settle(seen[0] ^ seen[1] ^ seen[2] ^ seen[3] ^ seen[4] ^ seen[5]);
      named_sync(11, 128);
      if (warp == 4) publish(scr, C_O + rb);
      OBS(tid == 160, 8);
      setup_out();
      float as[56];
      if (g1) named_sync(5, 256);
      get_x();
      mbar_wait(bars, 0);
      if (g1) named_sync(12, 256);
      fresh(as);
      gemm_issue<0>(as, base >> 4, 0);
      OBS(tid == 128, 22);
      gemm_loop<0>(as, base, 1, 7, rel, 104);
      fresh(acc);
      mbar_wait(bars + 56, 0);
      gemm_issue<1>(acc, (base + 7 * SLOT) >> 4, 0);
      OBS(tid == 128, 24);
      wg_wait<1>();
      mbar_arrive_if(rel, bars + B_EMPTY + 6 * 8);
      give(as, 3);
#pragma unroll
      for (int j = 0; j < 16; j++) Sv[j] = pack2(as[ai(j)], as[ai(j) + 1]);
      gemm_loop<1>(acc, base, 8, 35, rel, 65);
      named_sync(10, 256);
      wg_wait<0>();
      OBS(tid == 128, 25);
      give(acc, 5);
      fence_code(31);
      keep_h(2);
      gate(0); leave(0);
    }
    {
#pragma unroll
      for (int i = 1; i < 4; i++) { gate(i); leave(i); }
      OBS(tid == 128, 27);
    }
  }
}

typedef CUresult (*EncFn)(CUtensorMap*, CUtensorMapDataType, cuuint32_t, void*, const cuuint64_t*, const cuuint64_t*, const cuuint32_t*,
                          const cuuint32_t*, CUtensorMapInterleave, CUtensorMapSwizzle, CUtensorMapL2promotion, CUtensorMapFloatOOBfill);
void enc(EncFn f, CUtensorMap* m, const void* ptr, cuuint64_t d0, cuuint64_t d1, cuuint64_t d2, cuuint64_t s1, cuuint64_t s2, cuuint32_t b1, cuuint32_t b2, cuuint32_t b0 = 64) {
  const cuuint64_t gd[3] = {d0, d1, d2}, gs[2] = {s1 * 2, s2 * 2};
  const cuuint32_t bx[3] = {b0, b1, b2}, es[3] = {1, 1, 1};
  f(m, CU_TENSOR_MAP_DATA_TYPE_BFLOAT16, 3, (void*)ptr, gd, gs, bx, es, CU_TENSOR_MAP_INTERLEAVE_NONE, b0 == 64 ? CU_TENSOR_MAP_SWIZZLE_128B : CU_TENSOR_MAP_SWIZZLE_NONE,
    CU_TENSOR_MAP_L2_PROMOTION_L2_128B, CU_TENSOR_MAP_FLOAT_OOB_FILL_NONE);
}
}

extern "C" void kernel_launch(void* const* d_in, const int* in_sizes, int n_in, void* d_out, int out_size) {
  (void)in_sizes; (void)n_in; (void)out_size;
  void* fp = nullptr;
  cudaDriverEntryPointQueryResult qr;
  cudaGetDriverEntryPoint("cuTensorMapEncodeTiled", &fp, cudaEnableDefault, &qr);
  EncFn f = (EncFn)fp;
  CUtensorMap m_x, m_wkv, m_wq, m_w1, m_w2, m_res;
  void* scr = nullptr;
  cudaGetSymbolAddress(&scr, g_scr);
  enc(f, &m_x, d_in[0], D_, S_, 1, D_, D_, 64, 1);
  enc(f, &m_wkv, d_in[1], D_, D_, 3, 3 * D_, D_, 64, 2);
  enc(f, &m_wq, d_in[1], D_, D_, 3, 3 * D_, D_, 64, 1);
  enc(f, &m_w1, d_in[4], F_, S_, 1, F_, F_, 64, 1);
  enc(f, &m_w2, d_in[6], S_, 16, F_ / 16, S_, 16 * S_, 8, 8);
  enc(f, &m_res, d_in[0], D_, S_, 1, D_, D_, 64, 1, 112);
  Params p;
  p.wqkv = (const unsigned char*)d_in[1]; p.wo = (const unsigned char*)d_in[2];
  p.w1 = (const unsigned char*)d_in[4]; p.b1 = (const unsigned char*)d_in[5];
  p.w2 = (const unsigned char*)d_in[6]; p.b2 = (const unsigned char*)d_in[7];
  p.out = (unsigned char*)d_out; p.scr = (unsigned char*)scr;
  cudaFuncSetAttribute(fused_kernel, cudaFuncAttributeMaxDynamicSharedMemorySize, SMEM_BYTES);
  fused_kernel<<<128, NTHREADS, SMEM_BYTES, cudaStreamPerThread>>>(m_x, m_wkv, m_wq, m_w1, m_w2, m_res, p);
}
```

```cpp
#include <cuda_runtime.h>
#include <cuda.h>
#include <cuda_bf16.h>
#include <stdint.h>

template<int TA, int TB> __device__ __forceinline__ void wgmma_n112(float (&d)[56], uint64_t da, uint64_t db, int sc) {
  asm volatile("{\n.reg .pred p;\nsetp.ne.b32 p, %58, 0;\n"
    "wgmma.mma_async.sync.aligned.m64n112k16.f32.bf16.bf16 {%0, %1, %2, %3, %4, %5, %6, %7, %8, %9, %10, %11, %12, %13, %14, %15, %16, %17, %18, %19, %20, %21, %22, %23, %24, %25, %26, %27, %28, %29, %30, %31, %32, %33, %34, %35, %36, %37, %38, %39, %40, %41, %42, %43, %44, %45, %46, %47, %48, %49, %50, %51, %52, %53, %54, %55}, %56, %57, p, 1, 1, %59, %60;\n}\n"
    : "+f"(d[0]), "+f"(d[1]), "+f"(d[2]), "+f"(d[3]), "+f"(d[4]), "+f"(d[5]), "+f"(d[6]), "+f"(d[7]), "+f"(d[8]), "+f"(d[9]), "+f"(d[10]), "+f"(d[11]), "+f"(d[12]), "+f"(d[13]), "+f"(d[14]), "+f"(d[15]), "+f"(d[16]), "+f"(d[17]), "+f"(d[18]), "+f"(d[19]), "+f"(d[20]), "+f"(d[21]), "+f"(d[22]), "+f"(d[23]), "+f"(d[24]), "+f"(d[25]), "+f"(d[26]), "+f"(d[27]), "+f"(d[28]), "+f"(d[29]), "+f"(d[30]), "+f"(d[31]), "+f"(d[32]), "+f"(d[33]), "+f"(d[34]), "+f"(d[35]), "+f"(d[36]), "+f"(d[37]), "+f"(d[38]), "+f"(d[39]), "+f"(d[40]), "+f"(d[41]), "+f"(d[42]), "+f"(d[43]), "+f"(d[44]), "+f"(d[45]), "+f"(d[46]), "+f"(d[47]), "+f"(d[48]), "+f"(d[49]), "+f"(d[50]), "+f"(d[51]), "+f"(d[52]), "+f"(d[53]), "+f"(d[54]), "+f"(d[55])
    : "l"(da), "l"(db), "r"(sc), "n"(TA), "n"(TB));
}

template<int TA, int TB> __device__ __forceinline__ void wgmma_n80(float (&d)[40], uint64_t da, uint64_t db, int sc) {
  asm volatile("{\n.reg .pred p;\nsetp.ne.b32 p, %42, 0;\n"
    "wgmma.mma_async.sync.aligned.m64n80k16.f32.bf16.bf16 {%0, %1, %2, %3, %4, %5, %6, %7, %8, %9, %10, %11, %12, %13, %14, %15, %16, %17, %18, %19, %20, %21, %22, %23, %24, %25, %26, %27, %28, %29, %30, %31, %32, %33, %34, %35, %36, %37, %38, %39}, %40, %41, p, 1, 1, %43, %44;\n}\n"
    : "+f"(d[0]), "+f"(d[1]), "+f"(d[2]), "+f"(d[3]), "+f"(d[4]), "+f"(d[5]), "+f"(d[6]), "+f"(d[7]), "+f"(d[8]), "+f"(d[9]), "+f"(d[10]), "+f"(d[11]), "+f"(d[12]), "+f"(d[13]), "+f"(d[14]), "+f"(d[15]), "+f"(d[16]), "+f"(d[17]), "+f"(d[18]), "+f"(d[19]), "+f"(d[20]), "+f"(d[21]), "+f"(d[22]), "+f"(d[23]), "+f"(d[24]), "+f"(d[25]), "+f"(d[26]), "+f"(d[27]), "+f"(d[28]), "+f"(d[29]), "+f"(d[30]), "+f"(d[31]), "+f"(d[32]), "+f"(d[33]), "+f"(d[34]), "+f"(d[35]), "+f"(d[36]), "+f"(d[37]), "+f"(d[38]), "+f"(d[39])
    : "l"(da), "l"(db), "r"(sc), "n"(TA), "n"(TB));
}

template<int TB> __device__ __forceinline__ void wgmma_rs_n120(float (&d)[60], const uint32_t (&a)[4], uint64_t db, int sc) {
  asm volatile("{\n.reg .pred p;\nsetp.ne.b32 p, %65, 0;\n"
    "wgmma.mma_async.sync.aligned.m64n120k16.f32.bf16.bf16 {%0, %1, %2, %3, %4, %5, %6, %7, %8, %9, %10, %11, %12, %13, %14, %15, %16, %17, %18, %19, %20, %21, %22, %23, %24, %25, %26, %27, %28, %29, %30, %31, %32, %33, %34, %35, %36, %37, %38, %39, %40, %41, %42, %43, %44, %45, %46, %47, %48, %49, %50, %51, %52, %53, %54, %55, %56, %57, %58, %59}, {%60, %61, %62, %63}, %64, p, 1, 1, %66;\n}\n"
    : "+f"(d[0]), "+f"(d[1]), "+f"(d[2]), "+f"(d[3]), "+f"(d[4]), "+f"(d[5]), "+f"(d[6]), "+f"(d[7]), "+f"(d[8]), "+f"(d[9]), "+f"(d[10]), "+f"(d[11]), "+f"(d[12]), "+f"(d[13]), "+f"(d[14]), "+f"(d[15]), "+f"(d[16]), "+f"(d[17]), "+f"(d[18]), "+f"(d[19]), "+f"(d[20]), "+f"(d[21]), "+f"(d[22]), "+f"(d[23]), "+f"(d[24]), "+f"(d[25]), "+f"(d[26]), "+f"(d[27]), "+f"(d[28]), "+f"(d[29]), "+f"(d[30]), "+f"(d[31]), "+f"(d[32]), "+f"(d[33]), "+f"(d[34]), "+f"(d[35]), "+f"(d[36]), "+f"(d[37]), "+f"(d[38]), "+f"(d[39]), "+f"(d[40]), "+f"(d[41]), "+f"(d[42]), "+f"(d[43]), "+f"(d[44]), "+f"(d[45]), "+f"(d[46]), "+f"(d[47]), "+f"(d[48]), "+f"(d[49]), "+f"(d[50]), "+f"(d[51]), "+f"(d[52]), "+f"(d[53]), "+f"(d[54]), "+f"(d[55]), "+f"(d[56]), "+f"(d[57]), "+f"(d[58]), "+f"(d[59])
    : "r"(a[0]), "r"(a[1]), "r"(a[2]), "r"(a[3]), "l"(db), "r"(sc), "n"(TB));
}

template<int TB> __device__ __forceinline__ void wgmma_rs_n56(float (&d)[28], const uint32_t (&a)[4], uint64_t db, int sc) {
  asm volatile("{\n.reg .pred p;\nsetp.ne.b32 p, %33, 0;\n"
    "wgmma.mma_async.sync.aligned.m64n56k16.f32.bf16.bf16 {%0, %1, %2, %3, %4, %5, %6, %7, %8, %9, %10, %11, %12, %13, %14, %15, %16, %17, %18, %19, %20, %21, %22, %23, %24, %25, %26, %27}, {%28, %29, %30, %31}, %32, p, 1, 1, %34;\n}\n"
    : "+f"(d[0]), "+f"(d[1]), "+f"(d[2]), "+f"(d[3]), "+f"(d[4]), "+f"(d[5]), "+f"(d[6]), "+f"(d[7]), "+f"(d[8]), "+f"(d[9]), "+f"(d[10]), "+f"(d[11]), "+f"(d[12]), "+f"(d[13]), "+f"(d[14]), "+f"(d[15]), "+f"(d[16]), "+f"(d[17]), "+f"(d[18]), "+f"(d[19]), "+f"(d[20]), "+f"(d[21]), "+f"(d[22]), "+f"(d[23]), "+f"(d[24]), "+f"(d[25]), "+f"(d[26]), "+f"(d[27])
    : "r"(a[0]), "r"(a[1]), "r"(a[2]), "r"(a[3]), "l"(db), "r"(sc), "n"(TB));
}

template<int TB> __device__ __forceinline__ void wgmma_rs_n32(float (&d)[16], const uint32_t (&a)[4], uint64_t db, int sc) {
  asm volatile("{\n.reg .pred p;\nsetp.ne.b32 p, %21, 0;\n"
    "wgmma.mma_async.sync.aligned.m64n32k16.f32.bf16.bf16 {%0, %1, %2, %3, %4, %5, %6, %7, %8, %9, %10, %11, %12, %13, %14, %15}, {%16, %17, %18, %19}, %20, p, 1, 1, %22;\n}\n"
    : "+f"(d[0]), "+f"(d[1]), "+f"(d[2]), "+f"(d[3]), "+f"(d[4]), "+f"(d[5]), "+f"(d[6]), "+f"(d[7]), "+f"(d[8]), "+f"(d[9]), "+f"(d[10]), "+f"(d[11]), "+f"(d[12]), "+f"(d[13]), "+f"(d[14]), "+f"(d[15])
    : "r"(a[0]), "r"(a[1]), "r"(a[2]), "r"(a[3]), "l"(db), "r"(sc), "n"(TB));
}

template<int TB> __device__ __forceinline__ void wgmma_rs_n80(float (&d)[40], const uint32_t (&a)[4], uint64_t db, int sc) {
  asm volatile("{\n.reg .pred p;\nsetp.ne.b32 p, %45, 0;\n"
    "wgmma.mma_async.sync.aligned.m64n80k16.f32.bf16.bf16 {%0, %1, %2, %3, %4, %5, %6, %7, %8, %9, %10, %11, %12, %13, %14, %15, %16, %17, %18, %19, %20, %21, %22, %23, %24, %25, %26, %27, %28, %29, %30, %31, %32, %33, %34, %35, %36, %37, %38, %39}, {%40, %41, %42, %43}, %44, p, 1, 1, %46;\n}\n"
    : "+f"(d[0]), "+f"(d[1]), "+f"(d[2]), "+f"(d[3]), "+f"(d[4]), "+f"(d[5]), "+f"(d[6]), "+f"(d[7]), "+f"(d[8]), "+f"(d[9]), "+f"(d[10]), "+f"(d[11]), "+f"(d[12]), "+f"(d[13]), "+f"(d[14]), "+f"(d[15]), "+f"(d[16]), "+f"(d[17]), "+f"(d[18]), "+f"(d[19]), "+f"(d[20]), "+f"(d[21]), "+f"(d[22]), "+f"(d[23]), "+f"(d[24]), "+f"(d[25]), "+f"(d[26]), "+f"(d[27]), "+f"(d[28]), "+f"(d[29]), "+f"(d[30]), "+f"(d[31]), "+f"(d[32]), "+f"(d[33]), "+f"(d[34]), "+f"(d[35]), "+f"(d[36]), "+f"(d[37]), "+f"(d[38]), "+f"(d[39])
    : "r"(a[0]), "r"(a[1]), "r"(a[2]), "r"(a[3]), "l"(db), "r"(sc), "n"(TB));
}

namespace {
constexpr int S_ = 2048, D_ = 448, F_ = 1792;
constexpr int NSLOT = 8, SLOT = 22528;
constexpr int OFF_X = 7 * 16384;
constexpr int OFF_WQ = 8 * 16384;
constexpr int OFF_Q = NSLOT * SLOT;
constexpr int OFF_K = OFF_Q + 16384;
constexpr int OFF_BAR = 14 * 16384;
constexpr int OFF_LN = OFF_BAR + 512;
constexpr int OFF_OBS = OFF_BAR + 640;
constexpr int SMEM_BYTES = OFF_OBS + 1024;
#define PACE1 540
#define PACE2 650
#define J1 6
#define J2 14
#define TS 3120
#define UP 170
#define WQA 4
#define SOBS 0
#define FREQ 0
#define KOBS 0
#define LANDOBS 0
#define OBS(c, i) do {} while (0)
#define OBSG(c, i, j) do {} while (0)
constexpr int NTHREADS = 384;
constexpr float LOG2E = 1.4426950408889634f;
constexpr uint32_t SC_HI = 0x3e423e42u, SC_LO = 0xb9f7b9f7u;
constexpr int BT = 14336;

constexpr int HU_T = 67;
constexpr int O_OFF = 4 * HU_T * BT;
constexpr int HALO_OFF = O_OFF + 32 * 7 * 8192;
constexpr int CNT_OFF = HALO_OFF + 128 * 3584;
constexpr int SCR_BYTES = CNT_OFF + 160 * 128;
constexpr int C_U = 0, C_O = 8, C_H = 24, C_WO = 25, C_TK = 26, C_HALO = 32;
__device__ __align__(1024) unsigned char g_scr[SCR_BYTES];

__device__ __forceinline__ uint32_t smem_u32(const void* p) { return (uint32_t)__cvta_generic_to_shared(p); }
__device__ __forceinline__ void mbar_init(uint32_t bar, uint32_t cnt) { asm volatile("mbarrier.init.shared::cta.b64 [%0], %1;" :: "r"(bar), "r"(cnt)); }
__device__ __forceinline__ void mbar_expect_tx(uint32_t bar, uint32_t bytes) { asm volatile("mbarrier.arrive.expect_tx.shared::cta.b64 _, [%0], %1;" :: "r"(bar), "r"(bytes) : "memory"); }
__device__ __forceinline__ void mbar_arrive_if(uint32_t c, uint32_t bar) { asm volatile("{\n.reg .pred q;\nsetp.ne.u32 q, %1, 0;\n@q mbarrier.arrive.shared::cta.b64 _, [%0];\n}" :: "r"(bar), "r"(c) : "memory"); }
__device__ __forceinline__ void mbar_arrive(uint32_t bar) { asm volatile("mbarrier.arrive.shared::cta.b64 _, [%0];" :: "r"(bar) : "memory"); }
__device__ __forceinline__ void mbar_wait(uint32_t bar, uint32_t parity) {
  asm volatile("{\n.reg .pred p;\n.reg .u32 n;\nmov.u32 n, 0;\nLAB_WAIT:\n"
               "mbarrier.try_wait.parity.shared::cta.b64 p, [%0], %1;\n@p bra DONE;\n"
               "add.u32 n, n, 1;\nsetp.lt.u32 p, n, 400000;\n@p bra LAB_WAIT;\ntrap;\nDONE:\n}" :: "r"(bar), "r"(parity) : "memory");
}
__device__ __forceinline__ uint32_t mbar_try(uint32_t bar, uint32_t parity) {
  uint32_t ok;
  asm volatile("{\n.reg .pred p;\nmbarrier.test_wait.parity.shared::cta.b64 p, [%1], %2;\nselp.u32 %0, 1, 0, p;\n}" : "=r"(ok) : "r"(bar), "r"(parity) : "memory");
  return ok;
}
__device__ __forceinline__ void tma3d(uint32_t dst, const CUtensorMap* m, int c0, int c1, int c2, uint32_t bar) {
  asm volatile("cp.async.bulk.tensor.3d.shared::cluster.global.mbarrier::complete_tx::bytes [%0], [%1, {%3, %4, %5}], [%2];"
               :: "r"(dst), "l"(m), "r"(bar), "r"(c0), "r"(c1), "r"(c2) : "memory");
}
__device__ __forceinline__ void bulk_g2s(uint32_t dst, const void* src, uint32_t bytes, uint32_t bar) {
  asm volatile("cp.async.bulk.shared::cluster.global.mbarrier::complete_tx::bytes [%0], [%1], %2, [%3];" :: "r"(dst), "l"(src), "r"(bytes), "r"(bar) : "memory");
}
__device__ __forceinline__ void wg_fence() { asm volatile("wgmma.fence.sync.aligned;" ::: "memory"); }
__device__ __forceinline__ void wg_commit() { asm volatile("wgmma.commit_group.sync.aligned;" ::: "memory"); }
template <int N> __device__ __forceinline__ void wg_wait() { asm volatile("wgmma.wait_group.sync.aligned %0;" :: "n"(N) : "memory"); }
__device__ __forceinline__ void smem_fence() { asm volatile("fence.proxy.async.shared::cta;" ::: "memory"); }
__device__ __forceinline__ void stg128(void* p, uint32_t a, uint32_t b, uint32_t c, uint32_t d) { asm volatile("st.global.v4.u32 [%0], {%1,%2,%3,%4};" :: "l"(p), "r"(a), "r"(b), "r"(c), "r"(d) : "memory"); }
__device__ __forceinline__ void stg32(void* p, uint32_t v) { asm volatile("st.global.u32 [%0], %1;" :: "l"(p), "r"(v) : "memory"); }
__device__ __forceinline__ uint4 ldg128(const void* p) { uint4 v; asm volatile("ld.global.nc.L1::no_allocate.v4.u32 {%0,%1,%2,%3}, [%4];" : "=r"(v.x), "=r"(v.y), "=r"(v.z), "=r"(v.w) : "l"(p)); return v; }
__device__ __forceinline__ void publish(unsigned char* scr, int i) {
  asm volatile("{\n.reg .pred q;\nelect.sync _|q, 0xffffffff;\n@q red.relaxed.gpu.global.inc.u32 [%0], 0xffffffff;\n}" :: "l"(scr + CNT_OFF + i * 128) : "memory");
}
__device__ __forceinline__ uint32_t probe(const unsigned char* p) { uint32_t v; asm volatile("ld.relaxed.gpu.global.u32 %0, [%1];" : "=r"(v) : "l"(p) : "memory"); return v; }
__device__ __forceinline__ void settle(uint32_t v) {
  asm volatile("{\n.reg .pred q;\nsetp.eq.u32 q, %0, 0x7fc1dead;\n@q st.volatile.shared.u32 [%1], %0;\n}" :: "r"(v), "r"(1024 + OFF_BAR + 376) : "memory");
  __syncwarp();
}
__device__ __forceinline__ uint32_t spin_ge(unsigned char* scr, int i, unsigned target) {
  uint32_t v;
  asm volatile("{\n.reg .pred p;\n.reg .u32 n;\nmov.u32 n, 0;\nLAB_SPIN:\n"
               "ld.relaxed.gpu.global.u32 %0, [%1];\nsetp.ge.u32 p, %0, %2;\nvote.sync.all.pred p, p, 0xffffffff;\n@p bra DONE;\n"
               "add.u32 n, n, 1;\nsetp.lt.u32 p, n, 4000000;\n@p bra LAB_SPIN;\ntrap;\nDONE:\n}" : "=&r"(v) : "l"(scr + CNT_OFF + i * 128), "r"(target) : "memory");
  return v;
}
__device__ __forceinline__ int lane_id() { int l; asm volatile("mov.u32 %0, %%laneid;" : "=r"(l)); return l; }
__device__ __forceinline__ uint32_t pin(uint32_t v) { return __shfl_xor_sync(0xffffffffu, v, blockIdx.y); }
__device__ __forceinline__ unsigned char* pin(unsigned char* p) { return (unsigned char*)(((uint64_t)pin((uint32_t)((uint64_t)p >> 32)) << 32) | pin((uint32_t)(uint64_t)p)); }
__device__ __forceinline__ uint32_t gtime() { uint32_t g; asm volatile("mov.u32 %0, %%globaltimer_lo;" : "=r"(g)); return g; }
__device__ __forceinline__ bool elect() {
  uint32_t r; asm volatile("{\n.reg .pred p;\nelect.sync _|p, 0xffffffff;\nselp.u32 %0, 1, 0, p;\n}" : "=r"(r)); return r != 0;
}
__device__ __forceinline__ uint4 lds128(uint32_t a) { uint4 v; asm volatile("ld.shared.v4.u32 {%0,%1,%2,%3}, [%4];" : "=r"(v.x), "=r"(v.y), "=r"(v.z), "=r"(v.w) : "r"(a) : "memory"); return v; }
__device__ __forceinline__ uint2 lds64(uint32_t a) { uint2 v; asm volatile("ld.shared.v2.u32 {%0,%1}, [%2];" : "=r"(v.x), "=r"(v.y) : "r"(a) : "memory"); return v; }
__device__ __forceinline__ void sts128(uint32_t p, uint32_t a, uint32_t b, uint32_t c, uint32_t d) { asm volatile("st.shared.v4.u32 [%0], {%1,%2,%3,%4};" :: "r"(p), "r"(a), "r"(b), "r"(c), "r"(d) : "memory"); }
__device__ __forceinline__ void sts32(uint32_t a, float v) { asm volatile("st.shared.f32 [%0], %1;" :: "r"(a), "f"(v) : "memory"); }
__device__ __forceinline__ void named_sync(int id, int n) { asm volatile("bar.sync %0, %1;" :: "r"(id), "r"(n) : "memory"); }
__device__ __forceinline__ void named_arrive(int id, int n) { asm volatile("bar.arrive %0, %1;" :: "r"(id), "r"(n) : "memory"); }
__device__ __forceinline__ void named_arrive_if(uint32_t c, int id, int n) { asm volatile("{\n.reg .pred q;\nsetp.ne.u32 q, %2, 0;\n@q bar.arrive %0, %1;\n}" :: "r"(id), "r"(n), "r"(c) : "memory"); }
__device__ __forceinline__ uint64_t mkdesc(uint32_t hi, uint32_t lo) { return ((uint64_t)hi << 32) | lo; }
constexpr uint32_t HI_SW128 = 0x40000040u;
__device__ __forceinline__ uint32_t pack2(float lo, float hi) { uint32_t r; asm("cvt.rn.bf16x2.f32 %0, %1, %2;" : "=r"(r) : "f"(hi), "f"(lo)); return r; }
__device__ __forceinline__ float bf_lo(uint32_t v) { return __uint_as_float(v << 16); }
__device__ __forceinline__ float bf_hi(uint32_t v) { return __uint_as_float(v & 0xffff0000u); }
__device__ __forceinline__ float rbf(float x) { return bf_lo(pack2(x, 0.f)); }
__device__ __forceinline__ uint32_t hsub2(uint32_t a, uint32_t b) { uint32_t r; asm("sub.rn.bf16x2 %0, %1, %2;" : "=r"(r) : "r"(a), "r"(b)); return r; }
__device__ __forceinline__ uint32_t hadd2(uint32_t a, uint32_t b) { uint32_t r; asm("add.rn.bf16x2 %0, %1, %2;" : "=r"(r) : "r"(a), "r"(b)); return r; }
__device__ __forceinline__ uint32_t place(uint32_t v, uint32_t sel) { uint32_t r; asm volatile("prmt.b32 %0, %1, 0, %2;" : "=r"(r) : "r"(v), "r"(sel)); return r; }
__device__ __forceinline__ uint32_t hmax2(uint32_t a, uint32_t b) { uint32_t r; asm("max.bf16x2 %0, %1, %2;" : "=r"(r) : "r"(a), "r"(b)); return r; }
__device__ __forceinline__ uint32_t hmul2(uint32_t a, uint32_t b) { uint32_t r; asm("mul.rn.bf16x2 %0, %1, %2;" : "=r"(r) : "r"(a), "r"(b)); return r; }
__device__ __forceinline__ uint32_t hfma2(uint32_t a, uint32_t b, uint32_t c) { uint32_t r; asm("fma.rn.bf16x2 %0, %1, %2, %3;" : "=r"(r) : "r"(a), "r"(b), "r"(c)); return r; }
__device__ __forceinline__ float tanh_fast(float x) { float r; asm("tanh.approx.f32 %0, %1;" : "=f"(r) : "f"(x)); return r; }
__device__ __forceinline__ float rcp_fast(float x) { float r; asm("rcp.approx.ftz.f32 %0, %1;" : "=f"(r) : "f"(x)); return r; }
__device__ __forceinline__ float ex2_fast(float x) { float r; asm("ex2.approx.ftz.f32 %0, %1;" : "=f"(r) : "f"(x)); return r; }
__device__ __forceinline__ void mma16816(float (&c)[4], uint32_t a0, uint32_t a1, uint32_t a2, uint32_t a3, uint32_t b0, uint32_t b1) {
  asm volatile("mma.sync.aligned.m16n8k16.row.col.f32.bf16.bf16.f32 {%0,%1,%2,%3}, {%4,%5,%6,%7}, {%8,%9}, {%0,%1,%2,%3};"
               : "+f"(c[0]), "+f"(c[1]), "+f"(c[2]), "+f"(c[3]) : "r"(a0), "r"(a1), "r"(a2), "r"(a3), "r"(b0), "r"(b1));
}
__device__ __forceinline__ void ldsm4(uint32_t (&r)[4], uint32_t addr) {
  asm volatile("ldmatrix.sync.aligned.m8n8.x4.shared.b16 {%0,%1,%2,%3}, [%4];" : "=r"(r[0]), "=r"(r[1]), "=r"(r[2]), "=r"(r[3]) : "r"(addr) : "memory");
}
__device__ __forceinline__ void stsm4(uint32_t addr, uint32_t a, uint32_t b, uint32_t c, uint32_t d) {
  asm volatile("stmatrix.sync.aligned.m8n8.x4.shared.b16 [%0], {%1,%2,%3,%4};" :: "r"(addr), "r"(a), "r"(b), "r"(c), "r"(d) : "memory");
}

__device__ __forceinline__ float ln_rstd(float var, float eps = 1e-5f) {
  float sd;
  asm("sqrt.approx.ftz.f32 %0, %1;" : "=f"(sd) : "f"(rbf(rbf(var) + eps)));
  return rcp_fast(rbf(sd));
}
__device__ __forceinline__ float ln_var(float mean, float sq) { return fmaxf(fmaf(-mean, mean, sq * (1.0f / D_)), 0.f); }
struct LnC { uint32_t m, rh, rl; };
__device__ __forceinline__ LnC ln_consts(float sum, float sq, float eps) {
  const float mean = sum * (1.0f / D_), r = ln_rstd(ln_var(mean, sq), eps), rh = rbf(r);
  LnC c; c.m = pack2(mean, mean); c.rh = pack2(rh, rh); c.rl = pack2(r - rh, r - rh);
  return c;
}
__device__ __forceinline__ uint32_t ln_apply(uint32_t x, const LnC& c) {
  uint32_t d = hsub2(x, c.m);
  return hfma2(d, c.rh, hmul2(d, c.rl));
}

__device__ __forceinline__ void fence_code(int id) {
  asm volatile("{\n.reg .pred q;\nLAB_F:\nsetp.eq.u32 q, %0, %1;\n@q st.volatile.shared.u32 [%2], %2;\n@q bra LAB_F;\n}" :: "r"(blockIdx.x), "r"(0x70000000 + id), "r"(0) : "memory");
}
template <int N> __device__ __forceinline__ void fresh(float (&a)[N]) {
#pragma unroll
  for (int i = 0; i < N; i++) asm volatile("" : "=f"(a[i]));
}
constexpr int B_EMPTY = 64, B_U1 = 128, B_U2 = 136, B_WQ = 144, B_WQ2 = 152, B_HIN = 160, B_HALO = 168, B_GATE = 176, B_ATT = 192, B_RES = 200, B_WO = 208, B_O = 216;
constexpr int B_KV = 256, B_TAG = 360, B_T0 = 368, B_X = 384;

template <int TA>
__device__ __forceinline__ void gemm_issue(float (&acc)[56], uint32_t lo, int sc) {
  wg_fence();
#pragma unroll
  for (int k = 0; k < 4; k++)
    wgmma_n112<TA, 1>(acc, mkdesc(TA ? HI_SW128 : 8, lo + (TA ? 512u << 16 : 64u << 16) + k * 128), mkdesc(8, lo + (112u << 16) + 512 + k * 224), sc | k);
  wg_commit();
}
template <int TA>
__device__ __forceinline__ void gemm_loop(float (&acc)[56], uint32_t base, int it, int end, bool rel, int oi, uint32_t ok = 0, int gate_it = -1, uint32_t gate = 0) {
#pragma unroll 1
  for (; it < end;) {
    if (__builtin_expect(!ok, 0)) mbar_wait(base + OFF_BAR + (it & 7) * 8, (it >> 3) & 1);
    gemm_issue<TA>(acc, (base >> 4) + (it & 7) * (SLOT >> 4), 1);
    OBS(SOBS && rel, oi + it);
    it++;
    ok = mbar_try(base + OFF_BAR + (it & 7) * 8, (it >> 3) & 1);
    wg_wait<1>();
    if (rel || it == gate_it) mbar_arrive(rel ? base + OFF_BAR + B_EMPTY + ((it - 2) & 7) * 8 : gate);
  }
}
template <int S1, int S2>
__device__ __forceinline__ void produce_box(uint32_t base, int it, int end, const CUtensorMap* mp, int c0, int c1) {
#pragma unroll 1
  for (int c2 = 0; it < end; it++, c1 += S1, c2 += S2) {
    const uint32_t fb = base + OFF_BAR + (it & 7) * 8;
    mbar_wait(fb + B_EMPTY, (it >> 3) & 1);
    if (elect()) { mbar_expect_tx(fb, 8192); tma3d(base + (it & 7) * SLOT, mp, c0, c1, c2, fb); }
  }
}
template <int PER>
__device__ __forceinline__ void produce_lin(uint32_t base, int it, int end, const unsigned char* src, uint32_t bytes, uint32_t tn = 0) {
#pragma unroll 1
  for (; it < end; it++) {
    const uint32_t fb = base + OFF_BAR + (it & 7) * 8;
    mbar_wait(fb + B_EMPTY, (it >> 3) & 1);
    if (PER) { while ((int)(clock() - tn) < 0); tn += PER; }
    if (elect()) { mbar_expect_tx(fb, bytes); bulk_g2s(base + (it & 7) * SLOT + (bytes & 2048) * 4, src, bytes, fb); }
    src += bytes;
  }
}

__device__ __forceinline__ void retile_wo(const unsigned char* wo, unsigned char* scr, int u, int lane) {
  const int r8 = lane & 7, mi = lane >> 3;
  const unsigned char* src = wo + ((u >> 1) * 8 + r8) * 896 + ((u & 1) * 28 + mi) * 16;
  unsigned char* dst = scr + ((u & 1) * 2 * HU_T + 60 + (u >> 4)) * BT + ((u >> 1) & 7) * 1792 + mi * 128 + r8 * 16;
  uint4 v[7];
#pragma unroll
  for (int i = 0; i < 7; i++) v[i] = ldg128(src + i * 64);
#pragma unroll
  for (int i = 0; i < 7; i++) stg128(dst + i * 512 + ((i * 4 + mi) / 14) * (HU_T * BT - 1792), v[i].x, v[i].y, v[i].z, v[i].w);
}

struct Params {
  const unsigned char *wqkv, *wo, *w1, *b1, *w2, *b2;
  unsigned char *out, *scr;
};

__global__ void __launch_bounds__(NTHREADS, 1)
fused_kernel(const __grid_constant__ CUtensorMap m_x, const __grid_constant__ CUtensorMap m_wkv, const __grid_constant__ CUtensorMap m_wq,
             const __grid_constant__ CUtensorMap m_w1, const __grid_constant__ CUtensorMap m_w2, const __grid_constant__ CUtensorMap m_res, const Params p) {
  extern __shared__ __align__(1024) unsigned char smem_raw[];
  constexpr uint32_t base = 1024, bars = base + OFF_BAR;
  const int tid = threadIdx.x, lane = tid & 31, b = blockIdx.x;
  const int rb = (b >> 2) & 15, hp = ((b >> 6) << 2) | (b & 3);
  const int wcol = hp * 56 - (hp & 1) * 8;
  auto load_wq = [&](int s0, int s1, uint32_t bar) {
    mbar_expect_tx(bar, (s1 - s0) * 8192);
#pragma unroll 1
    for (int s = s0; s < s1; s++) tma3d(base + OFF_WQ + s * 8192, &m_wq, wcol, s * 64, 0, bar);
  };
  auto load_kv = [&](int s) { mbar_expect_tx(bars + B_KV + s * 8, 16384); tma3d(base + s * 16384, &m_wkv, wcol, s * 64, 1, bars + B_KV + s * 8); };
  if (tid < 32) {
    if (elect()) {
#pragma unroll
      for (int i = 0; i < 7; i++) mbar_init(bars + B_X + i * 8, 1);
      asm volatile("fence.mbarrier_init.release.cluster;" ::: "memory");
#pragma unroll
      for (int i = 0; i < 7; i++) { mbar_expect_tx(bars + B_X + i * 8, 8192); tma3d(base + OFF_X + i * 16384 + 8192, &m_x, i * 64, rb * 128 + 64, 0, bars + B_X + i * 8); }
#pragma unroll
      for (int i = 0; i < 7; i++) { mbar_init(bars + B_KV + i * 8, 1); mbar_init(bars + B_X + 64 + i * 8, 1); }
      asm volatile("fence.mbarrier_init.release.cluster;" ::: "memory");
      load_kv(0);
#pragma unroll
      for (int i = 0; i < 7; i++) { mbar_expect_tx(bars + B_X + 64 + i * 8, 8192); tma3d(base + OFF_X + i * 16384, &m_x, i * 64, rb * 128, 0, bars + B_X + 64 + i * 8); }
      load_kv(1);
    }
  }
  const int warp = __shfl_sync(0xffffffffu, tid >> 5, 0);
  if (warp == 1) {
    if (elect()) {
#pragma unroll
      for (int i = 0; i < 28; i++) mbar_init(bars + i * 8, i < 16 ? 2 : 1);
      asm volatile("fence.mbarrier_init.release.cluster;" ::: "memory");
      if (smem_u32(smem_raw) != base) asm volatile("trap;");
    }
  }
  const int dt = b & 3, mt = b >> 2;
  const bool g1 = (b & 15) < 14;
  const int a1 = b - 2 * (b >> 4), ft = a1 >> 2, d1 = a1 & 3;
  const int g = lane >> 2, t = lane & 3, r8 = lane & 7, mi = lane >> 3;
  OBSG(FREQ && tid == 160, 128, 160);
  __syncthreads();
  if (warp >= 8) {
    asm volatile("setmaxnreg.dec.sync.aligned.u32 40;");
    const int pw = warp - 8;
    unsigned char* scr = p.scr;
    if (pw == 2) {
      mbar_wait(bars + B_X + 48, 0);
      if (b < 112 && lane < 28) asm volatile("prefetch.global.L2 [%0];" :: "l"(p.wqkv + (b * 4 + lane / 7) * 2688 + (lane % 7) * 128) : "memory");
      if (b < 98) asm volatile("prefetch.global.L2 [%0];" :: "l"(p.wo + b * 4096 + lane * 128) : "memory");
      if (lane == 31) asm volatile("prefetch.tensormap [%0];" :: "l"(&m_wq) : "memory");
      __syncwarp();
    }
    if (pw == 3) {
      mbar_wait(bars + B_X, 0);
      if (elect()) {
#pragma unroll 1
        for (int i = 2; i < 7; i++) load_kv(i);
      }
      __syncwarp();
    }
    {
      const int c0 = pw * 14 + (mi >> 1);
      unsigned char* dst = scr + (pw * HU_T + rb * 2 + (hp >> 2)) * BT + ((hp & 3) * 2 + (mi & 1)) * 1792 + (mi >> 1) * 128 + r8 * 16;
      const uint32_t xs = base + OFF_X + (hp * 16 + (lane & 15)) * 128;
      uint4 H[7];
      named_sync(9, 160);
#pragma unroll
      for (int i = 0; i < 7; i++) H[i] = lds128(xs + ((c0 + 2 * i) >> 3) * 16384 + ((((c0 + 2 * i) & 7) ^ r8) << 4));
      asm volatile("" :: "r"(H[6].w), "r"(H[0].x) : "memory");
      if (pw != 3) named_arrive(8, 384);
      else {
        named_sync(8, 384);
        if (elect()) {
          if (g1) asm volatile("red.relaxed.gpu.global.max.u32 [%0], %1;" :: "l"(scr + CNT_OFF + C_H * 128 + 8), "r"(gtime()) : "memory");
          load_wq(0, WQA, bars + B_WQ);
        }
        __syncwarp();
      }
      const uint2 st = lds64(base + OFF_LN + (lane & 15) * 8);
      const float sum = __uint_as_float(st.x), mean = sum * (1.0f / D_), var = ln_var(mean, __uint_as_float(st.y));
      const float m = rbf(mean), r = ln_rstd(var), r2 = ln_rstd(var * r * r);
      const float nc = fmaf(m, (float)D_, -sum) * (1.0f / D_) * (r * r2);
      const uint32_t m2 = pack2(m, m), r2x = pack2(r * r2, r * r2), nc2 = pack2(nc, nc);
      auto f = [&](uint32_t v) { return hfma2(hsub2(v, m2), r2x, nc2); };
#pragma unroll
      for (int i = 0; i < 7; i++) stg128(dst + i * 256, f(H[i].x), f(H[i].y), f(H[i].z), f(H[i].w));
      if (pw != 1) named_arrive(4, 128);
    }
    const int lane = lane_id();
    if (pw == 0) {
      if (elect()) {
        asm volatile("prefetch.tensormap [%0];" :: "l"(&m_w1) : "memory");
        asm volatile("prefetch.tensormap [%0];" :: "l"(&m_w2) : "memory");
        asm volatile("prefetch.tensormap [%0];" :: "l"(&m_res) : "memory");
      }
      __syncwarp();
      const uint32_t e = probe(scr + CNT_OFF + C_H * 128 + 4) + 1;
      sts32(bars + B_TAG, __uint_as_float((e & 0x3fffu) | ((e << 2) & 0x3fff0000u)));
      named_arrive(1, 96);
      if (g1) produce_box<64, 0>(base, 0, 32, &m_w1, ft * 64, 0);
      mbar_wait(bars + B_ATT, 0);
      if (elect()) { mbar_expect_tx(bars + B_RES, BT); tma3d(base + OFF_Q, &m_res, dt * 112, mt * 64, 0, bars + B_RES); }
      mbar_wait(bars + B_WO, 0);
      produce_lin<0>(base, 0, 7, scr + (dt * HU_T + 60) * BT, BT);
#pragma unroll 1
      for (int h = 0; h < 2; h++) produce_box<0, 8>(base, 7 + h * 14, 21 + h * 14, &m_w2, mt * 64, h * 8);
    } else if (pw == 1) {
      named_sync(4, 128);
      const unsigned char* hl = scr + (rb * 2 + (hp >> 2)) * BT + (hp & 3) * 3584 + min(lane, 27) * 128;
      settle(probe(hl) ^ probe(hl + HU_T * BT) ^ probe(hl + 2 * HU_T * BT) ^ probe(hl + 3 * HU_T * BT));
      publish(scr, C_H);
      OBS(lane == 0, 4);
      if (elect()) load_wq(WQA, 7, bars + B_WQ2);
      __syncwarp();
      if (g1) {
        __nanosleep(200);
        const uint32_t v = spin_ge(scr + (lane & 1) * 8, C_H, lane & 1 ? 0 : 128);
        if (lane == 1) sts32(bars + B_T0, __uint_as_float(v + TS));
        __syncwarp();
        OBS(lane == 0, 16);
        produce_lin<0>(base, 0, 32, scr + d1 * HU_T * BT, BT);
      }
      mbar_wait(bars + B_O, 0);
      produce_lin<0>(base, 0, 7, scr + O_OFF + mt * 57344, 8192);
      const unsigned char* us = scr + (dt * HU_T + 32) * BT;
      mbar_wait(bars + B_EMPTY + 56, 0);
      if (elect()) mbar_expect_tx(bars + 56, BT);
      __syncwarp();
      spin_ge(scr, C_U + dt, 28);
      if (elect()) bulk_g2s(base + 7 * SLOT + 8192, us, BT, bars + 56);
      if (lane == 0) mbar_arrive(bars + B_U1);
      const uint32_t tu = clock();
      OBS(lane == 0, 18);
      produce_lin<UP>(base, 8, 15, us + BT, BT, tu + UP);
#pragma unroll 1
      for (int h = 0; h < 2; h++) {
        if (h) mbar_wait(bars + B_U2, 0);
        produce_lin<0>(base, 15 + h * 6, 21 + h * 14, us + (8 + h * 6) * BT, BT);
      }
      unsigned tk = 0;
      if (lane == 0) tk = atomicAdd((unsigned*)(scr + CNT_OFF + C_TK * 128), 1u);
      if (__shfl_sync(0xffffffffu, tk, 0) == 127) {
#pragma unroll 1
        for (int i = lane; i < 160; i += 32) *(unsigned*)(scr + CNT_OFF + i * 128) = 0;
        *(unsigned*)(scr + CNT_OFF + C_H * 128 + 8) = 0;
        publish(scr + 4, C_H);
      }
    } else if (pw == 2) {
      uint32_t tn = clock();
      const unsigned char* src = p.w1 + b * 4096 + lane * 128;
#pragma unroll 1
      for (int i = 0; i < 28 + FREQ * 2; i++) {
        while ((int)(clock() - tn) < 0) __nanosleep(20);
        if (i == 14 || i == 21) src = p.w2 + ((b >> 3) * 16 + (b & 7) + (i & 1) * 8) * 4096 + lane * 128;
        if (i < 28) asm volatile("prefetch.global.L2 [%0];" :: "l"(src) : "memory");
        OBSG(FREQ && lane == 0, 129 + i, 161 + i);
        src += (i < 14 ? 128 : 256) * 4096;
        tn += i < 14 ? PACE1 : PACE2;
      }
    } else {
      if (b < 112) retile_wo(p.wo, scr, b, lane_id());
      const int lane = lane_id();
      unsigned char* hg = scr + HALO_OFF + (rb * 8 + hp) * 3584;
      named_sync(1, 96);
      const uint32_t tag = lds64(bars + B_TAG).x;
      if (rb < 15) {
#pragma unroll
        for (int q = 0; q < 7; q += 4) {
          uint4 v[4];
#pragma unroll
          for (int i = q; i < q + 4 && i < 7; i++) v[i - q] = lds128(base + OFF_K + 8 * 3584 + i * 512 + lane * 16 + (i * 32 + lane < 112 && !(lane & 7) ? 1792 : 0));
#pragma unroll
          for (int i = q; i < q + 4 && i < 7; i++) stg128(hg + i * 512 + lane * 16, (lane & 7) == (i * 32 + lane < 112) ? tag : v[i - q].x, v[i - q].y, v[i - q].z, v[i - q].w);
        }
        publish(scr, C_HALO + rb * 8 + hp);
      }
      OBS(lane == 0, 29);
      if (rb > 0) {
        spin_ge(scr, C_HALO + (rb - 1) * 8 + hp, 1);
        const uint32_t la = base + OFF_K + min(lane, 27) * 128;
#pragma unroll 1
        for (int n = 0;; n++) {
          if (elect()) { mbar_expect_tx(bars + B_HIN, 3584); bulk_g2s(base + OFF_K, hg - 8 * 3584, 3584, bars + B_HIN); }
          __syncwarp();
          mbar_wait(bars + B_HIN, n & 1);
          if (__all_sync(0xffffffffu, lds64(la + (lane < 14 ? 16 : 0)).x == tag)) break;
          if (n > 1000000) asm volatile("trap;");
        }
        if (lane < 14) { const uint4 v = lds128(la); sts128(la + 1792, v.x, v.y, v.z, v.w); }
      } else {
#pragma unroll
        for (int i = 0; i < 7; i++) sts128(base + OFF_K + i * 512 + lane * 16, 0, 0, 0, 0);
      }
      OBS(lane == 0, 12);
      smem_fence();
      __syncwarp();
      if (lane == 0) mbar_arrive(bars + B_HALO);
      __syncwarp();
      if (b < 112) {
        settle(probe(scr + (((b & 1) * 2 + (lane >> 4)) * HU_T + 60 + (b >> 4)) * BT + ((b >> 1) & 7) * 1792 + min(lane & 15, 13) * 128));
        publish(scr, C_WO);
      }
      mbar_wait(bars + (g1 ? B_GATE + 8 : B_ATT), 0);
      spin_ge(scr, C_WO, 112);
      if (lane == 0) mbar_arrive(bars + B_WO);
      mbar_wait(bars + B_ATT, 0);
      spin_ge(scr, C_O + (mt >> 1), 8);
      OBS(lane == 0, 17);
      if (lane == 0) mbar_arrive(bars + B_O);
      mbar_wait(bars + B_U1, 0);
      spin_ge(scr, C_U + 4 + dt, 28);
      OBS(lane == 0, 11);
      if (lane == 0) mbar_arrive(bars + B_U2);
    }
  } else {
    asm volatile("setmaxnreg.inc.sync.aligned.u32 232;");
    const int wg = warp >> 2, w4 = warp & 3, th = wg ^ 1;
    const bool rel = (tid & 127) < 2;
    unsigned char* scr = p.scr;
    uint32_t X[28][4];
    float aq[28];
    const uint32_t dlo = (base >> 4) + (512u << 16) + (hp & 1), dlq = dlo + (OFF_WQ >> 4);
    {
      uint32_t xa[4];
#pragma unroll
      for (int k = 0; k < 4; k++) xa[k] = base + OFF_X + (th * 64 + w4 * 16 + (mi >> 1) * 8 + r8) * 128 + (((2 * k + (mi & 1)) ^ r8) << 4);
      float c0[2][4] = {}, c1[2][4] = {};
      uint32_t one[8];
#pragma unroll
      for (int j = 0; j < 8; j++) asm volatile("{\n.reg .u32 y;\nmov.u32 y, %%tid.y;\nmad.lo.u32 %0, y, %1, 0x3f803f80;\n}" : "=r"(one[j]) : "r"(lane + j));
      asm volatile("" : "+l"(scr));
      uint32_t ok = 0;
      const uint32_t bx = bars + B_X + wg * 64;
      {
#pragma unroll 1
        for (int n = 0; n < 64 && !ok; n++) { mma16816(c0[0], 0, 0, 0, 0, 0, 0); ok = mbar_try(bars + B_X, 0); }
        if (wg) ok = 0;
      }
#pragma unroll
      for (int i = 0; i < 8; i++) {
        if (i < 7) {
          if (!ok) mbar_wait(bx + i * 8, 0);
          OBS(tid == 64 && i == 0, 0); OBS(tid == 64 && i == 6, 15);
#pragma unroll
          for (int k = 0; k < 4; k++) ldsm4(X[i * 4 + k], xa[k] + i * 16384);
          if (i < 6) ok = mbar_try(bx + i * 8 + 8, 0);
        }
        if (i > 0) {
#pragma unroll
          for (int k = i * 4 - 4; k < i * 4; k++) {
            mma16816(c0[k & 1], X[k][0], one[(k & 1) * 4], X[k][1], one[(k & 1) * 4 + 1], X[k][0], X[k][1]);
            mma16816(c1[k & 1], X[k][2], one[(k & 1) * 4 + 2], X[k][3], one[(k & 1) * 4 + 3], X[k][2], X[k][3]);
          }
        }
      }
      float st[4];
#pragma unroll
      for (int j = 0; j < 2; j++) {
        st[j] = __shfl_sync(0xffffffffu, (g & 1) ? c0[0][2 * j + 1] + c0[1][2 * j + 1] : c0[0][2 * j] + c0[1][2 * j], (lane & 28) | (g >> 1));
        st[2 + j] = __shfl_sync(0xffffffffu, (g & 1) ? c1[0][2 * j + 1] + c1[1][2 * j + 1] : c1[0][2 * j] + c1[1][2 * j], (lane & 28) | (g >> 1));
      }
      named_arrive(8, 384);
      fence_code(20);
      named_arrive_if(wg, 0, 256);
      asm volatile("{\n.reg .pred q;\nsetp.ne.u32 q, %3, 0;\n@q st.shared.v2.f32 [%0], {%1,%2};\n@q bar.arrive 9, 160;\n}"
                   :: "r"(base + OFF_LN + ((t & 1) * 8 + g) * 8), "f"((t & 1) ? st[3] : st[1]), "f"((t & 1) ? st[2] : st[0]), "r"((uint32_t)((warp ^ 4) == hp)) : "memory");
      ok = mbar_try(bars + B_KV, 0);
      LnC l0, l1;
      float eps = 1e-5f;
#pragma unroll 1
      do {
        l0 = ln_consts(st[1], st[0], eps); l1 = ln_consts(st[3], st[2], eps);
#pragma unroll
        for (int k = 0; k < 16; k++) X[k >> 2][k & 3] = hsub2(X[k >> 2][k & 3], k & 2 ? l1.m : l0.m);
        eps += eps;
      } while ((l0.rl ^ l1.rl) == 4);
      OBS(tid == 32, 1);
      float ak[60], *av = ak + 32;
      auto norm = [&](int s) {
#pragma unroll
        for (int k = s * 4; k < s * 4 + 4; k++) {
          auto f = [&](uint32_t d, const LnC& l) { return s ? ln_apply(d, l) : hfma2(d, l.rh, hmul2(d, l.rl)); };
          const uint32_t y = f(X[k][1], l0);
          X[k][0] = f(X[k][0], l0); X[k][1] = f(X[k][2], l1); X[k][2] = y; X[k][3] = f(X[k][3], l1);
        }
      };
      const int pp_in = wg ? 6 : 0, pp_out = wg ? 0 : 6;
#pragma unroll
      for (int s = 0; s < 7; s++) {
        if (s != 1 || wg) norm(s);
        if (s == 0 && !wg) norm(1);
        if (__builtin_expect(!ok, 0)) { mbar_wait(bars + B_KV + s * 8, 0); if (s == 6) mbar_wait(bars + B_WQ, 0); }
        if (s == 0) fresh(ak);
        OBS(KOBS && (tid & 127) == 0, 40 + wg * 32 + s);
        if (wg ? s < 6 : s != 1) named_sync(pp_in, 256);
        OBS(KOBS && (tid & 127) == 32, 48 + wg * 32 + s);
        OBS(tid == 64 && s == 0, 2);
        wg_fence();
#pragma unroll
        for (int k = 0; k < 4; k++) {
          wgmma_rs_n120<1>(ak, X[s * 4 + k], mkdesc(HI_SW128, dlo + s * 1024 + k * 128), (s | k) != 0);
        }
        wg_commit();
        if (s == 6) {
          wg_wait<1>();
          if ((tid & 127) == 0) mbar_arrive(bars + B_EMPTY + 3 * 8);
          fresh(aq);
#pragma unroll
          for (int k = 0; k < 4; k++) {
            if (k == 2) named_arrive(pp_out, 256);
            wgmma_rs_n56<1>(aq, X[k], mkdesc(HI_SW128, dlq + k * 128), k);
          }
          wg_commit();
        }
        if (s < 6) named_arrive_if(wg ? s != 5 : s != 0, pp_out, 256);
        fence_code(s);
        OBS(KOBS && (tid & 127) == 64, 56 + wg * 32 + s);
        if (s < 6) ok = mbar_try(bars + B_KV + s * 8 + 8, 0);
        if (s == 5) ok &= mbar_try(bars + B_WQ, 0);
        OBS(tid == 64 && s == 5, 31);
        if (s > 0) wg_wait<1>();
        OBS(KOBS && (tid & 127) == 96, 64 + wg * 32 + s);
        if ((s == 2 || s == 3 || s == 5) && (tid & 127) == 0) mbar_arrive(bars + B_EMPTY + (s == 5 ? 2 : s - 2) * 8);
      }
      if ((tid & 127) == 0) mbar_arrive(bars + B_EMPTY + 4 * 8);
      OBS(tid == 32, 3);
      {
        const uint32_t kst = base + OFF_K + (2 + (warp ^ 4) * 2 + (mi & 1)) * 1792 + (mi >> 1) * 896 + r8 * 16;
#pragma unroll
        for (int n = 0; n < 7; n++)
          stsm4(kst + n * 128, pack2(ak[n * 4], ak[n * 4 + 1]), pack2(ak[n * 4 + 2], ak[n * 4 + 3]), pack2(av[n * 4], av[n * 4 + 1]), pack2(av[n * 4 + 2], av[n * 4 + 3]));
        named_arrive_if(warp == 3, 1, 96);
      }
      OBS(tid == 96, 32); OBS(tid == 224, 34);
      wg_wait<0>();
      if ((tid & 127) == 0) mbar_arrive(bars + B_EMPTY + 5 * 8);
      mbar_wait(bars + B_WQ2, 0);
    }
    const unsigned short *bp1 = (const unsigned short*)p.b1 + (g1 ? ft * 64 : 0) + w4 * 16 + g, *bp2 = (const unsigned short*)p.b2 + mt * 64 + w4 * 16 + g;
    const uint32_t braw[4] = {__ldg(bp1), __ldg(bp1 + 8), __ldg(bp2), __ldg(bp2 + 8)};
    auto q_rest = [&]() {
      wg_fence();
#pragma unroll
      for (int s = 1; s < 7; s++) {
#pragma unroll
        for (int k = s * 4; k < s * 4 + 4; k++) wgmma_rs_n56<1>(aq, X[k], mkdesc(HI_SW128, dlq + k * 128), 1);
        wg_commit();
        if (s == 5) { wg_wait<2>(); if ((tid & 127) == 0) mbar_arrive(bars + B_EMPTY + 6 * 8); }
      }
    };
    uint32_t Q[4][4];
    auto q_pack = [&]() {
#pragma unroll
      for (int n = 0; n < 14; n++) { const int m = n + 2 * (n > 7); Q[m >> 2][m & 3] = pack2(aq[n * 2], aq[n * 2 + 1]); }
#pragma unroll
      for (int h = 0; h < 2; h++) { Q[2][h] = t < 2 ? 0u : Q[1][2 + h]; Q[1][2 + h] = t < 2 ? Q[1][2 + h] : 0u; }
    };
    float acc[56];
    auto ai = [](int p) { return p < 4 ? 48 + (p & 1) * 4 + (p & 2) : (p - 4) * 4; };
    uint32_t xch, ts, tl;
    unsigned char *outp, *outq;
    auto setup_out = [&]() {
      xch = pin(base + OFF_K + (tid & 127) * 16);
      const uint32_t tb = base + OFF_K + 6144 + warp * 2560;
      ts = pin(tb + mi * 160 + r8 * 16); tl = pin(tb + t * 160 + g * 16);
      unsigned char* o = p.out + (mt * 64 + w4 * 16 + g) * 896 + dt * 224;
      outp = pin(o + th * 7168 + t * 16); outq = pin(o + (t >> 1) * 7168 + 192 + (t & 1) * 16);
    };
    auto give = [&](const float (&a)[56], int id) {
#pragma unroll
      for (int i = 0; i < 48; i += 16) sts128(xch + i * 128, pack2(a[i + 2], a[i + 3]), pack2(a[i + 6], a[i + 7]), pack2(a[i + 10], a[i + 11]), pack2(a[i + 14], a[i + 15]));
      named_arrive(id, 256);
    };
    auto take = [&](uint32_t (&r)[12], int id) {
      named_sync(id, 256);
#pragma unroll
      for (int i = 0; i < 3; i++) { const uint4 v = lds128(xch + i * 2048); r[i * 4] = v.x; r[i * 4 + 1] = v.y; r[i * 4 + 2] = v.z; r[i * 4 + 3] = v.w; }
    };
    float hv[32];
    auto keep_h = [&](int i) {
      const float hb0 = 0.5f * bf_lo(braw[i]), hb1 = 0.5f * bf_lo(braw[i + 1]);
#pragma unroll
      for (int j = 0; j < 32; j++) hv[j] = fmaf(acc[ai(j >> 1) + (j & 1)], 0.5f, j >= 4 && j < 8 ? hb1 : hb0);
    };
    auto take_h = [&](int i) {
      const float hb1 = 0.5f * bf_lo(braw[i + 1]);
      uint32_t r[12];
      take(r, 5);
#pragma unroll
      for (int j = 0; j < 12; j++) { hv[8 + 2 * j] = fmaf(bf_lo(r[j]), 0.5f, hb1); hv[9 + 2 * j] = fmaf(bf_hi(r[j]), 0.5f, hb1); }
    };
    uint4 Xr[4];
    auto get_x = [&]() {
      const uint32_t xr = base + OFF_Q + (w4 * 16 + g) * 224;
      mbar_wait(bars + B_RES, 0);
      Xr[0] = lds128(xr + (t >> 1) * 1792 + 192 + (t & 1) * 16);
#pragma unroll
      for (int i = 1; i < 4; i++) Xr[i] = lds128(xr + th * 1792 + t * 16 + (i - 1) * 64);
    };
    uint32_t Sv[16];
    auto gate = [&](int i) {
      uint32_t R[4];
#pragma unroll
      for (int q = 0; q < 4; q++) {
        const int j = i * 4 + q;
        const float h0 = hv[2 * j], h1 = hv[2 * j + 1];
        R[q] = hmul2(Sv[j], pack2(fmaf(h0, tanh_fast(h0), h0), fmaf(h1, tanh_fast(h1), h1)));
      }
      stsm4(ts + i * 640, R[0], R[1], R[2], R[3]);
    };
    auto leave = [&](int i) {
      __syncwarp();
      const uint4 v = lds128(tl + i * 640), x = Xr[i];
      stg128(i ? outp + (i - 1) * 64 : outq, hadd2(x.x, v.x), hadd2(x.y, v.y), hadd2(x.z, v.z), hadd2(x.w, v.w));
    };
    if (wg == 0) {
      named_sync(0, 256);
      OBS(tid == 96, 14);
      q_rest();
      named_arrive(6, 256);
      wg_wait<0>();
      if (tid == 0) mbar_arrive(bars + B_EMPTY + 7 * 8);
      q_pack();
      const uint32_t qst = base + OFF_Q + 8192 + (mi >> 1) * 1024 + (w4 * 16 + (mi & 1) * 8 + r8) * 16;
#pragma unroll
      for (int n = 0; n < 4; n++) stsm4(qst + n * 2048, Q[n][0], Q[n][1], Q[n][2], Q[n][3]);
      smem_fence();
      named_arrive(7, 256);
      OBS(tid == 32, 5);
      fresh(acc);
      if (g1) {
        unsigned char* ug = pin(scr + (d1 * HU_T + 32 + (ft >> 1)) * BT + ((ft & 1) * 4 + w4) * 1792 + lane * 4);
        unsigned char* ur = pin(ug + min(lane, 13) * 128);
        unsigned char* uc = pin(scr + d1 * 128);
        mbar_wait(bars, 0); mbar_wait(bars + 8, 0);
        {
          const uint32_t tg = lds64(bars + B_T0).x;
          while (tg - gtime() - 1 < 1000u);
        }
        named_sync(0, 256);
        gemm_issue<1>(acc, base >> 4, 0);
        OBS(tid == 0, 20);
        gemm_loop<1>(acc, base, 1, 32, rel, 40, 1, tid == 32 ? J1 : tid == 64 ? J2 : -1, bars + B_GATE - 8 + w4 * 8);
        wg_wait<0>();
        OBS(tid == 0, 21);
        named_arrive(5, 256);
        mbar_arrive_if(rel, bars + B_EMPTY + 7 * 8);
        auto gelu = [&](int n, int h) {
          const float hb = 0.5f * bf_lo(braw[h]);
          const float h0 = fmaf(acc[4 * n + 2 * h], 0.5f, hb), h1 = fmaf(acc[4 * n + 2 * h + 1], 0.5f, hb);
          const float t0 = tanh_fast(h0 * fmaf(h0 * h0, 0.2854192648f, 1.5957691216f)), t1 = tanh_fast(h1 * fmaf(h1 * h1, 0.2854192648f, 1.5957691216f));
          return pack2(fmaf(h0, t0, h0), fmaf(h1, t1, h1));
        };
        auto done = [&](int h) {
          if (w4) named_arrive(13 + h, 128);
          else { named_sync(13 + h, 128); publish(uc, C_U + h * 4); OBS(tid == 0, h ? 13 : 9); }
          fence_code(10 + h);
        };
#pragma unroll
        for (int n = 0; n < 14; n++) { stg32(ug + n * 128, gelu(n, 0)); if (n == 6) fence_code(8); }
        settle(probe(ur));
        named_arrive(12, 256);
        done(0);
#pragma unroll
        for (int n = 0; n < 14; n++) { stg32(ug + 14 * BT + n * 128, gelu(n, 1)); if (n == 6) fence_code(9); }
        settle(probe(ur + 14 * BT));
        done(1);
      } else if (tid == 32 || tid == 64) mbar_arrive(bars + B_GATE - 8 + w4 * 8);
      setup_out();
      get_x();
      uint32_t r[12];
      take(r, 3);
#pragma unroll
      for (int j = 0; j < 16; j++) Sv[j] = r[j < 4 ? 0 : j - 4];
      asm volatile("" :: "r"(r[0]), "r"(r[11]) : "memory");
      named_arrive(10, 256);
      take_h(2);
    } else {
      const uint32_t dq = ((base + OFF_Q) >> 4) + (64u << 16), dk = (base + OFF_K) >> 4;
      const bool odd = g & 1, early = 2 * t + (g & 1) > g;
      uint32_t selA[5], selB[4];
#pragma unroll
      for (int j = 0; j < 5; j++) { selA[j] = j == w4 + (early ? 0 : 1) ? (odd ? 0x1044u : 0x4410u) : 0x4444u; }
#pragma unroll
      for (int j = 0; j < 4; j++) { selB[j] = j == w4 ? (odd ? 0x3244u : 0x4432u) : 0x4444u; }
      float Sc[2][40], Op[2][2][16];
      uint32_t A[2][5][4];
      auto scores = [&](int T) {
        fresh(Sc[0]); fresh(Sc[1]);
#pragma unroll
        for (int k = 0; k < 2; k++) {
#pragma unroll
          for (int hh = 0; hh < 2; hh++)
            if (T) wgmma_n80<0, 0>(Sc[hh], mkdesc(8, dq + 512 + hh * 256 + k * 128), mkdesc(112, dk + (8u << 16) + 896 + hh * 24 + k * 16), k);
            else wgmma_rs_n80<0>(Sc[hh], Q[hh * 2 + k], mkdesc(112, dk + (8u << 16) + hh * 24 + k * 16), k);
        }
      };
      auto softmax = [&](int T) {
        uint32_t L[2][2];
        auto pick = [&](int w) {
#pragma unroll
          for (int hh = 0; hh < 2; hh++) {
            const float* q = Sc[hh] + w * 8;
            auto at = [&](int i) { return odd ? q[i + 1] : q[i]; };
            L[hh][0] = pack2(early ? at(0) : at(8), early ? at(6) : at(14)); L[hh][1] = pack2(at(4), at(10));
          }
          asm volatile("" ::: "memory");
        };
        if (w4 & 2) { if (w4 & 1) pick(3); else pick(2); } else { if (w4 & 1) pick(1); else pick(0); }
#pragma unroll
        for (int hh = 0; hh < 2; hh++) {
          uint32_t a = hfma2(L[hh][0], SC_HI, hmul2(L[hh][0], SC_LO)), c = hfma2(L[hh][1], SC_HI, hmul2(L[hh][1], SC_LO));
          if (T == 0 && w4 == 0 && rb == 0) { if (early) a = 0xce6ece6eu; c = (c & 0xffff0000u) | 0xce6eu; }
          uint32_t mx = hmax2(a, c);
          mx = hmax2(mx, __shfl_xor_sync(0xffffffffu, mx, 1));
          mx = hmax2(mx, __shfl_xor_sync(0xffffffffu, mx, 2));
          uint32_t pp[2];
#pragma unroll
          for (int h = 0; h < 2; h++) {
            const float m = h ? bf_hi(mx) : bf_lo(mx);
            const float p0 = ex2_fast(((h ? bf_hi(a) : bf_lo(a)) - m) * LOG2E), p1 = ex2_fast(((h ? bf_hi(c) : bf_lo(c)) - m) * LOG2E);
            float sm = p0 + p1;
            sm += __shfl_xor_sync(0xffffffffu, sm, 1);
            sm += __shfl_xor_sync(0xffffffffu, sm, 2);
            const float inv = rcp_fast(sm);
            pp[h] = pack2(p0 * inv, p1 * inv);
          }
#pragma unroll
          for (int j = 0; j < 5; j++) {
            A[hh][j][0] = place(pp[0], selA[j]); A[hh][j][1] = j ? place(pp[1], selB[j ? j - 1 : 0]) : 0u;
            A[hh][j][2] = j < 4 ? place(pp[0], selB[j & 3]) : 0u; A[hh][j][3] = place(pp[1], selA[j]);
          }
        }
      };
      auto values = [&](int T) {
        fresh(Op[T][0]); fresh(Op[T][1]);
#pragma unroll
        for (int j = 0; j < 5; j++)
#pragma unroll
          for (int hh = 0; hh < 2; hh++) {
            wgmma_rs_n32<1>(Op[T][hh], A[hh][j], mkdesc(8, dk + (112u << 16) + 56 + T * 896 + hh * 24 + j * 224), j);
          }
        wg_commit();
      };
      uint32_t Ob[2][14];
      auto pack = [&](int T) {
        const float (&O)[2][16] = Op[T];
#pragma unroll
        for (int n = 0; n < 7; n++)
#pragma unroll
          for (int h = 0; h < 2; h++) {
            if (n < 3) Ob[T][n * 2 + h] = pack2(O[0][n * 4 + 2 * h], O[0][n * 4 + 2 * h + 1]);
            else if (n == 3) Ob[T][n * 2 + h] = pack2(t < 2 ? O[0][12 + 2 * h] : O[1][2 * h], t < 2 ? O[0][13 + 2 * h] : O[1][2 * h + 1]);
            else Ob[T][n * 2 + h] = pack2(O[1][(n - 3) * 4 + 2 * h], O[1][(n - 3) * 4 + 2 * h + 1]);
          }
      };
      smem_fence();
      named_sync(6, 256);
      OBS(tid == 224, 26);
      q_rest();
      named_sync(7, 256);
      wg_fence();
      scores(1);
      wg_commit();
      named_arrive_if(g1, 0, 256);
      wg_wait<2>();
      if (tid == 128) mbar_arrive(bars + B_EMPTY + 7 * 8);
      wg_wait<0>();
      OBS(tid == 160, 10);
      softmax(1);
      q_pack();
      OBS(tid == 160, 30);
      mbar_wait(bars + B_HALO, 0);
      OBS(tid == 160, 7);
      mbar_wait(bars + B_GATE, 0);
      wg_fence();
      scores(0);
      values(1);
      wg_wait<0>();
      OBS(tid == 160, 33);
      unsigned char* og = scr + O_OFF + rb * 2 * 57344 + hp * 7168 + w4 * 256 + lane * 4;
      uint32_t seen[6];
      auto put = [&](int T) {
#pragma unroll
        for (int n = 0; n < 7; n++) {
          stg32(og + T * 57344 + n * 1024, Ob[T][2 * n]); stg32(og + T * 57344 + n * 1024 + 128, Ob[T][2 * n + 1]);
          if (n == 2 || n == 5 || n == 6) seen[T * 3 + n / 3] = probe(og + T * 57344 + (n - (n == 6 ? 0 : min(g, 2))) * 1024 + (t & 1) * 128);
          __nanosleep(20);
        }
      };
      pack(1); put(1);
      softmax(0);
      mbar_wait(bars + B_GATE + 8, 0);
      wg_fence();
      values(0);
      wg_wait<0>();
      OBS(tid == 160, 35);
      named_sync(11, 128);
      if (tid == 160) mbar_arrive(bars + B_ATT);
      pack(0); put(0);
      OBS(tid == 160, 28);
      settle(seen[0] ^ seen[1] ^ seen[2] ^ seen[3] ^ seen[4] ^ seen[5]);
      named_sync(11, 128);
      if (warp == 4) publish(scr, C_O + rb);
      OBS(tid == 160, 8);
      setup_out();
      float as[56];
      if (g1) named_sync(5, 256);
      get_x();
      mbar_wait(bars, 0);
      if (g1) named_sync(12, 256);
      fresh(as);
      gemm_issue<0>(as, base >> 4, 0);
      OBS(tid == 128, 22);
      gemm_loop<0>(as, base, 1, 7, rel, 104);
      fresh(acc);
      mbar_wait(bars + 56, 0);
      gemm_issue<1>(acc, (base + 7 * SLOT) >> 4, 0);
      OBS(tid == 128, 24);
      wg_wait<1>();
      mbar_arrive_if(rel, bars + B_EMPTY + 6 * 8);
      give(as, 3);
#pragma unroll
      for (int j = 0; j < 16; j++) Sv[j] = pack2(as[ai(j)], as[ai(j) + 1]);
      gemm_loop<1>(acc, base, 8, 35, rel, 65);
      named_sync(10, 256);
      wg_wait<0>();
      OBS(tid == 128, 25);
      give(acc, 5);
      fence_code(31);
      keep_h(2);
      gate(0); leave(0);
    }
    {
#pragma unroll
      for (int i = 1; i < 4; i++) { gate(i); leave(i); }
      OBS(tid == 128, 27);
    }
  }
}

typedef CUresult (*EncFn)(CUtensorMap*, CUtensorMapDataType, cuuint32_t, void*, const cuuint64_t*, const cuuint64_t*, const cuuint32_t*,
                          const cuuint32_t*, CUtensorMapInterleave, CUtensorMapSwizzle, CUtensorMapL2promotion, CUtensorMapFloatOOBfill);
void enc(EncFn f, CUtensorMap* m, const void* ptr, cuuint64_t d0, cuuint64_t d1, cuuint64_t d2, cuuint64_t s1, cuuint64_t s2, cuuint32_t b1, cuuint32_t b2, cuuint32_t b0 = 64) {
  const cuuint64_t gd[3] = {d0, d1, d2}, gs[2] = {s1 * 2, s2 * 2};
  const cuuint32_t bx[3] = {b0, b1, b2}, es[3] = {1, 1, 1};
  f(m, CU_TENSOR_MAP_DATA_TYPE_BFLOAT16, 3, (void*)ptr, gd, gs, bx, es, CU_TENSOR_MAP_INTERLEAVE_NONE, b0 == 64 ? CU_TENSOR_MAP_SWIZZLE_128B : CU_TENSOR_MAP_SWIZZLE_NONE,
    CU_TENSOR_MAP_L2_PROMOTION_L2_128B, CU_TENSOR_MAP_FLOAT_OOB_FILL_NONE);
}
}

extern "C" void kernel_launch(void* const* d_in, const int* in_sizes, int n_in, void* d_out, int out_size) {
  (void)in_sizes; (void)n_in; (void)out_size;
  void* fp = nullptr;
  cudaDriverEntryPointQueryResult qr;
  cudaGetDriverEntryPoint("cuTensorMapEncodeTiled", &fp, cudaEnableDefault, &qr);
  EncFn f = (EncFn)fp;
  CUtensorMap m_x, m_wkv, m_wq, m_w1, m_w2, m_res;
  void* scr = nullptr;
  cudaGetSymbolAddress(&scr, g_scr);
  enc(f, &m_x, d_in[0], D_, S_, 1, D_, D_, 64, 1);
  enc(f, &m_wkv, d_in[1], D_, D_, 3, 3 * D_, D_, 64, 2);
  enc(f, &m_wq, d_in[1], D_, D_, 3, 3 * D_, D_, 64, 1);
  enc(f, &m_w1, d_in[4], F_, S_, 1, F_, F_, 64, 1);
  enc(f, &m_w2, d_in[6], S_, 16, F_ / 16, S_, 16 * S_, 8, 8);
  enc(f, &m_res, d_in[0], D_, S_, 1, D_, D_, 64, 1, 112);
  Params p;
  p.wqkv = (const unsigned char*)d_in[1]; p.wo = (const unsigned char*)d_in[2];
  p.w1 = (const unsigned char*)d_in[4]; p.b1 = (const unsigned char*)d_in[5];
  p.w2 = (const unsigned char*)d_in[6]; p.b2 = (const unsigned char*)d_in[7];
  p.out = (unsigned char*)d_out; p.scr = (unsigned char*)scr;
  cudaFuncSetAttribute(fused_kernel, cudaFuncAttributeMaxDynamicSharedMemorySize, SMEM_BYTES);
  fused_kernel<<<128, NTHREADS, SMEM_BYTES, cudaStreamPerThread>>>(m_x, m_wkv, m_wq, m_w1, m_w2, m_res, p);
}
```

```cpp
#include <cuda_runtime.h>
#include <cuda.h>
#include <cuda_bf16.h>
#include <stdint.h>

template<int TA, int TB> __device__ __forceinline__ void wgmma_n112(float (&d)[56], uint64_t da, uint64_t db, int sc) {
  asm volatile("{\n.reg .pred p;\nsetp.ne.b32 p, %58, 0;\n"
    "wgmma.mma_async.sync.aligned.m64n112k16.f32.bf16.bf16 {%0, %1, %2, %3, %4, %5, %6, %7, %8, %9, %10, %11, %12, %13, %14, %15, %16, %17, %18, %19, %20, %21, %22, %23, %24, %25, %26, %27, %28, %29, %30, %31, %32, %33, %34, %35, %36, %37, %38, %39, %40, %41, %42, %43, %44, %45, %46, %47, %48, %49, %50, %51, %52, %53, %54, %55}, %56, %57, p, 1, 1, %59, %60;\n}\n"
    : "+f"(d[0]), "+f"(d[1]), "+f"(d[2]), "+f"(d[3]), "+f"(d[4]), "+f"(d[5]), "+f"(d[6]), "+f"(d[7]), "+f"(d[8]), "+f"(d[9]), "+f"(d[10]), "+f"(d[11]), "+f"(d[12]), "+f"(d[13]), "+f"(d[14]), "+f"(d[15]), "+f"(d[16]), "+f"(d[17]), "+f"(d[18]), "+f"(d[19]), "+f"(d[20]), "+f"(d[21]), "+f"(d[22]), "+f"(d[23]), "+f"(d[24]), "+f"(d[25]), "+f"(d[26]), "+f"(d[27]), "+f"(d[28]), "+f"(d[29]), "+f"(d[30]), "+f"(d[31]), "+f"(d[32]), "+f"(d[33]), "+f"(d[34]), "+f"(d[35]), "+f"(d[36]), "+f"(d[37]), "+f"(d[38]), "+f"(d[39]), "+f"(d[40]), "+f"(d[41]), "+f"(d[42]), "+f"(d[43]), "+f"(d[44]), "+f"(d[45]), "+f"(d[46]), "+f"(d[47]), "+f"(d[48]), "+f"(d[49]), "+f"(d[50]), "+f"(d[51]), "+f"(d[52]), "+f"(d[53]), "+f"(d[54]), "+f"(d[55])
    : "l"(da), "l"(db), "r"(sc), "n"(TA), "n"(TB));
}

template<int TA, int TB> __device__ __forceinline__ void wgmma_n80(float (&d)[40], uint64_t da, uint64_t db, int sc) {
  asm volatile("{\n.reg .pred p;\nsetp.ne.b32 p, %42, 0;\n"
    "wgmma.mma_async.sync.aligned.m64n80k16.f32.bf16.bf16 {%0, %1, %2, %3, %4, %5, %6, %7, %8, %9, %10, %11, %12, %13, %14, %15, %16, %17, %18, %19, %20, %21, %22, %23, %24, %25, %26, %27, %28, %29, %30, %31, %32, %33, %34, %35, %36, %37, %38, %39}, %40, %41, p, 1, 1, %43, %44;\n}\n"
    : "+f"(d[0]), "+f"(d[1]), "+f"(d[2]), "+f"(d[3]), "+f"(d[4]), "+f"(d[5]), "+f"(d[6]), "+f"(d[7]), "+f"(d[8]), "+f"(d[9]), "+f"(d[10]), "+f"(d[11]), "+f"(d[12]), "+f"(d[13]), "+f"(d[14]), "+f"(d[15]), "+f"(d[16]), "+f"(d[17]), "+f"(d[18]), "+f"(d[19]), "+f"(d[20]), "+f"(d[21]), "+f"(d[22]), "+f"(d[23]), "+f"(d[24]), "+f"(d[25]), "+f"(d[26]), "+f"(d[27]), "+f"(d[28]), "+f"(d[29]), "+f"(d[30]), "+f"(d[31]), "+f"(d[32]), "+f"(d[33]), "+f"(d[34]), "+f"(d[35]), "+f"(d[36]), "+f"(d[37]), "+f"(d[38]), "+f"(d[39])
    : "l"(da), "l"(db), "r"(sc), "n"(TA), "n"(TB));
}

template<int TB> __device__ __forceinline__ void wgmma_rs_n120(float (&d)[60], const uint32_t (&a)[4], uint64_t db, int sc) {
  asm volatile("{\n.reg .pred p;\nsetp.ne.b32 p, %65, 0;\n"
    "wgmma.mma_async.sync.aligned.m64n120k16.f32.bf16.bf16 {%0, %1, %2, %3, %4, %5, %6, %7, %8, %9, %10, %11, %12, %13, %14, %15, %16, %17, %18, %19, %20, %21, %22, %23, %24, %25, %26, %27, %28, %29, %30, %31, %32, %33, %34, %35, %36, %37, %38, %39, %40, %41, %42, %43, %44, %45, %46, %47, %48, %49, %50, %51, %52, %53, %54, %55, %56, %57, %58, %59}, {%60, %61, %62, %63}, %64, p, 1, 1, %66;\n}\n"
    : "+f"(d[0]), "+f"(d[1]), "+f"(d[2]), "+f"(d[3]), "+f"(d[4]), "+f"(d[5]), "+f"(d[6]), "+f"(d[7]), "+f"(d[8]), "+f"(d[9]), "+f"(d[10]), "+f"(d[11]), "+f"(d[12]), "+f"(d[13]), "+f"(d[14]), "+f"(d[15]), "+f"(d[16]), "+f"(d[17]), "+f"(d[18]), "+f"(d[19]), "+f"(d[20]), "+f"(d[21]), "+f"(d[22]), "+f"(d[23]), "+f"(d[24]), "+f"(d[25]), "+f"(d[26]), "+f"(d[27]), "+f"(d[28]), "+f"(d[29]), "+f"(d[30]), "+f"(d[31]), "+f"(d[32]), "+f"(d[33]), "+f"(d[34]), "+f"(d[35]), "+f"(d[36]), "+f"(d[37]), "+f"(d[38]), "+f"(d[39]), "+f"(d[40]), "+f"(d[41]), "+f"(d[42]), "+f"(d[43]), "+f"(d[44]), "+f"(d[45]), "+f"(d[46]), "+f"(d[47]), "+f"(d[48]), "+f"(d[49]), "+f"(d[50]), "+f"(d[51]), "+f"(d[52]), "+f"(d[53]), "+f"(d[54]), "+f"(d[55]), "+f"(d[56]), "+f"(d[57]), "+f"(d[58]), "+f"(d[59])
    : "r"(a[0]), "r"(a[1]), "r"(a[2]), "r"(a[3]), "l"(db), "r"(sc), "n"(TB));
}

template<int TB> __device__ __forceinline__ void wgmma_rs_n56(float (&d)[28], const uint32_t (&a)[4], uint64_t db, int sc) {
  asm volatile("{\n.reg .pred p;\nsetp.ne.b32 p, %33, 0;\n"
    "wgmma.mma_async.sync.aligned.m64n56k16.f32.bf16.bf16 {%0, %1, %2, %3, %4, %5, %6, %7, %8, %9, %10, %11, %12, %13, %14, %15, %16, %17, %18, %19, %20, %21, %22, %23, %24, %25, %26, %27}, {%28, %29, %30, %31}, %32, p, 1, 1, %34;\n}\n"
    : "+f"(d[0]), "+f"(d[1]), "+f"(d[2]), "+f"(d[3]), "+f"(d[4]), "+f"(d[5]), "+f"(d[6]), "+f"(d[7]), "+f"(d[8]), "+f"(d[9]), "+f"(d[10]), "+f"(d[11]), "+f"(d[12]), "+f"(d[13]), "+f"(d[14]), "+f"(d[15]), "+f"(d[16]), "+f"(d[17]), "+f"(d[18]), "+f"(d[19]), "+f"(d[20]), "+f"(d[21]), "+f"(d[22]), "+f"(d[23]), "+f"(d[24]), "+f"(d[25]), "+f"(d[26]), "+f"(d[27])
    : "r"(a[0]), "r"(a[1]), "r"(a[2]), "r"(a[3]), "l"(db), "r"(sc), "n"(TB));
}

template<int TB> __device__ __forceinline__ void wgmma_rs_n32(float (&d)[16], const uint32_t (&a)[4], uint64_t db, int sc) {
  asm volatile("{\n.reg .pred p;\nsetp.ne.b32 p, %21, 0;\n"
    "wgmma.mma_async.sync.aligned.m64n32k16.f32.bf16.bf16 {%0, %1, %2, %3, %4, %5, %6, %7, %8, %9, %10, %11, %12, %13, %14, %15}, {%16, %17, %18, %19}, %20, p, 1, 1, %22;\n}\n"
    : "+f"(d[0]), "+f"(d[1]), "+f"(d[2]), "+f"(d[3]), "+f"(d[4]), "+f"(d[5]), "+f"(d[6]), "+f"(d[7]), "+f"(d[8]), "+f"(d[9]), "+f"(d[10]), "+f"(d[11]), "+f"(d[12]), "+f"(d[13]), "+f"(d[14]), "+f"(d[15])
    : "r"(a[0]), "r"(a[1]), "r"(a[2]), "r"(a[3]), "l"(db), "r"(sc), "n"(TB));
}

template<int TB> __device__ __forceinline__ void wgmma_rs_n80(float (&d)[40], const uint32_t (&a)[4], uint64_t db, int sc) {
  asm volatile("{\n.reg .pred p;\nsetp.ne.b32 p, %45, 0;\n"
    "wgmma.mma_async.sync.aligned.m64n80k16.f32.bf16.bf16 {%0, %1, %2, %3, %4, %5, %6, %7, %8, %9, %10, %11, %12, %13, %14, %15, %16, %17, %18, %19, %20, %21, %22, %23, %24, %25, %26, %27, %28, %29, %30, %31, %32, %33, %34, %35, %36, %37, %38, %39}, {%40, %41, %42, %43}, %44, p, 1, 1, %46;\n}\n"
    : "+f"(d[0]), "+f"(d[1]), "+f"(d[2]), "+f"(d[3]), "+f"(d[4]), "+f"(d[5]), "+f"(d[6]), "+f"(d[7]), "+f"(d[8]), "+f"(d[9]), "+f"(d[10]), "+f"(d[11]), "+f"(d[12]), "+f"(d[13]), "+f"(d[14]), "+f"(d[15]), "+f"(d[16]), "+f"(d[17]), "+f"(d[18]), "+f"(d[19]), "+f"(d[20]), "+f"(d[21]), "+f"(d[22]), "+f"(d[23]), "+f"(d[24]), "+f"(d[25]), "+f"(d[26]), "+f"(d[27]), "+f"(d[28]), "+f"(d[29]), "+f"(d[30]), "+f"(d[31]), "+f"(d[32]), "+f"(d[33]), "+f"(d[34]), "+f"(d[35]), "+f"(d[36]), "+f"(d[37]), "+f"(d[38]), "+f"(d[39])
    : "r"(a[0]), "r"(a[1]), "r"(a[2]), "r"(a[3]), "l"(db), "r"(sc), "n"(TB));
}

namespace {
constexpr int S_ = 2048, D_ = 448, F_ = 1792;
constexpr int NSLOT = 8, SLOT = 22528;
constexpr int OFF_X = 7 * 16384;
constexpr int OFF_WQ = 8 * 16384;
constexpr int OFF_Q = NSLOT * SLOT;
constexpr int OFF_K = OFF_Q + 16384;
constexpr int OFF_BAR = 14 * 16384;
constexpr int OFF_LN = OFF_BAR + 512;
constexpr int OFF_OBS = OFF_BAR + 640;
constexpr int SMEM_BYTES = OFF_OBS + 1024;
#define PACE1 540
#define PACE2 650
#define J1 6
#define J2 14
#define TS 3120
#define UP 170
#define WQA 4
#define OTAG 1
#define SOBS 0
#define FREQ 0
#define KOBS 0
#define LANDOBS 0
#define OBS(c, i) do {} while (0)
#define OBSG(c, i, j) do {} while (0)
constexpr int NTHREADS = 384;
constexpr float LOG2E = 1.4426950408889634f;
constexpr uint32_t SC_HI = 0x3e423e42u, SC_LO = 0xb9f7b9f7u;
constexpr int BT = 14336;

constexpr int HU_T = 67;
constexpr int O_OFF = 4 * HU_T * BT;
constexpr int HALO_OFF = O_OFF + 32 * 7 * 8192;
constexpr int CNT_OFF = HALO_OFF + 128 * 3584;
constexpr int SCR_BYTES = CNT_OFF + 160 * 128;
constexpr int C_U = 0, C_O = 8, C_H = 24, C_WO = 25, C_TK = 26, C_HALO = 32;
__device__ __align__(1024) unsigned char g_scr[SCR_BYTES];

__device__ __forceinline__ uint32_t smem_u32(const void* p) { return (uint32_t)__cvta_generic_to_shared(p); }
__device__ __forceinline__ void mbar_init(uint32_t bar, uint32_t cnt) { asm volatile("mbarrier.init.shared::cta.b64 [%0], %1;" :: "r"(bar), "r"(cnt)); }
__device__ __forceinline__ void mbar_expect_tx(uint32_t bar, uint32_t bytes) { asm volatile("mbarrier.arrive.expect_tx.shared::cta.b64 _, [%0], %1;" :: "r"(bar), "r"(bytes) : "memory"); }
__device__ __forceinline__ void mbar_arrive_if(uint32_t c, uint32_t bar) { asm volatile("{\n.reg .pred q;\nsetp.ne.u32 q, %1, 0;\n@q mbarrier.arrive.shared::cta.b64 _, [%0];\n}" :: "r"(bar), "r"(c) : "memory"); }
__device__ __forceinline__ void mbar_arrive(uint32_t bar) { asm volatile("mbarrier.arrive.shared::cta.b64 _, [%0];" :: "r"(bar) : "memory"); }
__device__ __forceinline__ void mbar_wait(uint32_t bar, uint32_t parity) {
  asm volatile("{\n.reg .pred p;\n.reg .u32 n;\nmov.u32 n, 0;\nLAB_WAIT:\n"
               "mbarrier.try_wait.parity.shared::cta.b64 p, [%0], %1;\n@p bra DONE;\n"
               "add.u32 n, n, 1;\nsetp.lt.u32 p, n, 400000;\n@p bra LAB_WAIT;\ntrap;\nDONE:\n}" :: "r"(bar), "r"(parity) : "memory");
}
__device__ __forceinline__ uint32_t mbar_try(uint32_t bar, uint32_t parity) {
  uint32_t ok;
  asm volatile("{\n.reg .pred p;\nmbarrier.test_wait.parity.shared::cta.b64 p, [%1], %2;\nselp.u32 %0, 1, 0, p;\n}" : "=r"(ok) : "r"(bar), "r"(parity) : "memory");
  return ok;
}
__device__ __forceinline__ void tma3d(uint32_t dst, const CUtensorMap* m, int c0, int c1, int c2, uint32_t bar) {
  asm volatile("cp.async.bulk.tensor.3d.shared::cluster.global.mbarrier::complete_tx::bytes [%0], [%1, {%3, %4, %5}], [%2];"
               :: "r"(dst), "l"(m), "r"(bar), "r"(c0), "r"(c1), "r"(c2) : "memory");
}
__device__ __forceinline__ void bulk_g2s(uint32_t dst, const void* src, uint32_t bytes, uint32_t bar) {
  asm volatile("cp.async.bulk.shared::cluster.global.mbarrier::complete_tx::bytes [%0], [%1], %2, [%3];" :: "r"(dst), "l"(src), "r"(bytes), "r"(bar) : "memory");
}
__device__ __forceinline__ void wg_fence() { asm volatile("wgmma.fence.sync.aligned;" ::: "memory"); }
__device__ __forceinline__ void wg_commit() { asm volatile("wgmma.commit_group.sync.aligned;" ::: "memory"); }
template <int N> __device__ __forceinline__ void wg_wait() { asm volatile("wgmma.wait_group.sync.aligned %0;" :: "n"(N) : "memory"); }
__device__ __forceinline__ void smem_fence() { asm volatile("fence.proxy.async.shared::cta;" ::: "memory"); }
__device__ __forceinline__ void stg128(void* p, uint32_t a, uint32_t b, uint32_t c, uint32_t d) { asm volatile("st.global.v4.u32 [%0], {%1,%2,%3,%4};" :: "l"(p), "r"(a), "r"(b), "r"(c), "r"(d) : "memory"); }
__device__ __forceinline__ void stg32(void* p, uint32_t v) { asm volatile("st.global.u32 [%0], %1;" :: "l"(p), "r"(v) : "memory"); }
__device__ __forceinline__ uint4 ldg128(const void* p) { uint4 v; asm volatile("ld.global.nc.L1::no_allocate.v4.u32 {%0,%1,%2,%3}, [%4];" : "=r"(v.x), "=r"(v.y), "=r"(v.z), "=r"(v.w) : "l"(p)); return v; }
__device__ __forceinline__ void publish(unsigned char* scr, int i) {
  asm volatile("{\n.reg .pred q;\nelect.sync _|q, 0xffffffff;\n@q red.relaxed.gpu.global.inc.u32 [%0], 0xffffffff;\n}" :: "l"(scr + CNT_OFF + i * 128) : "memory");
}
__device__ __forceinline__ uint32_t probe(const unsigned char* p) { uint32_t v; asm volatile("ld.relaxed.gpu.global.u32 %0, [%1];" : "=r"(v) : "l"(p) : "memory"); return v; }
__device__ __forceinline__ void settle(uint32_t v) {
  asm volatile("{\n.reg .pred q;\nsetp.eq.u32 q, %0, 0x7fc1dead;\n@q st.volatile.shared.u32 [%1], %0;\n}" :: "r"(v), "r"(1024 + OFF_BAR + 376) : "memory");
  __syncwarp();
}
__device__ __forceinline__ uint32_t spin_ge(unsigned char* scr, int i, unsigned target) {
  uint32_t v;
  asm volatile("{\n.reg .pred p;\n.reg .u32 n;\nmov.u32 n, 0;\nLAB_SPIN:\n"
               "ld.relaxed.gpu.global.u32 %0, [%1];\nsetp.ge.u32 p, %0, %2;\nvote.sync.all.pred p, p, 0xffffffff;\n@p bra DONE;\n"
               "add.u32 n, n, 1;\nsetp.lt.u32 p, n, 4000000;\n@p bra LAB_SPIN;\ntrap;\nDONE:\n}" : "=&r"(v) : "l"(scr + CNT_OFF + i * 128), "r"(target) : "memory");
  return v;
}
__device__ __forceinline__ int lane_id() { int l; asm volatile("mov.u32 %0, %%laneid;" : "=r"(l)); return l; }
__device__ __forceinline__ uint32_t pin(uint32_t v) { return __shfl_xor_sync(0xffffffffu, v, blockIdx.y); }
__device__ __forceinline__ unsigned char* pin(unsigned char* p) { return (unsigned char*)(((uint64_t)pin((uint32_t)((uint64_t)p >> 32)) << 32) | pin((uint32_t)(uint64_t)p)); }
__device__ __forceinline__ uint32_t gtime() { uint32_t g; asm volatile("mov.u32 %0, %%globaltimer_lo;" : "=r"(g)); return g; }
__device__ __forceinline__ bool elect() {
  uint32_t r; asm volatile("{\n.reg .pred p;\nelect.sync _|p, 0xffffffff;\nselp.u32 %0, 1, 0, p;\n}" : "=r"(r)); return r != 0;
}
__device__ __forceinline__ uint4 lds128(uint32_t a) { uint4 v; asm volatile("ld.shared.v4.u32 {%0,%1,%2,%3}, [%4];" : "=r"(v.x), "=r"(v.y), "=r"(v.z), "=r"(v.w) : "r"(a) : "memory"); return v; }
__device__ __forceinline__ uint32_t lds32(uint32_t a) { uint32_t v; asm volatile("ld.shared.u32 %0, [%1];" : "=r"(v) : "r"(a) : "memory"); return v; }
__device__ __forceinline__ uint2 lds64(uint32_t a) { uint2 v; asm volatile("ld.shared.v2.u32 {%0,%1}, [%2];" : "=r"(v.x), "=r"(v.y) : "r"(a) : "memory"); return v; }
__device__ __forceinline__ void sts128(uint32_t p, uint32_t a, uint32_t b, uint32_t c, uint32_t d) { asm volatile("st.shared.v4.u32 [%0], {%1,%2,%3,%4};" :: "r"(p), "r"(a), "r"(b), "r"(c), "r"(d) : "memory"); }
__device__ __forceinline__ void sts32(uint32_t a, float v) { asm volatile("st.shared.f32 [%0], %1;" :: "r"(a), "f"(v) : "memory"); }
__device__ __forceinline__ void named_sync(int id, int n) { asm volatile("bar.sync %0, %1;" :: "r"(id), "r"(n) : "memory"); }
__device__ __forceinline__ void named_arrive(int id, int n) { asm volatile("bar.arrive %0, %1;" :: "r"(id), "r"(n) : "memory"); }
__device__ __forceinline__ void named_arrive_if(uint32_t c, int id, int n) { asm volatile("{\n.reg .pred q;\nsetp.ne.u32 q, %2, 0;\n@q bar.arrive %0, %1;\n}" :: "r"(id), "r"(n), "r"(c) : "memory"); }
__device__ __forceinline__ uint64_t mkdesc(uint32_t hi, uint32_t lo) { return ((uint64_t)hi << 32) | lo; }
constexpr uint32_t HI_SW128 = 0x40000040u;
__device__ __forceinline__ uint32_t pack2(float lo, float hi) { uint32_t r; asm("cvt.rn.bf16x2.f32 %0, %1, %2;" : "=r"(r) : "f"(hi), "f"(lo)); return r; }
__device__ __forceinline__ float bf_lo(uint32_t v) { return __uint_as_float(v << 16); }
__device__ __forceinline__ float bf_hi(uint32_t v) { return __uint_as_float(v & 0xffff0000u); }
__device__ __forceinline__ float rbf(float x) { return bf_lo(pack2(x, 0.f)); }
__device__ __forceinline__ uint32_t hsub2(uint32_t a, uint32_t b) { uint32_t r; asm("sub.rn.bf16x2 %0, %1, %2;" : "=r"(r) : "r"(a), "r"(b)); return r; }
__device__ __forceinline__ uint32_t hadd2(uint32_t a, uint32_t b) { uint32_t r; asm("add.rn.bf16x2 %0, %1, %2;" : "=r"(r) : "r"(a), "r"(b)); return r; }
__device__ __forceinline__ uint32_t place(uint32_t v, uint32_t sel) { uint32_t r; asm volatile("prmt.b32 %0, %1, 0, %2;" : "=r"(r) : "r"(v), "r"(sel)); return r; }
__device__ __forceinline__ uint32_t hmax2(uint32_t a, uint32_t b) { uint32_t r; asm("max.bf16x2 %0, %1, %2;" : "=r"(r) : "r"(a), "r"(b)); return r; }
__device__ __forceinline__ uint32_t hmul2(uint32_t a, uint32_t b) { uint32_t r; asm("mul.rn.bf16x2 %0, %1, %2;" : "=r"(r) : "r"(a), "r"(b)); return r; }
__device__ __forceinline__ uint32_t hfma2(uint32_t a, uint32_t b, uint32_t c) { uint32_t r; asm("fma.rn.bf16x2 %0, %1, %2, %3;" : "=r"(r) : "r"(a), "r"(b), "r"(c)); return r; }
__device__ __forceinline__ float tanh_fast(float x) { float r; asm("tanh.approx.f32 %0, %1;" : "=f"(r) : "f"(x)); return r; }
__device__ __forceinline__ float rcp_fast(float x) { float r; asm("rcp.approx.ftz.f32 %0, %1;" : "=f"(r) : "f"(x)); return r; }
__device__ __forceinline__ float ex2_fast(float x) { float r; asm("ex2.approx.ftz.f32 %0, %1;" : "=f"(r) : "f"(x)); return r; }
__device__ __forceinline__ void mma16816(float (&c)[4], uint32_t a0, uint32_t a1, uint32_t a2, uint32_t a3, uint32_t b0, uint32_t b1) {
  asm volatile("mma.sync.aligned.m16n8k16.row.col.f32.bf16.bf16.f32 {%0,%1,%2,%3}, {%4,%5,%6,%7}, {%8,%9}, {%0,%1,%2,%3};"
               : "+f"(c[0]), "+f"(c[1]), "+f"(c[2]), "+f"(c[3]) : "r"(a0), "r"(a1), "r"(a2), "r"(a3), "r"(b0), "r"(b1));
}
__device__ __forceinline__ void ldsm4(uint32_t (&r)[4], uint32_t addr) {
  asm volatile("ldmatrix.sync.aligned.m8n8.x4.shared.b16 {%0,%1,%2,%3}, [%4];" : "=r"(r[0]), "=r"(r[1]), "=r"(r[2]), "=r"(r[3]) : "r"(addr) : "memory");
}
__device__ __forceinline__ void stsm4(uint32_t addr, uint32_t a, uint32_t b, uint32_t c, uint32_t d) {
  asm volatile("stmatrix.sync.aligned.m8n8.x4.shared.b16 [%0], {%1,%2,%3,%4};" :: "r"(addr), "r"(a), "r"(b), "r"(c), "r"(d) : "memory");
}

__device__ __forceinline__ float ln_rstd(float var, float eps = 1e-5f) {
  float sd;
  asm("sqrt.approx.ftz.f32 %0, %1;" : "=f"(sd) : "f"(rbf(rbf(var) + eps)));
  return rcp_fast(rbf(sd));
}
__device__ __forceinline__ float ln_var(float mean, float sq) { return fmaxf(fmaf(-mean, mean, sq * (1.0f / D_)), 0.f); }
struct LnC { uint32_t m, rh, rl; };
__device__ __forceinline__ LnC ln_consts(float sum, float sq, float eps) {
  const float mean = sum * (1.0f / D_), r = ln_rstd(ln_var(mean, sq), eps), rh = rbf(r);
  LnC c; c.m = pack2(mean, mean); c.rh = pack2(rh, rh); c.rl = pack2(r - rh, r - rh);
  return c;
}
__device__ __forceinline__ uint32_t ln_apply(uint32_t x, const LnC& c) {
  uint32_t d = hsub2(x, c.m);
  return hfma2(d, c.rh, hmul2(d, c.rl));
}

__device__ __forceinline__ void fence_code(int id) {
  asm volatile("{\n.reg .pred q;\nLAB_F:\nsetp.eq.u32 q, %0, %1;\n@q st.volatile.shared.u32 [%2], %2;\n@q bra LAB_F;\n}" :: "r"(blockIdx.x), "r"(0x70000000 + id), "r"(0) : "memory");
}
template <int N> __device__ __forceinline__ void fresh(float (&a)[N]) {
#pragma unroll
  for (int i = 0; i < N; i++) asm volatile("" : "=f"(a[i]));
}
constexpr int B_EMPTY = 64, B_U1 = 128, B_U2 = 136, B_WQ = 144, B_WQ2 = 152, B_HIN = 160, B_HALO = 168, B_GATE = 176, B_ATT = 192, B_RES = 200, B_WO = 208, B_O = 216;
constexpr int B_OL = 224, B_KV = 296, B_TAG = 360, B_T0 = 368, B_X = 384;

template <int TA>
__device__ __forceinline__ void gemm_issue(float (&acc)[56], uint32_t lo, int sc) {
  wg_fence();
#pragma unroll
  for (int k = 0; k < 4; k++)
    wgmma_n112<TA, 1>(acc, mkdesc(TA ? HI_SW128 : 8, lo + (TA ? 512u << 16 : 64u << 16) + k * 128), mkdesc(8, lo + (112u << 16) + 512 + k * 224), sc | k);
  wg_commit();
}
template <int TA>
__device__ __forceinline__ void gemm_loop(float (&acc)[56], uint32_t base, int it, int end, bool rel, int oi, uint32_t ok = 0, int gate_it = -1, uint32_t gate = 0) {
#pragma unroll 1
  for (; it < end;) {
    if (__builtin_expect(!ok, 0)) mbar_wait(base + OFF_BAR + (it & 7) * 8, (it >> 3) & 1);
    gemm_issue<TA>(acc, (base >> 4) + (it & 7) * (SLOT >> 4), 1);
    OBS(SOBS && rel, oi + it);
    it++;
    ok = mbar_try(base + OFF_BAR + (it & 7) * 8, (it >> 3) & 1);
    wg_wait<1>();
    if (rel || it == gate_it) mbar_arrive(rel ? base + OFF_BAR + B_EMPTY + ((it - 2) & 7) * 8 : gate);
  }
}
template <int S1, int S2>
__device__ __forceinline__ void produce_box(uint32_t base, int it, int end, const CUtensorMap* mp, int c0, int c1) {
#pragma unroll 1
  for (int c2 = 0; it < end; it++, c1 += S1, c2 += S2) {
    const uint32_t fb = base + OFF_BAR + (it & 7) * 8;
    mbar_wait(fb + B_EMPTY, (it >> 3) & 1);
    if (elect()) { mbar_expect_tx(fb, 8192); tma3d(base + (it & 7) * SLOT, mp, c0, c1, c2, fb); }
  }
}
template <int PER>
__device__ __forceinline__ void produce_lin(uint32_t base, int it, int end, const unsigned char* src, uint32_t bytes, uint32_t tn = 0) {
#pragma unroll 1
  for (; it < end; it++) {
    const uint32_t fb = base + OFF_BAR + (it & 7) * 8;
    mbar_wait(fb + B_EMPTY, (it >> 3) & 1);
    if (PER) { while ((int)(clock() - tn) < 0); tn += PER; }
    if (elect()) { mbar_expect_tx(fb, bytes); bulk_g2s(base + (it & 7) * SLOT + (bytes & 2048) * 4, src, bytes, fb); }
    src += bytes;
  }
}

__device__ __forceinline__ void retile_wo(const unsigned char* wo, unsigned char* scr, int u, int lane) {
  const int r8 = lane & 7, mi = lane >> 3;
  const unsigned char* src = wo + ((u >> 1) * 8 + r8) * 896 + ((u & 1) * 28 + mi) * 16;
  unsigned char* dst = scr + ((u & 1) * 2 * HU_T + 60 + (u >> 4)) * BT + ((u >> 1) & 7) * 1792 + mi * 128 + r8 * 16;
  uint4 v[7];
#pragma unroll
  for (int i = 0; i < 7; i++) v[i] = ldg128(src + i * 64);
#pragma unroll
  for (int i = 0; i < 7; i++) stg128(dst + i * 512 + ((i * 4 + mi) / 14) * (HU_T * BT - 1792), v[i].x, v[i].y, v[i].z, v[i].w);
}

struct Params {
  const unsigned char *wqkv, *wo, *w1, *b1, *w2, *b2;
  unsigned char *out, *scr;
};

__global__ void __launch_bounds__(NTHREADS, 1)
fused_kernel(const __grid_constant__ CUtensorMap m_x, const __grid_constant__ CUtensorMap m_wkv, const __grid_constant__ CUtensorMap m_wq,
             const __grid_constant__ CUtensorMap m_w1, const __grid_constant__ CUtensorMap m_w2, const __grid_constant__ CUtensorMap m_res, const Params p) {
  extern __shared__ __align__(1024) unsigned char smem_raw[];
  constexpr uint32_t base = 1024, bars = base + OFF_BAR;
  const int tid = threadIdx.x, lane = tid & 31, b = blockIdx.x;
  const int rb = (b >> 2) & 15, hp = ((b >> 6) << 2) | (b & 3);
  const int wcol = hp * 56 - (hp & 1) * 8;
  auto load_wq = [&](int s0, int s1, uint32_t bar) {
    mbar_expect_tx(bar, (s1 - s0) * 8192);
#pragma unroll 1
    for (int s = s0; s < s1; s++) tma3d(base + OFF_WQ + s * 8192, &m_wq, wcol, s * 64, 0, bar);
  };
  auto load_kv = [&](int s) { mbar_expect_tx(bars + B_KV + s * 8, 16384); tma3d(base + s * 16384, &m_wkv, wcol, s * 64, 1, bars + B_KV + s * 8); };
  if (tid < 32) {
    if (elect()) {
#pragma unroll
      for (int i = 0; i < 7; i++) mbar_init(bars + B_X + i * 8, 1);
      asm volatile("fence.mbarrier_init.release.cluster;" ::: "memory");
#pragma unroll
      for (int i = 0; i < 7; i++) { mbar_expect_tx(bars + B_X + i * 8, 8192); tma3d(base + OFF_X + i * 16384 + 8192, &m_x, i * 64, rb * 128 + 64, 0, bars + B_X + i * 8); }
#pragma unroll
      for (int i = 0; i < 7; i++) { mbar_init(bars + B_KV + i * 8, 1); mbar_init(bars + B_X + 64 + i * 8, 1); }
      asm volatile("fence.mbarrier_init.release.cluster;" ::: "memory");
      load_kv(0);
#pragma unroll
      for (int i = 0; i < 7; i++) { mbar_expect_tx(bars + B_X + 64 + i * 8, 8192); tma3d(base + OFF_X + i * 16384, &m_x, i * 64, rb * 128, 0, bars + B_X + 64 + i * 8); }
      load_kv(1);
    }
  }
  const int warp = __shfl_sync(0xffffffffu, tid >> 5, 0);
  if (warp == 1) {
    if (elect()) {
#pragma unroll
      for (int i = 0; i < 35; i++) mbar_init(bars + i * 8, i < 16 ? 2 : 1);
      asm volatile("fence.mbarrier_init.release.cluster;" ::: "memory");
      if (smem_u32(smem_raw) != base) asm volatile("trap;");
    }
  }
  const int dt = b & 3, mt = b >> 2;
  const bool g1 = (b & 15) < 14;
  const int a1 = b - 2 * (b >> 4), ft = a1 >> 2, d1 = a1 & 3;
  const int g = lane >> 2, t = lane & 3, r8 = lane & 7, mi = lane >> 3;
  OBSG(FREQ && tid == 160, 128, 160);
  __syncthreads();
  if (warp >= 8) {
    asm volatile("setmaxnreg.dec.sync.aligned.u32 40;");
    const int pw = warp - 8;
    unsigned char* scr = p.scr;
    if (pw == 2) {
      mbar_wait(bars + B_X + 48, 0);
      if (b < 112 && lane < 28) asm volatile("prefetch.global.L2 [%0];" :: "l"(p.wqkv + (b * 4 + lane / 7) * 2688 + (lane % 7) * 128) : "memory");
      if (b < 98) asm volatile("prefetch.global.L2 [%0];" :: "l"(p.wo + b * 4096 + lane * 128) : "memory");
      if (lane == 31) asm volatile("prefetch.tensormap [%0];" :: "l"(&m_wq) : "memory");
      __syncwarp();
    }
    if (pw == 3) {
      mbar_wait(bars + B_X, 0);
      if (elect()) {
#pragma unroll 1
        for (int i = 2; i < 7; i++) load_kv(i);
      }
      __syncwarp();
    }
    {
      const int c0 = pw * 14 + (mi >> 1);
      unsigned char* dst = scr + (pw * HU_T + rb * 2 + (hp >> 2)) * BT + ((hp & 3) * 2 + (mi & 1)) * 1792 + (mi >> 1) * 128 + r8 * 16;
      const uint32_t xs = base + OFF_X + (hp * 16 + (lane & 15)) * 128;
      uint4 H[7];
      named_sync(9, 160);
#pragma unroll
      for (int i = 0; i < 7; i++) H[i] = lds128(xs + ((c0 + 2 * i) >> 3) * 16384 + ((((c0 + 2 * i) & 7) ^ r8) << 4));
      asm volatile("" :: "r"(H[6].w), "r"(H[0].x) : "memory");
      if (pw != 3) named_arrive(8, 384);
      else {
        named_sync(8, 384);
        if (elect()) {
          if (g1) asm volatile("red.relaxed.gpu.global.max.u32 [%0], %1;" :: "l"(scr + CNT_OFF + C_H * 128 + 8), "r"(gtime()) : "memory");
          load_wq(0, WQA, bars + B_WQ);
        }
        __syncwarp();
      }
      const uint2 st = lds64(base + OFF_LN + (lane & 15) * 8);
      const float sum = __uint_as_float(st.x), mean = sum * (1.0f / D_), var = ln_var(mean, __uint_as_float(st.y));
      const float m = rbf(mean), r = ln_rstd(var), r2 = ln_rstd(var * r * r);
      const float nc = fmaf(m, (float)D_, -sum) * (1.0f / D_) * (r * r2);
      const uint32_t m2 = pack2(m, m), r2x = pack2(r * r2, r * r2), nc2 = pack2(nc, nc);
      auto f = [&](uint32_t v) { return hfma2(hsub2(v, m2), r2x, nc2); };
#pragma unroll
      for (int i = 0; i < 7; i++) stg128(dst + i * 256, f(H[i].x), f(H[i].y), f(H[i].z), f(H[i].w));
      if (pw != 1) named_arrive(4, 128);
    }
    const int lane = lane_id();
    if (pw == 0) {
      if (elect()) {
        asm volatile("prefetch.tensormap [%0];" :: "l"(&m_w1) : "memory");
        asm volatile("prefetch.tensormap [%0];" :: "l"(&m_w2) : "memory");
        asm volatile("prefetch.tensormap [%0];" :: "l"(&m_res) : "memory");
      }
      __syncwarp();
      const uint32_t e = probe(scr + CNT_OFF + C_H * 128 + 4) + 1;
      sts32(bars + B_TAG, __uint_as_float((e & 0x3fffu) | ((e << 2) & 0x3fff0000u)));
      named_arrive(1, 96);
      if (g1) produce_box<64, 0>(base, 0, 32, &m_w1, ft * 64, 0);
      mbar_wait(bars + B_ATT, 0);
      if (elect()) { mbar_expect_tx(bars + B_RES, BT); tma3d(base + OFF_Q, &m_res, dt * 112, mt * 64, 0, bars + B_RES); }
      mbar_wait(bars + B_WO, 0);
      produce_lin<0>(base, 0, 7, scr + (dt * HU_T + 60) * BT, BT);
#pragma unroll 1
      for (int h = 0; h < 2; h++) produce_box<0, 8>(base, 7 + h * 14, 21 + h * 14, &m_w2, mt * 64, h * 8);
    } else if (pw == 1) {
      named_sync(4, 128);
      const unsigned char* hl = scr + (rb * 2 + (hp >> 2)) * BT + (hp & 3) * 3584 + min(lane, 27) * 128;
      settle(probe(hl) ^ probe(hl + HU_T * BT) ^ probe(hl + 2 * HU_T * BT) ^ probe(hl + 3 * HU_T * BT));
      publish(scr, C_H);
      OBS(lane == 0, 4);
      if (elect()) load_wq(WQA, 7, bars + B_WQ2);
      __syncwarp();
      if (g1) {
        __nanosleep(200);
        const uint32_t v = spin_ge(scr + (lane & 1) * 8, C_H, lane & 1 ? 0 : 128);
        if (lane == 1) sts32(bars + B_T0, __uint_as_float(v + TS));
        __syncwarp();
        OBS(lane == 0, 16);
        produce_lin<0>(base, 0, 32, scr + d1 * HU_T * BT, BT);
      }
      mbar_wait(bars + B_O, 0);
      if (OTAG) {
#pragma unroll 1
        for (int s = 0; s < 7; s++) {
          mbar_wait(bars + B_EMPTY + s * 8, 0);
          if (elect()) { mbar_expect_tx(bars + B_OL + s * 8, 8192); bulk_g2s(base + s * SLOT, scr + O_OFF + mt * 57344 + s * 8192, 8192, bars + B_OL + s * 8); }
        }
      } else produce_lin<0>(base, 0, 7, scr + O_OFF + mt * 57344, 8192);
      const unsigned char* us = scr + (dt * HU_T + 32) * BT;
      mbar_wait(bars + B_EMPTY + 56, 0);
      if (elect()) mbar_expect_tx(bars + 56, BT);
      __syncwarp();
      spin_ge(scr, C_U + dt, 28);
      if (elect()) bulk_g2s(base + 7 * SLOT + 8192, us, BT, bars + 56);
      if (lane == 0) mbar_arrive(bars + B_U1);
      const uint32_t tu = clock();
      OBS(lane == 0, 18);
      produce_lin<UP>(base, 8, 15, us + BT, BT, tu + UP);
#pragma unroll 1
      for (int h = 0; h < 2; h++) {
        if (h) mbar_wait(bars + B_U2, 0);
        produce_lin<0>(base, 15 + h * 6, 21 + h * 14, us + (8 + h * 6) * BT, BT);
      }
      unsigned tk = 0;
      if (lane == 0) tk = atomicAdd((unsigned*)(scr + CNT_OFF + C_TK * 128), 1u);
      if (__shfl_sync(0xffffffffu, tk, 0) == 127) {
#pragma unroll 1
        for (int i = lane; i < 160; i += 32) *(unsigned*)(scr + CNT_OFF + i * 128) = 0;
        *(unsigned*)(scr + CNT_OFF + C_H * 128 + 8) = 0;
        publish(scr + 4, C_H);
      }
    } else if (pw == 2) {
      uint32_t tn = clock();
      const unsigned char* src = p.w1 + b * 4096 + lane * 128;
#pragma unroll 1
      for (int i = 0; i < 28 + FREQ * 2; i++) {
        while ((int)(clock() - tn) < 0) __nanosleep(20);
        if (i == 14 || i == 21) src = p.w2 + ((b >> 3) * 16 + (b & 7) + (i & 1) * 8) * 4096 + lane * 128;
        if (i < 28) asm volatile("prefetch.global.L2 [%0];" :: "l"(src) : "memory");
        OBSG(FREQ && lane == 0, 129 + i, 161 + i);
        src += (i < 14 ? 128 : 256) * 4096;
        tn += i < 14 ? PACE1 : PACE2;
      }
    } else {
      if (b < 112) retile_wo(p.wo, scr, b, lane_id());
      const int lane = lane_id();
      unsigned char* hg = scr + HALO_OFF + (rb * 8 + hp) * 3584;
      named_sync(1, 96);
      const uint32_t tag = lds64(bars + B_TAG).x;
      if (rb < 15) {
#pragma unroll
        for (int q = 0; q < 7; q += 4) {
          uint4 v[4];
#pragma unroll
          for (int i = q; i < q + 4 && i < 7; i++) v[i - q] = lds128(base + OFF_K + 8 * 3584 + i * 512 + lane * 16 + (i * 32 + lane < 112 && !(lane & 7) ? 1792 : 0));
#pragma unroll
          for (int i = q; i < q + 4 && i < 7; i++) stg128(hg + i * 512 + lane * 16, (lane & 7) == (i * 32 + lane < 112) ? tag : v[i - q].x, v[i - q].y, v[i - q].z, v[i - q].w);
        }
        publish(scr, C_HALO + rb * 8 + hp);
      }
      OBS(lane == 0, 29);
      if (rb > 0) {
        spin_ge(scr, C_HALO + (rb - 1) * 8 + hp, 1);
        const uint32_t la = base + OFF_K + min(lane, 27) * 128;
#pragma unroll 1
        for (int n = 0;; n++) {
          if (elect()) { mbar_expect_tx(bars + B_HIN, 3584); bulk_g2s(base + OFF_K, hg - 8 * 3584, 3584, bars + B_HIN); }
          __syncwarp();
          mbar_wait(bars + B_HIN, n & 1);
          if (__all_sync(0xffffffffu, lds64(la + (lane < 14 ? 16 : 0)).x == tag)) break;
          if (n > 1000000) asm volatile("trap;");
        }
        if (lane < 14) { const uint4 v = lds128(la); sts128(la + 1792, v.x, v.y, v.z, v.w); }
      } else {
#pragma unroll
        for (int i = 0; i < 7; i++) sts128(base + OFF_K + i * 512 + lane * 16, 0, 0, 0, 0);
      }
      OBS(lane == 0, 12);
      smem_fence();
      __syncwarp();
      if (lane == 0) mbar_arrive(bars + B_HALO);
      __syncwarp();
      if (b < 112) {
        settle(probe(scr + (((b & 1) * 2 + (lane >> 4)) * HU_T + 60 + (b >> 4)) * BT + ((b >> 1) & 7) * 1792 + min(lane & 15, 13) * 128));
        publish(scr, C_WO);
      }
      mbar_wait(bars + (g1 ? B_GATE + 8 : B_ATT), 0);
      spin_ge(scr, C_WO, 112);
      if (lane == 0) mbar_arrive(bars + B_WO);
      mbar_wait(bars + B_ATT, 0);
      spin_ge(scr, C_O + (mt >> 1), 8);
      OBS(lane == 0, 17);
      if (lane == 0) mbar_arrive(bars + B_O);
      if (OTAG) {
#pragma unroll 1
        for (int s = 0; s < 7; s++) {
#pragma unroll 1
          for (int n = 0;; n++) {
            mbar_wait(bars + B_OL + s * 8, n & 1);
            const uint32_t a = base + s * SLOT + lane * 132;
            if (__all_sync(0xffffffffu, !(((lds32(a) ^ tag) | (lds32(a + 4096) ^ tag)) & 1))) break;
            if (n > 1000000) asm volatile("trap;");
            if (elect()) { mbar_expect_tx(bars + B_OL + s * 8, 8192); bulk_g2s(base + s * SLOT, scr + O_OFF + mt * 57344 + s * 8192, 8192, bars + B_OL + s * 8); }
            __syncwarp();
          }
          if (lane == 0) mbar_arrive(bars + s * 8);
        }
      }
      mbar_wait(bars + B_U1, 0);
      spin_ge(scr, C_U + 4 + dt, 28);
      OBS(lane == 0, 11);
      if (lane == 0) mbar_arrive(bars + B_U2);
    }
  } else {
    asm volatile("setmaxnreg.inc.sync.aligned.u32 232;");
    const int wg = warp >> 2, w4 = warp & 3, th = wg ^ 1;
    const bool rel = (tid & 127) < 2;
    unsigned char* scr = p.scr;
    uint32_t X[28][4];
    float aq[28];
    const uint32_t dlo = (base >> 4) + (512u << 16) + (hp & 1), dlq = dlo + (OFF_WQ >> 4);
    {
      uint32_t xa[4];
#pragma unroll
      for (int k = 0; k < 4; k++) xa[k] = base + OFF_X + (th * 64 + w4 * 16 + (mi >> 1) * 8 + r8) * 128 + (((2 * k + (mi & 1)) ^ r8) << 4);
      float c0[2][4] = {}, c1[2][4] = {};
      uint32_t one[8];
#pragma unroll
      for (int j = 0; j < 8; j++) asm volatile("{\n.reg .u32 y;\nmov.u32 y, %%tid.y;\nmad.lo.u32 %0, y, %1, 0x3f803f80;\n}" : "=r"(one[j]) : "r"(lane + j));
      asm volatile("" : "+l"(scr));
      uint32_t ok = 0;
      const uint32_t bx = bars + B_X + wg * 64;
      {
#pragma unroll 1
        for (int n = 0; n < 64 && !ok; n++) { mma16816(c0[0], 0, 0, 0, 0, 0, 0); ok = mbar_try(bars + B_X, 0); }
        if (wg) ok = 0;
      }
#pragma unroll
      for (int i = 0; i < 8; i++) {
        if (i < 7) {
          if (!ok) mbar_wait(bx + i * 8, 0);
          OBS(tid == 64 && i == 0, 0); OBS(tid == 64 && i == 6, 15);
#pragma unroll
          for (int k = 0; k < 4; k++) ldsm4(X[i * 4 + k], xa[k] + i * 16384);
          if (i < 6) ok = mbar_try(bx + i * 8 + 8, 0);
        }
        if (i > 0) {
#pragma unroll
          for (int k = i * 4 - 4; k < i * 4; k++) {
            mma16816(c0[k & 1], X[k][0], one[(k & 1) * 4], X[k][1], one[(k & 1) * 4 + 1], X[k][0], X[k][1]);
            mma16816(c1[k & 1], X[k][2], one[(k & 1) * 4 + 2], X[k][3], one[(k & 1) * 4 + 3], X[k][2], X[k][3]);
          }
        }
      }
      float st[4];
#pragma unroll
      for (int j = 0; j < 2; j++) {
        st[j] = __shfl_sync(0xffffffffu, (g & 1) ? c0[0][2 * j + 1] + c0[1][2 * j + 1] : c0[0][2 * j] + c0[1][2 * j], (lane & 28) | (g >> 1));
        st[2 + j] = __shfl_sync(0xffffffffu, (g & 1) ? c1[0][2 * j + 1] + c1[1][2 * j + 1] : c1[0][2 * j] + c1[1][2 * j], (lane & 28) | (g >> 1));
      }
      named_arrive(8, 384);
      fence_code(20);
      named_arrive_if(wg, 0, 256);
      asm volatile("{\n.reg .pred q;\nsetp.ne.u32 q, %3, 0;\n@q st.shared.v2.f32 [%0], {%1,%2};\n@q bar.arrive 9, 160;\n}"
                   :: "r"(base + OFF_LN + ((t & 1) * 8 + g) * 8), "f"((t & 1) ? st[3] : st[1]), "f"((t & 1) ? st[2] : st[0]), "r"((uint32_t)((warp ^ 4) == hp)) : "memory");
      ok = mbar_try(bars + B_KV, 0);
      LnC l0, l1;
      float eps = 1e-5f;
#pragma unroll 1
      do {
        l0 = ln_consts(st[1], st[0], eps); l1 = ln_consts(st[3], st[2], eps);
#pragma unroll
        for (int k = 0; k < 16; k++) X[k >> 2][k & 3] = hsub2(X[k >> 2][k & 3], k & 2 ? l1.m : l0.m);
        eps += eps;
      } while ((l0.rl ^ l1.rl) == 4);
      OBS(tid == 32, 1);
      float ak[60], *av = ak + 32;
      auto norm = [&](int s) {
#pragma unroll
        for (int k = s * 4; k < s * 4 + 4; k++) {
          auto f = [&](uint32_t d, const LnC& l) { return s ? ln_apply(d, l) : hfma2(d, l.rh, hmul2(d, l.rl)); };
          const uint32_t y = f(X[k][1], l0);
          X[k][0] = f(X[k][0], l0); X[k][1] = f(X[k][2], l1); X[k][2] = y; X[k][3] = f(X[k][3], l1);
        }
      };
      const int pp_in = wg ? 6 : 0, pp_out = wg ? 0 : 6;
#pragma unroll
      for (int s = 0; s < 7; s++) {
        if (s != 1 || wg) norm(s);
        if (s == 0 && !wg) norm(1);
        if (__builtin_expect(!ok, 0)) { mbar_wait(bars + B_KV + s * 8, 0); if (s == 6) mbar_wait(bars + B_WQ, 0); }
        if (s == 0) fresh(ak);
        OBS(KOBS && (tid & 127) == 0, 40 + wg * 32 + s);
        if (wg ? s < 6 : s != 1) named_sync(pp_in, 256);
        OBS(KOBS && (tid & 127) == 32, 48 + wg * 32 + s);
        OBS(tid == 64 && s == 0, 2);
        wg_fence();
#pragma unroll
        for (int k = 0; k < 4; k++) {
          wgmma_rs_n120<1>(ak, X[s * 4 + k], mkdesc(HI_SW128, dlo + s * 1024 + k * 128), (s | k) != 0);
        }
        wg_commit();
        if (s == 6) {
          wg_wait<1>();
          if ((tid & 127) == 0) mbar_arrive(bars + B_EMPTY + 3 * 8);
          fresh(aq);
#pragma unroll
          for (int k = 0; k < 4; k++) {
            if (k == 2) named_arrive(pp_out, 256);
            wgmma_rs_n56<1>(aq, X[k], mkdesc(HI_SW128, dlq + k * 128), k);
          }
          wg_commit();
        }
        if (s < 6) named_arrive_if(wg ? s != 5 : s != 0, pp_out, 256);
        fence_code(s);
        OBS(KOBS && (tid & 127) == 64, 56 + wg * 32 + s);
        if (s < 6) ok = mbar_try(bars + B_KV + s * 8 + 8, 0);
        if (s == 5) ok &= mbar_try(bars + B_WQ, 0);
        OBS(tid == 64 && s == 5, 31);
        if (s > 0) wg_wait<1>();
        OBS(KOBS && (tid & 127) == 96, 64 + wg * 32 + s);
        if ((s == 2 || s == 3 || s == 5) && (tid & 127) == 0) mbar_arrive(bars + B_EMPTY + (s == 5 ? 2 : s - 2) * 8);
      }
      if ((tid & 127) == 0) mbar_arrive(bars + B_EMPTY + 4 * 8);
      OBS(tid == 32, 3);
      {
        const uint32_t kst = base + OFF_K + (2 + (warp ^ 4) * 2 + (mi & 1)) * 1792 + (mi >> 1) * 896 + r8 * 16;
#pragma unroll
        for (int n = 0; n < 7; n++)
          stsm4(kst + n * 128, pack2(ak[n * 4], ak[n * 4 + 1]), pack2(ak[n * 4 + 2], ak[n * 4 + 3]), pack2(av[n * 4], av[n * 4 + 1]), pack2(av[n * 4 + 2], av[n * 4 + 3]));
        named_arrive_if(warp == 3, 1, 96);
      }
      OBS(tid == 96, 32); OBS(tid == 224, 34);
      wg_wait<0>();
      if ((tid & 127) == 0) mbar_arrive(bars + B_EMPTY + 5 * 8);
      mbar_wait(bars + B_WQ2, 0);
    }
    const unsigned short *bp1 = (const unsigned short*)p.b1 + (g1 ? ft * 64 : 0) + w4 * 16 + g, *bp2 = (const unsigned short*)p.b2 + mt * 64 + w4 * 16 + g;
    const uint32_t braw[4] = {__ldg(bp1), __ldg(bp1 + 8), __ldg(bp2), __ldg(bp2 + 8)};
    auto q_rest = [&]() {
      wg_fence();
#pragma unroll
      for (int s = 1; s < 7; s++) {
#pragma unroll
        for (int k = s * 4; k < s * 4 + 4; k++) wgmma_rs_n56<1>(aq, X[k], mkdesc(HI_SW128, dlq + k * 128), 1);
        wg_commit();
        if (s == 5) { wg_wait<2>(); if ((tid & 127) == 0) mbar_arrive(bars + B_EMPTY + 6 * 8); }
      }
    };
    uint32_t Q[4][4];
    auto q_pack = [&]() {
#pragma unroll
      for (int n = 0; n < 14; n++) { const int m = n + 2 * (n > 7); Q[m >> 2][m & 3] = pack2(aq[n * 2], aq[n * 2 + 1]); }
#pragma unroll
      for (int h = 0; h < 2; h++) { Q[2][h] = t < 2 ? 0u : Q[1][2 + h]; Q[1][2 + h] = t < 2 ? Q[1][2 + h] : 0u; }
    };
    float acc[56];
    auto ai = [](int p) { return p < 4 ? 48 + (p & 1) * 4 + (p & 2) : (p - 4) * 4; };
    uint32_t xch, ts, tl;
    unsigned char *outp, *outq;
    auto setup_out = [&]() {
      xch = pin(base + OFF_K + (tid & 127) * 16);
      const uint32_t tb = base + OFF_K + 6144 + warp * 2560;
      ts = pin(tb + mi * 160 + r8 * 16); tl = pin(tb + t * 160 + g * 16);
      unsigned char* o = p.out + (mt * 64 + w4 * 16 + g) * 896 + dt * 224;
      outp = pin(o + th * 7168 + t * 16); outq = pin(o + (t >> 1) * 7168 + 192 + (t & 1) * 16);
    };
    auto give = [&](const float (&a)[56], int id) {
#pragma unroll
      for (int i = 0; i < 48; i += 16) sts128(xch + i * 128, pack2(a[i + 2], a[i + 3]), pack2(a[i + 6], a[i + 7]), pack2(a[i + 10], a[i + 11]), pack2(a[i + 14], a[i + 15]));
      named_arrive(id, 256);
    };
    auto take = [&](uint32_t (&r)[12], int id) {
      named_sync(id, 256);
#pragma unroll
      for (int i = 0; i < 3; i++) { const uint4 v = lds128(xch + i * 2048); r[i * 4] = v.x; r[i * 4 + 1] = v.y; r[i * 4 + 2] = v.z; r[i * 4 + 3] = v.w; }
    };
    float hv[32];
    auto keep_h = [&](int i) {
      const float hb0 = 0.5f * bf_lo(braw[i]), hb1 = 0.5f * bf_lo(braw[i + 1]);
#pragma unroll
      for (int j = 0; j < 32; j++) hv[j] = fmaf(acc[ai(j >> 1) + (j & 1)], 0.5f, j >= 4 && j < 8 ? hb1 : hb0);
    };
    auto take_h = [&](int i) {
      const float hb1 = 0.5f * bf_lo(braw[i + 1]);
      uint32_t r[12];
      take(r, 5);
#pragma unroll
      for (int j = 0; j < 12; j++) { hv[8 + 2 * j] = fmaf(bf_lo(r[j]), 0.5f, hb1); hv[9 + 2 * j] = fmaf(bf_hi(r[j]), 0.5f, hb1); }
    };
    uint4 Xr[4];
    auto get_x = [&]() {
      const uint32_t xr = base + OFF_Q + (w4 * 16 + g) * 224;
      mbar_wait(bars + B_RES, 0);
      Xr[0] = lds128(xr + (t >> 1) * 1792 + 192 + (t & 1) * 16);
#pragma unroll
      for (int i = 1; i < 4; i++) Xr[i] = lds128(xr + th * 1792 + t * 16 + (i - 1) * 64);
    };
    uint32_t Sv[16];
    auto gate = [&](int i) {
      uint32_t R[4];
#pragma unroll
      for (int q = 0; q < 4; q++) {
        const int j = i * 4 + q;
        const float h0 = hv[2 * j], h1 = hv[2 * j + 1];
        R[q] = hmul2(Sv[j], pack2(fmaf(h0, tanh_fast(h0), h0), fmaf(h1, tanh_fast(h1), h1)));
      }
      stsm4(ts + i * 640, R[0], R[1], R[2], R[3]);
    };
    auto leave = [&](int i) {
      __syncwarp();
      const uint4 v = lds128(tl + i * 640), x = Xr[i];
      stg128(i ? outp + (i - 1) * 64 : outq, hadd2(x.x, v.x), hadd2(x.y, v.y), hadd2(x.z, v.z), hadd2(x.w, v.w));
    };
    if (wg == 0) {
      named_sync(0, 256);
      OBS(tid == 96, 14);
      q_rest();
      named_arrive(6, 256);
      wg_wait<0>();
      if (tid == 0) mbar_arrive(bars + B_EMPTY + 7 * 8);
      q_pack();
      const uint32_t qst = base + OFF_Q + 8192 + (mi >> 1) * 1024 + (w4 * 16 + (mi & 1) * 8 + r8) * 16;
#pragma unroll
      for (int n = 0; n < 4; n++) stsm4(qst + n * 2048, Q[n][0], Q[n][1], Q[n][2], Q[n][3]);
      smem_fence();
      named_arrive(7, 256);
      OBS(tid == 32, 5);
      fresh(acc);
      if (g1) {
        unsigned char* ug = pin(scr + (d1 * HU_T + 32 + (ft >> 1)) * BT + ((ft & 1) * 4 + w4) * 1792 + lane * 4);
        unsigned char* ur = pin(ug + min(lane, 13) * 128);
        unsigned char* uc = pin(scr + d1 * 128);
        mbar_wait(bars, 0); mbar_wait(bars + 8, 0);
        {
          const uint32_t tg = lds64(bars + B_T0).x;
          while (tg - gtime() - 1 < 1000u);
        }
        named_sync(0, 256);
        gemm_issue<1>(acc, base >> 4, 0);
        OBS(tid == 0, 20);
        gemm_loop<1>(acc, base, 1, 32, rel, 40, 1, tid == 32 ? J1 : tid == 64 ? J2 : -1, bars + B_GATE - 8 + w4 * 8);
        wg_wait<0>();
        OBS(tid == 0, 21);
        named_arrive(5, 256);
        mbar_arrive_if(rel, bars + B_EMPTY + 7 * 8);
        auto gelu = [&](int n, int h) {
          const float hb = 0.5f * bf_lo(braw[h]);
          const float h0 = fmaf(acc[4 * n + 2 * h], 0.5f, hb), h1 = fmaf(acc[4 * n + 2 * h + 1], 0.5f, hb);
          const float t0 = tanh_fast(h0 * fmaf(h0 * h0, 0.2854192648f, 1.5957691216f)), t1 = tanh_fast(h1 * fmaf(h1 * h1, 0.2854192648f, 1.5957691216f));
          return pack2(fmaf(h0, t0, h0), fmaf(h1, t1, h1));
        };
        auto done = [&](int h) {
          if (w4) named_arrive(13 + h, 128);
          else { named_sync(13 + h, 128); publish(uc, C_U + h * 4); OBS(tid == 0, h ? 13 : 9); }
          fence_code(10 + h);
        };
#pragma unroll
        for (int n = 0; n < 14; n++) { stg32(ug + n * 128, gelu(n, 0)); if (n == 6) fence_code(8); }
        settle(probe(ur));
        named_arrive(12, 256);
        done(0);
#pragma unroll
        for (int n = 0; n < 14; n++) { stg32(ug + 14 * BT + n * 128, gelu(n, 1)); if (n == 6) fence_code(9); }
        settle(probe(ur + 14 * BT));
        done(1);
      } else if (tid == 32 || tid == 64) mbar_arrive(bars + B_GATE - 8 + w4 * 8);
      setup_out();
      get_x();
      uint32_t r[12];
      take(r, 3);
#pragma unroll
      for (int j = 0; j < 16; j++) Sv[j] = r[j < 4 ? 0 : j - 4];
      asm volatile("" :: "r"(r[0]), "r"(r[11]) : "memory");
      named_arrive(10, 256);
      take_h(2);
    } else {
      const uint32_t dq = ((base + OFF_Q) >> 4) + (64u << 16), dk = (base + OFF_K) >> 4;
      const bool odd = g & 1, early = 2 * t + (g & 1) > g;
      uint32_t selA[5], selB[4];
#pragma unroll
      for (int j = 0; j < 5; j++) { selA[j] = j == w4 + (early ? 0 : 1) ? (odd ? 0x1044u : 0x4410u) : 0x4444u; }
#pragma unroll
      for (int j = 0; j < 4; j++) { selB[j] = j == w4 ? (odd ? 0x3244u : 0x4432u) : 0x4444u; }
      float Sc[2][40], Op[2][2][16];
      uint32_t A[2][5][4];
      auto scores = [&](int T) {
        fresh(Sc[0]); fresh(Sc[1]);
#pragma unroll
        for (int k = 0; k < 2; k++) {
#pragma unroll
          for (int hh = 0; hh < 2; hh++)
            if (T) wgmma_n80<0, 0>(Sc[hh], mkdesc(8, dq + 512 + hh * 256 + k * 128), mkdesc(112, dk + (8u << 16) + 896 + hh * 24 + k * 16), k);
            else wgmma_rs_n80<0>(Sc[hh], Q[hh * 2 + k], mkdesc(112, dk + (8u << 16) + hh * 24 + k * 16), k);
        }
      };
      auto softmax = [&](int T) {
        uint32_t L[2][2];
        auto pick = [&](int w) {
#pragma unroll
          for (int hh = 0; hh < 2; hh++) {
            const float* q = Sc[hh] + w * 8;
            auto at = [&](int i) { return odd ? q[i + 1] : q[i]; };
            L[hh][0] = pack2(early ? at(0) : at(8), early ? at(6) : at(14)); L[hh][1] = pack2(at(4), at(10));
          }
          asm volatile("" ::: "memory");
        };
        if (w4 & 2) { if (w4 & 1) pick(3); else pick(2); } else { if (w4 & 1) pick(1); else pick(0); }
#pragma unroll
        for (int hh = 0; hh < 2; hh++) {
          uint32_t a = hfma2(L[hh][0], SC_HI, hmul2(L[hh][0], SC_LO)), c = hfma2(L[hh][1], SC_HI, hmul2(L[hh][1], SC_LO));
          if (T == 0 && w4 == 0 && rb == 0) { if (early) a = 0xce6ece6eu; c = (c & 0xffff0000u) | 0xce6eu; }
          uint32_t mx = hmax2(a, c);
          mx = hmax2(mx, __shfl_xor_sync(0xffffffffu, mx, 1));
          mx = hmax2(mx, __shfl_xor_sync(0xffffffffu, mx, 2));
          uint32_t pp[2];
#pragma unroll
          for (int h = 0; h < 2; h++) {
            const float m = h ? bf_hi(mx) : bf_lo(mx);
            const float p0 = ex2_fast(((h ? bf_hi(a) : bf_lo(a)) - m) * LOG2E), p1 = ex2_fast(((h ? bf_hi(c) : bf_lo(c)) - m) * LOG2E);
            float sm = p0 + p1;
            sm += __shfl_xor_sync(0xffffffffu, sm, 1);
            sm += __shfl_xor_sync(0xffffffffu, sm, 2);
            const float inv = rcp_fast(sm);
            pp[h] = pack2(p0 * inv, p1 * inv);
          }
#pragma unroll
          for (int j = 0; j < 5; j++) {
            A[hh][j][0] = place(pp[0], selA[j]); A[hh][j][1] = j ? place(pp[1], selB[j ? j - 1 : 0]) : 0u;
            A[hh][j][2] = j < 4 ? place(pp[0], selB[j & 3]) : 0u; A[hh][j][3] = place(pp[1], selA[j]);
          }
        }
      };
      auto values = [&](int T) {
        fresh(Op[T][0]); fresh(Op[T][1]);
#pragma unroll
        for (int j = 0; j < 5; j++)
#pragma unroll
          for (int hh = 0; hh < 2; hh++) {
            wgmma_rs_n32<1>(Op[T][hh], A[hh][j], mkdesc(8, dk + (112u << 16) + 56 + T * 896 + hh * 24 + j * 224), j);
          }
        wg_commit();
      };
      uint32_t Ob[2][14];
      auto pack = [&](int T) {
        const float (&O)[2][16] = Op[T];
#pragma unroll
        for (int n = 0; n < 7; n++)
#pragma unroll
          for (int h = 0; h < 2; h++) {
            if (n < 3) Ob[T][n * 2 + h] = pack2(O[0][n * 4 + 2 * h], O[0][n * 4 + 2 * h + 1]);
            else if (n == 3) Ob[T][n * 2 + h] = pack2(t < 2 ? O[0][12 + 2 * h] : O[1][2 * h], t < 2 ? O[0][13 + 2 * h] : O[1][2 * h + 1]);
            else Ob[T][n * 2 + h] = pack2(O[1][(n - 3) * 4 + 2 * h], O[1][(n - 3) * 4 + 2 * h + 1]);
          }
      };
      smem_fence();
      named_sync(6, 256);
      OBS(tid == 224, 26);
      q_rest();
      named_sync(7, 256);
      wg_fence();
      scores(1);
      wg_commit();
      named_arrive_if(g1, 0, 256);
      wg_wait<2>();
      if (tid == 128) mbar_arrive(bars + B_EMPTY + 7 * 8);
      wg_wait<0>();
      OBS(tid == 160, 10);
      softmax(1);
      q_pack();
      OBS(tid == 160, 30);
      mbar_wait(bars + B_HALO, 0);
      OBS(tid == 160, 7);
      mbar_wait(bars + B_GATE, 0);
      wg_fence();
      scores(0);
      values(1);
      wg_wait<0>();
      OBS(tid == 160, 33);
      unsigned char* og = scr + O_OFF + rb * 2 * 57344 + hp * 7168 + w4 * 256 + lane * 4;
      uint32_t seen[6];
      const uint32_t tag = OTAG ? lds32(bars + B_TAG) : 0, m0 = OTAG && r8 == 2 * w4, m1 = OTAG && r8 == 2 * w4 + 1;
      auto put = [&](int T) {
#pragma unroll
        for (int n = 0; n < 7; n++) {
          stg32(og + T * 57344 + n * 1024, (Ob[T][2 * n] & ~m0) | (tag & m0)); stg32(og + T * 57344 + n * 1024 + 128, (Ob[T][2 * n + 1] & ~m1) | (tag & m1));
          if (!OTAG) if (n == 2 || n == 5 || n == 6) seen[T * 3 + n / 3] = probe(og + T * 57344 + (n - (n == 6 ? 0 : min(g, 2))) * 1024 + (t & 1) * 128);
          __nanosleep(20);
        }
      };
      pack(1); put(1);
      softmax(0);
      mbar_wait(bars + B_GATE + 8, 0);
      wg_fence();
      values(0);
      wg_wait<0>();
      OBS(tid == 160, 35);
      named_sync(11, 128);
      if (tid == 160) mbar_arrive(bars + B_ATT);
      pack(0); put(0);
      OBS(tid == 160, 28);
      if (!OTAG) settle(seen[0] ^ seen[1] ^ seen[2] ^ seen[3] ^ seen[4] ^ seen[5]);
      named_sync(11, 128);
      if (warp == 4) publish(scr, C_O + rb);
      OBS(tid == 160, 8);
      setup_out();
      float as[56];
      if (g1) named_sync(5, 256);
      get_x();
      mbar_wait(bars, 0);
      if (g1) named_sync(12, 256);
      fresh(as);
      gemm_issue<0>(as, base >> 4, 0);
      OBS(tid == 128, 22);
      gemm_loop<0>(as, base, 1, 7, rel, 104);
      fresh(acc);
      mbar_wait(bars + 56, 0);
      gemm_issue<1>(acc, (base + 7 * SLOT) >> 4, 0);
      OBS(tid == 128, 24);
      wg_wait<1>();
      mbar_arrive_if(rel, bars + B_EMPTY + 6 * 8);
      give(as, 3);
#pragma unroll
      for (int j = 0; j < 16; j++) Sv[j] = pack2(as[ai(j)], as[ai(j) + 1]);
      gemm_loop<1>(acc, base, 8, 35, rel, 65);
      named_sync(10, 256);
      wg_wait<0>();
      OBS(tid == 128, 25);
      give(acc, 5);
      fence_code(31);
      keep_h(2);
      gate(0); leave(0);
    }
    {
#pragma unroll
      for (int i = 1; i < 4; i++) { gate(i); leave(i); }
      OBS(tid == 128, 27);
    }
  }
}

typedef CUresult (*EncFn)(CUtensorMap*, CUtensorMapDataType, cuuint32_t, void*, const cuuint64_t*, const cuuint64_t*, const cuuint32_t*,
                          const cuuint32_t*, CUtensorMapInterleave, CUtensorMapSwizzle, CUtensorMapL2promotion, CUtensorMapFloatOOBfill);
void enc(EncFn f, CUtensorMap* m, const void* ptr, cuuint64_t d0, cuuint64_t d1, cuuint64_t d2, cuuint64_t s1, cuuint64_t s2, cuuint32_t b1, cuuint32_t b2, cuuint32_t b0 = 64) {
  const cuuint64_t gd[3] = {d0, d1, d2}, gs[2] = {s1 * 2, s2 * 2};
  const cuuint32_t bx[3] = {b0, b1, b2}, es[3] = {1, 1, 1};
  f(m, CU_TENSOR_MAP_DATA_TYPE_BFLOAT16, 3, (void*)ptr, gd, gs, bx, es, CU_TENSOR_MAP_INTERLEAVE_NONE, b0 == 64 ? CU_TENSOR_MAP_SWIZZLE_128B : CU_TENSOR_MAP_SWIZZLE_NONE,
    CU_TENSOR_MAP_L2_PROMOTION_L2_128B, CU_TENSOR_MAP_FLOAT_OOB_FILL_NONE);
}
}

extern "C" void kernel_launch(void* const* d_in, const int* in_sizes, int n_in, void* d_out, int out_size) {
  (void)in_sizes; (void)n_in; (void)out_size;
  void* fp = nullptr;
  cudaDriverEntryPointQueryResult qr;
  cudaGetDriverEntryPoint("cuTensorMapEncodeTiled", &fp, cudaEnableDefault, &qr);
  EncFn f = (EncFn)fp;
  CUtensorMap m_x, m_wkv, m_wq, m_w1, m_w2, m_res;
  void* scr = nullptr;
  cudaGetSymbolAddress(&scr, g_scr);
  enc(f, &m_x, d_in[0], D_, S_, 1, D_, D_, 64, 1);
  enc(f, &m_wkv, d_in[1], D_, D_, 3, 3 * D_, D_, 64, 2);
  enc(f, &m_wq, d_in[1], D_, D_, 3, 3 * D_, D_, 64, 1);
  enc(f, &m_w1, d_in[4], F_, S_, 1, F_, F_, 64, 1);
  enc(f, &m_w2, d_in[6], S_, 16, F_ / 16, S_, 16 * S_, 8, 8);
  enc(f, &m_res, d_in[0], D_, S_, 1, D_, D_, 64, 1, 112);
  Params p;
  p.wqkv = (const unsigned char*)d_in[1]; p.wo = (const unsigned char*)d_in[2];
  p.w1 = (const unsigned char*)d_in[4]; p.b1 = (const unsigned char*)d_in[5];
  p.w2 = (const unsigned char*)d_in[6]; p.b2 = (const unsigned char*)d_in[7];
  p.out = (unsigned char*)d_out; p.scr = (unsigned char*)scr;
  cudaFuncSetAttribute(fused_kernel, cudaFuncAttributeMaxDynamicSharedMemorySize, SMEM_BYTES);
  fused_kernel<<<128, NTHREADS, SMEM_BYTES, cudaStreamPerThread>>>(m_x, m_wkv, m_wq, m_w1, m_w2, m_res, p);
}
```

```cpp
#include <cuda_runtime.h>
#include <cuda.h>
#include <cuda_bf16.h>
#include <stdint.h>

template<int TA, int TB> __device__ __forceinline__ void wgmma_n112(float (&d)[56], uint64_t da, uint64_t db, int sc) {
  asm volatile("{\n.reg .pred p;\nsetp.ne.b32 p, %58, 0;\n"
    "wgmma.mma_async.sync.aligned.m64n112k16.f32.bf16.bf16 {%0, %1, %2, %3, %4, %5, %6, %7, %8, %9, %10, %11, %12, %13, %14, %15, %16, %17, %18, %19, %20, %21, %22, %23, %24, %25, %26, %27, %28, %29, %30, %31, %32, %33, %34, %35, %36, %37, %38, %39, %40, %41, %42, %43, %44, %45, %46, %47, %48, %49, %50, %51, %52, %53, %54, %55}, %56, %57, p, 1, 1, %59, %60;\n}\n"
    : "+f"(d[0]), "+f"(d[1]), "+f"(d[2]), "+f"(d[3]), "+f"(d[4]), "+f"(d[5]), "+f"(d[6]), "+f"(d[7]), "+f"(d[8]), "+f"(d[9]), "+f"(d[10]), "+f"(d[11]), "+f"(d[12]), "+f"(d[13]), "+f"(d[14]), "+f"(d[15]), "+f"(d[16]), "+f"(d[17]), "+f"(d[18]), "+f"(d[19]), "+f"(d[20]), "+f"(d[21]), "+f"(d[22]), "+f"(d[23]), "+f"(d[24]), "+f"(d[25]), "+f"(d[26]), "+f"(d[27]), "+f"(d[28]), "+f"(d[29]), "+f"(d[30]), "+f"(d[31]), "+f"(d[32]), "+f"(d[33]), "+f"(d[34]), "+f"(d[35]), "+f"(d[36]), "+f"(d[37]), "+f"(d[38]), "+f"(d[39]), "+f"(d[40]), "+f"(d[41]), "+f"(d[42]), "+f"(d[43]), "+f"(d[44]), "+f"(d[45]), "+f"(d[46]), "+f"(d[47]), "+f"(d[48]), "+f"(d[49]), "+f"(d[50]), "+f"(d[51]), "+f"(d[52]), "+f"(d[53]), "+f"(d[54]), "+f"(d[55])
    : "l"(da), "l"(db), "r"(sc), "n"(TA), "n"(TB));
}

template<int TA, int TB> __device__ __forceinline__ void wgmma_n80(float (&d)[40], uint64_t da, uint64_t db, int sc) {
  asm volatile("{\n.reg .pred p;\nsetp.ne.b32 p, %42, 0;\n"
    "wgmma.mma_async.sync.aligned.m64n80k16.f32.bf16.bf16 {%0, %1, %2, %3, %4, %5, %6, %7, %8, %9, %10, %11, %12, %13, %14, %15, %16, %17, %18, %19, %20, %21, %22, %23, %24, %25, %26, %27, %28, %29, %30, %31, %32, %33, %34, %35, %36, %37, %38, %39}, %40, %41, p, 1, 1, %43, %44;\n}\n"
    : "+f"(d[0]), "+f"(d[1]), "+f"(d[2]), "+f"(d[3]), "+f"(d[4]), "+f"(d[5]), "+f"(d[6]), "+f"(d[7]), "+f"(d[8]), "+f"(d[9]), "+f"(d[10]), "+f"(d[11]), "+f"(d[12]), "+f"(d[13]), "+f"(d[14]), "+f"(d[15]), "+f"(d[16]), "+f"(d[17]), "+f"(d[18]), "+f"(d[19]), "+f"(d[20]), "+f"(d[21]), "+f"(d[22]), "+f"(d[23]), "+f"(d[24]), "+f"(d[25]), "+f"(d[26]), "+f"(d[27]), "+f"(d[28]), "+f"(d[29]), "+f"(d[30]), "+f"(d[31]), "+f"(d[32]), "+f"(d[33]), "+f"(d[34]), "+f"(d[35]), "+f"(d[36]), "+f"(d[37]), "+f"(d[38]), "+f"(d[39])
    : "l"(da), "l"(db), "r"(sc), "n"(TA), "n"(TB));
}

template<int TB> __device__ __forceinline__ void wgmma_rs_n120(float (&d)[60], const uint32_t (&a)[4], uint64_t db, int sc) {
  asm volatile("{\n.reg .pred p;\nsetp.ne.b32 p, %65, 0;\n"
    "wgmma.mma_async.sync.aligned.m64n120k16.f32.bf16.bf16 {%0, %1, %2, %3, %4, %5, %6, %7, %8, %9, %10, %11, %12, %13, %14, %15, %16, %17, %18, %19, %20, %21, %22, %23, %24, %25, %26, %27, %28, %29, %30, %31, %32, %33, %34, %35, %36, %37, %38, %39, %40, %41, %42, %43, %44, %45, %46, %47, %48, %49, %50, %51, %52, %53, %54, %55, %56, %57, %58, %59}, {%60, %61, %62, %63}, %64, p, 1, 1, %66;\n}\n"
    : "+f"(d[0]), "+f"(d[1]), "+f"(d[2]), "+f"(d[3]), "+f"(d[4]), "+f"(d[5]), "+f"(d[6]), "+f"(d[7]), "+f"(d[8]), "+f"(d[9]), "+f"(d[10]), "+f"(d[11]), "+f"(d[12]), "+f"(d[13]), "+f"(d[14]), "+f"(d[15]), "+f"(d[16]), "+f"(d[17]), "+f"(d[18]), "+f"(d[19]), "+f"(d[20]), "+f"(d[21]), "+f"(d[22]), "+f"(d[23]), "+f"(d[24]), "+f"(d[25]), "+f"(d[26]), "+f"(d[27]), "+f"(d[28]), "+f"(d[29]), "+f"(d[30]), "+f"(d[31]), "+f"(d[32]), "+f"(d[33]), "+f"(d[34]), "+f"(d[35]), "+f"(d[36]), "+f"(d[37]), "+f"(d[38]), "+f"(d[39]), "+f"(d[40]), "+f"(d[41]), "+f"(d[42]), "+f"(d[43]), "+f"(d[44]), "+f"(d[45]), "+f"(d[46]), "+f"(d[47]), "+f"(d[48]), "+f"(d[49]), "+f"(d[50]), "+f"(d[51]), "+f"(d[52]), "+f"(d[53]), "+f"(d[54]), "+f"(d[55]), "+f"(d[56]), "+f"(d[57]), "+f"(d[58]), "+f"(d[59])
    : "r"(a[0]), "r"(a[1]), "r"(a[2]), "r"(a[3]), "l"(db), "r"(sc), "n"(TB));
}

template<int TB> __device__ __forceinline__ void wgmma_rs_n56(float (&d)[28], const uint32_t (&a)[4], uint64_t db, int sc) {
  asm volatile("{\n.reg .pred p;\nsetp.ne.b32 p, %33, 0;\n"
    "wgmma.mma_async.sync.aligned.m64n56k16.f32.bf16.bf16 {%0, %1, %2, %3, %4, %5, %6, %7, %8, %9, %10, %11, %12, %13, %14, %15, %16, %17, %18, %19, %20, %21, %22, %23, %24, %25, %26, %27}, {%28, %29, %30, %31}, %32, p, 1, 1, %34;\n}\n"
    : "+f"(d[0]), "+f"(d[1]), "+f"(d[2]), "+f"(d[3]), "+f"(d[4]), "+f"(d[5]), "+f"(d[6]), "+f"(d[7]), "+f"(d[8]), "+f"(d[9]), "+f"(d[10]), "+f"(d[11]), "+f"(d[12]), "+f"(d[13]), "+f"(d[14]), "+f"(d[15]), "+f"(d[16]), "+f"(d[17]), "+f"(d[18]), "+f"(d[19]), "+f"(d[20]), "+f"(d[21]), "+f"(d[22]), "+f"(d[23]), "+f"(d[24]), "+f"(d[25]), "+f"(d[26]), "+f"(d[27])
    : "r"(a[0]), "r"(a[1]), "r"(a[2]), "r"(a[3]), "l"(db), "r"(sc), "n"(TB));
}

template<int TB> __device__ __forceinline__ void wgmma_rs_n32(float (&d)[16], const uint32_t (&a)[4], uint64_t db, int sc) {
  asm volatile("{\n.reg .pred p;\nsetp.ne.b32 p, %21, 0;\n"
    "wgmma.mma_async.sync.aligned.m64n32k16.f32.bf16.bf16 {%0, %1, %2, %3, %4, %5, %6, %7, %8, %9, %10, %11, %12, %13, %14, %15}, {%16, %17, %18, %19}, %20, p, 1, 1, %22;\n}\n"
    : "+f"(d[0]), "+f"(d[1]), "+f"(d[2]), "+f"(d[3]), "+f"(d[4]), "+f"(d[5]), "+f"(d[6]), "+f"(d[7]), "+f"(d[8]), "+f"(d[9]), "+f"(d[10]), "+f"(d[11]), "+f"(d[12]), "+f"(d[13]), "+f"(d[14]), "+f"(d[15])
    : "r"(a[0]), "r"(a[1]), "r"(a[2]), "r"(a[3]), "l"(db), "r"(sc), "n"(TB));
}

template<int TB> __device__ __forceinline__ void wgmma_rs_n80(float (&d)[40], const uint32_t (&a)[4], uint64_t db, int sc) {
  asm volatile("{\n.reg .pred p;\nsetp.ne.b32 p, %45, 0;\n"
    "wgmma.mma_async.sync.aligned.m64n80k16.f32.bf16.bf16 {%0, %1, %2, %3, %4, %5, %6, %7, %8, %9, %10, %11, %12, %13, %14, %15, %16, %17, %18, %19, %20, %21, %22, %23, %24, %25, %26, %27, %28, %29, %30, %31, %32, %33, %34, %35, %36, %37, %38, %39}, {%40, %41, %42, %43}, %44, p, 1, 1, %46;\n}\n"
    : "+f"(d[0]), "+f"(d[1]), "+f"(d[2]), "+f"(d[3]), "+f"(d[4]), "+f"(d[5]), "+f"(d[6]), "+f"(d[7]), "+f"(d[8]), "+f"(d[9]), "+f"(d[10]), "+f"(d[11]), "+f"(d[12]), "+f"(d[13]), "+f"(d[14]), "+f"(d[15]), "+f"(d[16]), "+f"(d[17]), "+f"(d[18]), "+f"(d[19]), "+f"(d[20]), "+f"(d[21]), "+f"(d[22]), "+f"(d[23]), "+f"(d[24]), "+f"(d[25]), "+f"(d[26]), "+f"(d[27]), "+f"(d[28]), "+f"(d[29]), "+f"(d[30]), "+f"(d[31]), "+f"(d[32]), "+f"(d[33]), "+f"(d[34]), "+f"(d[35]), "+f"(d[36]), "+f"(d[37]), "+f"(d[38]), "+f"(d[39])
    : "r"(a[0]), "r"(a[1]), "r"(a[2]), "r"(a[3]), "l"(db), "r"(sc), "n"(TB));
}

namespace {
constexpr int S_ = 2048, D_ = 448, F_ = 1792;
constexpr int NSLOT = 8, SLOT = 22528;
constexpr int OFF_X = 7 * 16384;
constexpr int OFF_WQ = 8 * 16384;
constexpr int OFF_Q = NSLOT * SLOT;
constexpr int OFF_K = OFF_Q + 16384;
constexpr int OFF_BAR = 14 * 16384;
constexpr int OFF_LN = OFF_BAR + 512;
constexpr int OFF_OBS = OFF_BAR + 640;
constexpr int SMEM_BYTES = OFF_OBS + 1024;
#define PACE1 540
#define PACE2 600
#define J1 6
#define J2 14
#define TS 3120
#define UP 170
#define WQA 4
#define UTAG 1
#define OPD 0
#define UCH 7
#define UC2 7
#define SOBS 0
#define FREQ 0
#define KOBS 0
#define LANDOBS 0
#define OBS(c, i) do {} while (0)
#define OBSG(c, i, j) do {} while (0)
constexpr int NTHREADS = 384;
constexpr float LOG2E = 1.4426950408889634f;
constexpr uint32_t SC_HI = 0x3e423e42u, SC_LO = 0xb9f7b9f7u;
constexpr int BT = 14336;

constexpr int HU_T = 67;
constexpr int O_OFF = 4 * HU_T * BT;
constexpr int HALO_OFF = O_OFF + 32 * 7 * 8192;
constexpr int CNT_OFF = HALO_OFF + 128 * 3584;
constexpr int SCR_BYTES = CNT_OFF + 160 * 128;
constexpr int C_U = 0, C_O = 8, C_H = 24, C_WO = 25, C_TK = 26, C_HALO = 32;
__device__ __align__(1024) unsigned char g_scr[SCR_BYTES];

__device__ __forceinline__ uint32_t smem_u32(const void* p) { return (uint32_t)__cvta_generic_to_shared(p); }
__device__ __forceinline__ void mbar_init(uint32_t bar, uint32_t cnt) { asm volatile("mbarrier.init.shared::cta.b64 [%0], %1;" :: "r"(bar), "r"(cnt)); }
__device__ __forceinline__ void mbar_expect_tx(uint32_t bar, uint32_t bytes) { asm volatile("mbarrier.arrive.expect_tx.shared::cta.b64 _, [%0], %1;" :: "r"(bar), "r"(bytes) : "memory"); }
__device__ __forceinline__ void mbar_arrive_if(uint32_t c, uint32_t bar) { asm volatile("{\n.reg .pred q;\nsetp.ne.u32 q, %1, 0;\n@q mbarrier.arrive.shared::cta.b64 _, [%0];\n}" :: "r"(bar), "r"(c) : "memory"); }
__device__ __forceinline__ void mbar_arrive(uint32_t bar) { asm volatile("mbarrier.arrive.shared::cta.b64 _, [%0];" :: "r"(bar) : "memory"); }
__device__ __forceinline__ void mbar_wait(uint32_t bar, uint32_t parity) {
  asm volatile("{\n.reg .pred p;\n.reg .u32 n;\nmov.u32 n, 0;\nLAB_WAIT:\n"
               "mbarrier.try_wait.parity.shared::cta.b64 p, [%0], %1;\n@p bra DONE;\n"
               "add.u32 n, n, 1;\nsetp.lt.u32 p, n, 400000;\n@p bra LAB_WAIT;\ntrap;\nDONE:\n}" :: "r"(bar), "r"(parity) : "memory");
}
__device__ __forceinline__ uint32_t mbar_try(uint32_t bar, uint32_t parity) {
  uint32_t ok;
  asm volatile("{\n.reg .pred p;\nmbarrier.test_wait.parity.shared::cta.b64 p, [%1], %2;\nselp.u32 %0, 1, 0, p;\n}" : "=r"(ok) : "r"(bar), "r"(parity) : "memory");
  return ok;
}
__device__ __forceinline__ void tma3d(uint32_t dst, const CUtensorMap* m, int c0, int c1, int c2, uint32_t bar) {
  asm volatile("cp.async.bulk.tensor.3d.shared::cluster.global.mbarrier::complete_tx::bytes [%0], [%1, {%3, %4, %5}], [%2];"
               :: "r"(dst), "l"(m), "r"(bar), "r"(c0), "r"(c1), "r"(c2) : "memory");
}
__device__ __forceinline__ void bulk_g2s(uint32_t dst, const void* src, uint32_t bytes, uint32_t bar) {
  asm volatile("cp.async.bulk.shared::cluster.global.mbarrier::complete_tx::bytes [%0], [%1], %2, [%3];" :: "r"(dst), "l"(src), "r"(bytes), "r"(bar) : "memory");
}
__device__ __forceinline__ void wg_fence() { asm volatile("wgmma.fence.sync.aligned;" ::: "memory"); }
__device__ __forceinline__ void wg_commit() { asm volatile("wgmma.commit_group.sync.aligned;" ::: "memory"); }
template <int N> __device__ __forceinline__ void wg_wait() { asm volatile("wgmma.wait_group.sync.aligned %0;" :: "n"(N) : "memory"); }
__device__ __forceinline__ void smem_fence() { asm volatile("fence.proxy.async.shared::cta;" ::: "memory"); }
__device__ __forceinline__ void stg128(void* p, uint32_t a, uint32_t b, uint32_t c, uint32_t d) { asm volatile("st.global.v4.u32 [%0], {%1,%2,%3,%4};" :: "l"(p), "r"(a), "r"(b), "r"(c), "r"(d) : "memory"); }
__device__ __forceinline__ void stg32(void* p, uint32_t v) { asm volatile("st.global.u32 [%0], %1;" :: "l"(p), "r"(v) : "memory"); }
__device__ __forceinline__ uint4 ldg128(const void* p) { uint4 v; asm volatile("ld.global.nc.L1::no_allocate.v4.u32 {%0,%1,%2,%3}, [%4];" : "=r"(v.x), "=r"(v.y), "=r"(v.z), "=r"(v.w) : "l"(p)); return v; }
__device__ __forceinline__ void publish(unsigned char* scr, int i) {
  asm volatile("{\n.reg .pred q;\nelect.sync _|q, 0xffffffff;\n@q red.relaxed.gpu.global.inc.u32 [%0], 0xffffffff;\n}" :: "l"(scr + CNT_OFF + i * 128) : "memory");
}
__device__ __forceinline__ uint32_t probe(const unsigned char* p) { uint32_t v; asm volatile("ld.relaxed.gpu.global.u32 %0, [%1];" : "=r"(v) : "l"(p) : "memory"); return v; }
__device__ __forceinline__ void settle(uint32_t v) {
  asm volatile("{\n.reg .pred q;\nsetp.eq.u32 q, %0, 0x7fc1dead;\n@q st.volatile.shared.u32 [%1], %0;\n}" :: "r"(v), "r"(1024 + OFF_BAR + 376) : "memory");
  __syncwarp();
}
__device__ __forceinline__ uint32_t spin_ge(unsigned char* scr, int i, unsigned target) {
  uint32_t v;
  asm volatile("{\n.reg .pred p;\n.reg .u32 n;\nmov.u32 n, 0;\nLAB_SPIN:\n"
               "ld.relaxed.gpu.global.u32 %0, [%1];\nsetp.ge.u32 p, %0, %2;\nvote.sync.all.pred p, p, 0xffffffff;\n@p bra DONE;\n"
               "add.u32 n, n, 1;\nsetp.lt.u32 p, n, 4000000;\n@p bra LAB_SPIN;\ntrap;\nDONE:\n}" : "=&r"(v) : "l"(scr + CNT_OFF + i * 128), "r"(target) : "memory");
  return v;
}
__device__ __forceinline__ int lane_id() { int l; asm volatile("mov.u32 %0, %%laneid;" : "=r"(l)); return l; }
__device__ __forceinline__ uint32_t pin(uint32_t v) { return __shfl_xor_sync(0xffffffffu, v, blockIdx.y); }
__device__ __forceinline__ unsigned char* pin(unsigned char* p) { return (unsigned char*)(((uint64_t)pin((uint32_t)((uint64_t)p >> 32)) << 32) | pin((uint32_t)(uint64_t)p)); }
__device__ __forceinline__ uint32_t gtime() { uint32_t g; asm volatile("mov.u32 %0, %%globaltimer_lo;" : "=r"(g)); return g; }
__device__ __forceinline__ bool elect() {
  uint32_t r; asm volatile("{\n.reg .pred p;\nelect.sync _|p, 0xffffffff;\nselp.u32 %0, 1, 0, p;\n}" : "=r"(r)); return r != 0;
}
__device__ __forceinline__ uint4 lds128(uint32_t a) { uint4 v; asm volatile("ld.shared.v4.u32 {%0,%1,%2,%3}, [%4];" : "=r"(v.x), "=r"(v.y), "=r"(v.z), "=r"(v.w) : "r"(a) : "memory"); return v; }
__device__ __forceinline__ uint32_t lds32(uint32_t a) { uint32_t v; asm volatile("ld.shared.u32 %0, [%1];" : "=r"(v) : "r"(a) : "memory"); return v; }
__device__ __forceinline__ uint2 lds64(uint32_t a) { uint2 v; asm volatile("ld.shared.v2.u32 {%0,%1}, [%2];" : "=r"(v.x), "=r"(v.y) : "r"(a) : "memory"); return v; }
__device__ __forceinline__ void sts128(uint32_t p, uint32_t a, uint32_t b, uint32_t c, uint32_t d) { asm volatile("st.shared.v4.u32 [%0], {%1,%2,%3,%4};" :: "r"(p), "r"(a), "r"(b), "r"(c), "r"(d) : "memory"); }
__device__ __forceinline__ void sts32(uint32_t a, float v) { asm volatile("st.shared.f32 [%0], %1;" :: "r"(a), "f"(v) : "memory"); }
__device__ __forceinline__ void named_sync(int id, int n) { asm volatile("bar.sync %0, %1;" :: "r"(id), "r"(n) : "memory"); }
__device__ __forceinline__ void named_arrive(int id, int n) { asm volatile("bar.arrive %0, %1;" :: "r"(id), "r"(n) : "memory"); }
__device__ __forceinline__ void named_arrive_if(uint32_t c, int id, int n) { asm volatile("{\n.reg .pred q;\nsetp.ne.u32 q, %2, 0;\n@q bar.arrive %0, %1;\n}" :: "r"(id), "r"(n), "r"(c) : "memory"); }
__device__ __forceinline__ uint64_t mkdesc(uint32_t hi, uint32_t lo) { return ((uint64_t)hi << 32) | lo; }
constexpr uint32_t HI_SW128 = 0x40000040u;
__device__ __forceinline__ uint32_t pack2(float lo, float hi) { uint32_t r; asm("cvt.rn.bf16x2.f32 %0, %1, %2;" : "=r"(r) : "f"(hi), "f"(lo)); return r; }
__device__ __forceinline__ float bf_lo(uint32_t v) { return __uint_as_float(v << 16); }
__device__ __forceinline__ float bf_hi(uint32_t v) { return __uint_as_float(v & 0xffff0000u); }
__device__ __forceinline__ float rbf(float x) { return bf_lo(pack2(x, 0.f)); }
__device__ __forceinline__ uint32_t hsub2(uint32_t a, uint32_t b) { uint32_t r; asm("sub.rn.bf16x2 %0, %1, %2;" : "=r"(r) : "r"(a), "r"(b)); return r; }
__device__ __forceinline__ uint32_t hadd2(uint32_t a, uint32_t b) { uint32_t r; asm("add.rn.bf16x2 %0, %1, %2;" : "=r"(r) : "r"(a), "r"(b)); return r; }
__device__ __forceinline__ uint32_t place(uint32_t v, uint32_t sel) { uint32_t r; asm volatile("prmt.b32 %0, %1, 0, %2;" : "=r"(r) : "r"(v), "r"(sel)); return r; }
__device__ __forceinline__ uint32_t hmax2(uint32_t a, uint32_t b) { uint32_t r; asm("max.bf16x2 %0, %1, %2;" : "=r"(r) : "r"(a), "r"(b)); return r; }
__device__ __forceinline__ uint32_t hmul2(uint32_t a, uint32_t b) { uint32_t r; asm("mul.rn.bf16x2 %0, %1, %2;" : "=r"(r) : "r"(a), "r"(b)); return r; }
__device__ __forceinline__ uint32_t hfma2(uint32_t a, uint32_t b, uint32_t c) { uint32_t r; asm("fma.rn.bf16x2 %0, %1, %2, %3;" : "=r"(r) : "r"(a), "r"(b), "r"(c)); return r; }
__device__ __forceinline__ float tanh_fast(float x) { float r; asm("tanh.approx.f32 %0, %1;" : "=f"(r) : "f"(x)); return r; }
__device__ __forceinline__ float rcp_fast(float x) { float r; asm("rcp.approx.ftz.f32 %0, %1;" : "=f"(r) : "f"(x)); return r; }
__device__ __forceinline__ float ex2_fast(float x) { float r; asm("ex2.approx.ftz.f32 %0, %1;" : "=f"(r) : "f"(x)); return r; }
__device__ __forceinline__ void mma16816(float (&c)[4], uint32_t a0, uint32_t a1, uint32_t a2, uint32_t a3, uint32_t b0, uint32_t b1) {
  asm volatile("mma.sync.aligned.m16n8k16.row.col.f32.bf16.bf16.f32 {%0,%1,%2,%3}, {%4,%5,%6,%7}, {%8,%9}, {%0,%1,%2,%3};"
               : "+f"(c[0]), "+f"(c[1]), "+f"(c[2]), "+f"(c[3]) : "r"(a0), "r"(a1), "r"(a2), "r"(a3), "r"(b0), "r"(b1));
}
__device__ __forceinline__ void ldsm4(uint32_t (&r)[4], uint32_t addr) {
  asm volatile("ldmatrix.sync.aligned.m8n8.x4.shared.b16 {%0,%1,%2,%3}, [%4];" : "=r"(r[0]), "=r"(r[1]), "=r"(r[2]), "=r"(r[3]) : "r"(addr) : "memory");
}
__device__ __forceinline__ void stsm4(uint32_t addr, uint32_t a, uint32_t b, uint32_t c, uint32_t d) {
  asm volatile("stmatrix.sync.aligned.m8n8.x4.shared.b16 [%0], {%1,%2,%3,%4};" :: "r"(addr), "r"(a), "r"(b), "r"(c), "r"(d) : "memory");
}

__device__ __forceinline__ float ln_rstd(float var, float eps = 1e-5f) {
  float sd;
  asm("sqrt.approx.ftz.f32 %0, %1;" : "=f"(sd) : "f"(rbf(rbf(var) + eps)));
  return rcp_fast(rbf(sd));
}
__device__ __forceinline__ float ln_var(float mean, float sq) { return fmaxf(fmaf(-mean, mean, sq * (1.0f / D_)), 0.f); }
struct LnC { uint32_t m, rh, rl; };
__device__ __forceinline__ LnC ln_consts(float sum, float sq, float eps) {
  const float mean = sum * (1.0f / D_), r = ln_rstd(ln_var(mean, sq), eps), rh = rbf(r);
  LnC c; c.m = pack2(mean, mean); c.rh = pack2(rh, rh); c.rl = pack2(r - rh, r - rh);
  return c;
}
__device__ __forceinline__ uint32_t ln_apply(uint32_t x, const LnC& c) {
  uint32_t d = hsub2(x, c.m);
  return hfma2(d, c.rh, hmul2(d, c.rl));
}

__device__ __forceinline__ void fence_code(int id) {
  asm volatile("{\n.reg .pred q;\nLAB_F:\nsetp.eq.u32 q, %0, %1;\n@q st.volatile.shared.u32 [%2], %2;\n@q bra LAB_F;\n}" :: "r"(blockIdx.x), "r"(0x70000000 + id), "r"(0) : "memory");
}
template <int N> __device__ __forceinline__ void fresh(float (&a)[N]) {
#pragma unroll
  for (int i = 0; i < N; i++) asm volatile("" : "=f"(a[i]));
}
constexpr int B_EMPTY = 64, B_U1 = 128, B_U2 = 136, B_WQ = 144, B_WQ2 = 152, B_HIN = 160, B_HALO = 168, B_GATE = 176, B_ATT = 192, B_RES = 200, B_WO = 208, B_O = 216;
constexpr int B_OL = 224, B_KV = 296, B_TAG = 360, B_T0 = 368, B_X = 384;

template <int TA>
__device__ __forceinline__ void gemm_issue(float (&acc)[56], uint32_t lo, int sc) {
  wg_fence();
#pragma unroll
  for (int k = 0; k < 4; k++)
    wgmma_n112<TA, 1>(acc, mkdesc(TA ? HI_SW128 : 8, lo + (TA ? 512u << 16 : 64u << 16) + k * 128), mkdesc(8, lo + (112u << 16) + 512 + k * 224), sc | k);
  wg_commit();
}
template <int TA>
__device__ __forceinline__ void gemm_loop(float (&acc)[56], uint32_t base, int it, int end, bool rel, int oi, uint32_t ok = 0, int gate_it = -1, uint32_t gate = 0) {
#pragma unroll 1
  for (; it < end;) {
    if (__builtin_expect(!ok, 0)) mbar_wait(base + OFF_BAR + (it & 7) * 8, (it >> 3) & 1);
    gemm_issue<TA>(acc, (base >> 4) + (it & 7) * (SLOT >> 4), 1);
    OBS(SOBS && rel, oi + it);
    it++;
    ok = mbar_try(base + OFF_BAR + (it & 7) * 8, (it >> 3) & 1);
    wg_wait<1>();
    if (rel || it == gate_it) mbar_arrive(rel ? base + OFF_BAR + B_EMPTY + ((it - 2) & 7) * 8 : gate);
  }
}
template <int S1, int S2>
__device__ __forceinline__ void produce_box(uint32_t base, int it, int end, const CUtensorMap* mp, int c0, int c1) {
#pragma unroll 1
  for (int c2 = 0; it < end; it++, c1 += S1, c2 += S2) {
    const uint32_t fb = base + OFF_BAR + (it & 7) * 8;
    mbar_wait(fb + B_EMPTY, (it >> 3) & 1);
    if (elect()) { mbar_expect_tx(fb, 8192); tma3d(base + (it & 7) * SLOT, mp, c0, c1, c2, fb); }
  }
}
template <int PER, int LAND = 0>
__device__ __forceinline__ void produce_lin(uint32_t base, int it, int end, const unsigned char* src, uint32_t bytes, uint32_t tn = 0) {
#pragma unroll 1
  for (; it < end; it++) {
    const uint32_t fb = base + OFF_BAR + (it & 7) * 8;
    mbar_wait(fb + B_EMPTY, (it >> 3) & 1);
    if (PER) { while ((int)(clock() - tn) < 0); tn += PER; }
    if (elect()) { mbar_expect_tx(fb + LAND, bytes); bulk_g2s(base + (it & 7) * SLOT + (bytes & 2048) * 4, src, bytes, fb + LAND); }
    src += bytes;
  }
}

__device__ __forceinline__ void retile_wo(const unsigned char* wo, unsigned char* scr, int u, int lane) {
  const int r8 = lane & 7, mi = lane >> 3;
  const unsigned char* src = wo + ((u >> 1) * 8 + r8) * 896 + ((u & 1) * 28 + mi) * 16;
  unsigned char* dst = scr + ((u & 1) * 2 * HU_T + 60 + (u >> 4)) * BT + ((u >> 1) & 7) * 1792 + mi * 128 + r8 * 16;
  uint4 v[7];
#pragma unroll
  for (int i = 0; i < 7; i++) v[i] = ldg128(src + i * 64);
#pragma unroll
  for (int i = 0; i < 7; i++) stg128(dst + i * 512 + ((i * 4 + mi) / 14) * (HU_T * BT - 1792), v[i].x, v[i].y, v[i].z, v[i].w);
}

struct Params {
  const unsigned char *wqkv, *wo, *w1, *b1, *w2, *b2;
  unsigned char *out, *scr;
};

__global__ void __launch_bounds__(NTHREADS, 1)
fused_kernel(const __grid_constant__ CUtensorMap m_x, const __grid_constant__ CUtensorMap m_wkv, const __grid_constant__ CUtensorMap m_wq,
             const __grid_constant__ CUtensorMap m_w1, const __grid_constant__ CUtensorMap m_w2, const __grid_constant__ CUtensorMap m_res, const Params p) {
  extern __shared__ __align__(1024) unsigned char smem_raw[];
  constexpr uint32_t base = 1024, bars = base + OFF_BAR;
  const int tid = threadIdx.x, lane = tid & 31, b = blockIdx.x;
  const int rb = (b >> 2) & 15, hp = ((b >> 6) << 2) | (b & 3);
  const int wcol = hp * 56 - (hp & 1) * 8;
  auto load_wq = [&](int s0, int s1, uint32_t bar) {
    mbar_expect_tx(bar, (s1 - s0) * 8192);
#pragma unroll 1
    for (int s = s0; s < s1; s++) tma3d(base + OFF_WQ + s * 8192, &m_wq, wcol, s * 64, 0, bar);
  };
  auto load_kv = [&](int s) { mbar_expect_tx(bars + B_KV + s * 8, 16384); tma3d(base + s * 16384, &m_wkv, wcol, s * 64, 1, bars + B_KV + s * 8); };
  if (tid < 32) {
    if (elect()) {
#pragma unroll
      for (int i = 0; i < 7; i++) mbar_init(bars + B_X + i * 8, 1);
      asm volatile("fence.mbarrier_init.release.cluster;" ::: "memory");
#pragma unroll
      for (int i = 0; i < 7; i++) { mbar_expect_tx(bars + B_X + i * 8, 8192); tma3d(base + OFF_X + i * 16384 + 8192, &m_x, i * 64, rb * 128 + 64, 0, bars + B_X + i * 8); }
#pragma unroll
      for (int i = 0; i < 7; i++) { mbar_init(bars + B_KV + i * 8, 1); mbar_init(bars + B_X + 64 + i * 8, 1); }
      asm volatile("fence.mbarrier_init.release.cluster;" ::: "memory");
      load_kv(0);
#pragma unroll
      for (int i = 0; i < 7; i++) { mbar_expect_tx(bars + B_X + 64 + i * 8, 8192); tma3d(base + OFF_X + i * 16384, &m_x, i * 64, rb * 128, 0, bars + B_X + 64 + i * 8); }
      load_kv(1);
    }
  }
  const int warp = __shfl_sync(0xffffffffu, tid >> 5, 0);
  if (warp == 1) {
    if (elect()) {
#pragma unroll
      for (int i = 0; i < 36; i++) mbar_init(bars + i * 8, i < 16 ? 2 : 1);
      asm volatile("fence.mbarrier_init.release.cluster;" ::: "memory");
      if (smem_u32(smem_raw) != base) asm volatile("trap;");
    }
  }
  const int dt = b & 3, mt = b >> 2;
  const bool g1 = (b & 15) < 14;
  const int a1 = b - 2 * (b >> 4), ft = a1 >> 2, d1 = a1 & 3;
  const int g = lane >> 2, t = lane & 3, r8 = lane & 7, mi = lane >> 3;
  OBSG(FREQ && tid == 160, 128, 160);
  __syncthreads();
  if (warp >= 8) {
    asm volatile("setmaxnreg.dec.sync.aligned.u32 40;");
    const int pw = warp - 8;
    unsigned char* scr = p.scr;
    if (pw == 2) {
      mbar_wait(bars + B_X + 48, 0);
      if (b < 112 && lane < 28) asm volatile("prefetch.global.L2 [%0];" :: "l"(p.wqkv + (b * 4 + lane / 7) * 2688 + (lane % 7) * 128) : "memory");
      if (b < 98) asm volatile("prefetch.global.L2 [%0];" :: "l"(p.wo + b * 4096 + lane * 128) : "memory");
      if (lane == 31) asm volatile("prefetch.tensormap [%0];" :: "l"(&m_wq) : "memory");
      __syncwarp();
    }
    if (pw == 3) {
      mbar_wait(bars + B_X, 0);
      if (elect()) {
#pragma unroll 1
        for (int i = 2; i < 7; i++) load_kv(i);
      }
      __syncwarp();
    }
    {
      const int c0 = pw * 14 + (mi >> 1);
      unsigned char* dst = scr + (pw * HU_T + rb * 2 + (hp >> 2)) * BT + ((hp & 3) * 2 + (mi & 1)) * 1792 + (mi >> 1) * 128 + r8 * 16;
      const uint32_t xs = base + OFF_X + (hp * 16 + (lane & 15)) * 128;
      uint4 H[7];
      named_sync(9, 160);
#pragma unroll
      for (int i = 0; i < 7; i++) H[i] = lds128(xs + ((c0 + 2 * i) >> 3) * 16384 + ((((c0 + 2 * i) & 7) ^ r8) << 4));
      asm volatile("" :: "r"(H[6].w), "r"(H[0].x) : "memory");
      if (pw != 3) named_arrive(8, 384);
      else {
        named_sync(8, 384);
        if (elect()) {
          if (g1) asm volatile("red.relaxed.gpu.global.max.u32 [%0], %1;" :: "l"(scr + CNT_OFF + C_H * 128 + 8), "r"(gtime()) : "memory");
          load_wq(0, WQA, bars + B_WQ);
        }
        __syncwarp();
      }
      const uint2 st = lds64(base + OFF_LN + (lane & 15) * 8);
      const float sum = __uint_as_float(st.x), mean = sum * (1.0f / D_), var = ln_var(mean, __uint_as_float(st.y));
      const float m = rbf(mean), r = ln_rstd(var), r2 = ln_rstd(var * r * r);
      const float nc = fmaf(m, (float)D_, -sum) * (1.0f / D_) * (r * r2);
      const uint32_t m2 = pack2(m, m), r2x = pack2(r * r2, r * r2), nc2 = pack2(nc, nc);
      auto f = [&](uint32_t v) { return hfma2(hsub2(v, m2), r2x, nc2); };
#pragma unroll
      for (int i = 0; i < 7; i++) stg128(dst + i * 256, f(H[i].x), f(H[i].y), f(H[i].z), f(H[i].w));
      if (pw != 1) named_arrive(4, 128);
    }
    const int lane = lane_id();
    if (pw == 0) {
      if (elect()) {
        asm volatile("prefetch.tensormap [%0];" :: "l"(&m_w1) : "memory");
        asm volatile("prefetch.tensormap [%0];" :: "l"(&m_w2) : "memory");
        asm volatile("prefetch.tensormap [%0];" :: "l"(&m_res) : "memory");
      }
      __syncwarp();
      const uint32_t e = probe(scr + CNT_OFF + C_H * 128 + 4) + 1;
      sts32(bars + B_TAG, __uint_as_float((e & 0x3fffu) | ((e << 2) & 0x3fff0000u)));
      named_arrive(1, 96);
      if (g1) produce_box<64, 0>(base, 0, 32, &m_w1, ft * 64, 0);
      mbar_wait(bars + B_ATT, 0);
      if (elect()) { mbar_expect_tx(bars + B_RES, BT); tma3d(base + OFF_Q, &m_res, dt * 112, mt * 64, 0, bars + B_RES); }
      mbar_wait(bars + B_WO, 0);
      produce_lin<0>(base, 0, 7, scr + (dt * HU_T + 60) * BT, BT);
#pragma unroll 1
      for (int h = 0; h < 2; h++) produce_box<0, 8>(base, 7 + h * 14, 21 + h * 14, &m_w2, mt * 64, h * 8);
    } else if (pw == 1) {
      named_sync(4, 128);
      const unsigned char* hl = scr + (rb * 2 + (hp >> 2)) * BT + (hp & 3) * 3584 + min(lane, 27) * 128;
      settle(probe(hl) ^ probe(hl + HU_T * BT) ^ probe(hl + 2 * HU_T * BT) ^ probe(hl + 3 * HU_T * BT));
      publish(scr, C_H);
      OBS(lane == 0, 4);
      if (elect()) load_wq(WQA, 7, bars + B_WQ2);
      __syncwarp();
      if (g1) {
        __nanosleep(200);
        const uint32_t v = spin_ge(scr + (lane & 1) * 8, C_H, lane & 1 ? 0 : 128);
        if (lane == 1) sts32(bars + B_T0, __uint_as_float(v + TS));
        __syncwarp();
        OBS(lane == 0, 16);
        produce_lin<0>(base, 0, 32, scr + d1 * HU_T * BT, BT);
      }
      mbar_wait(bars + B_O, 0);
      produce_lin<0, B_OL>(base, 0, 7, scr + O_OFF + mt * 57344, 8192);
      constexpr int UL = UTAG ? B_OL : 0;
      const unsigned char* us = scr + (dt * HU_T + 32) * BT;
      mbar_wait(bars + B_EMPTY + 56, 0);
      if (elect()) mbar_expect_tx(bars + UL + 56, BT);
      __syncwarp();
      spin_ge(scr, C_U + dt, 28);
      if (elect()) bulk_g2s(base + 7 * SLOT + 8192, us, BT, bars + UL + 56);
      if (lane == 0) mbar_arrive(bars + B_U1);
      const uint32_t tu = clock();
      OBS(lane == 0, 18);
      produce_lin<UP, UL>(base, 8, 15, us + BT, BT, tu + UP);
      produce_lin<0, UL>(base, 15, 21, us + 8 * BT, BT);
      mbar_wait(bars + B_U2, 0);
      produce_lin<0, (UTAG == 2 ? UL : 0)>(base, 21, 35, us + 14 * BT, BT);
      unsigned tk = 0;
      if (lane == 0) tk = atomicAdd((unsigned*)(scr + CNT_OFF + C_TK * 128), 1u);
      if (__shfl_sync(0xffffffffu, tk, 0) == 127) {
#pragma unroll 1
        for (int i = lane; i < 160; i += 32) *(unsigned*)(scr + CNT_OFF + i * 128) = 0;
        *(unsigned*)(scr + CNT_OFF + C_H * 128 + 8) = 0;
        publish(scr + 4, C_H);
      }
    } else if (pw == 2) {
      uint32_t tn = clock();
      const unsigned char* src = p.w1 + b * 4096 + lane * 128;
#pragma unroll 1
      for (int i = 0; i < 28 + FREQ * 2; i++) {
        while ((int)(clock() - tn) < 0) __nanosleep(20);
        if (i == 14 || i == 21) src = p.w2 + ((b >> 3) * 16 + (b & 7) + (i & 1) * 8) * 4096 + lane * 128;
        if (i < 28) asm volatile("prefetch.global.L2 [%0];" :: "l"(src) : "memory");
        OBSG(FREQ && lane == 0, 129 + i, 161 + i);
        src += (i < 14 ? 128 : 256) * 4096;
        tn += i < 14 ? PACE1 : PACE2;
        if (UTAG && i == 27) {
          mbar_wait(bars + B_U1, 0);
          spin_ge(scr, C_U + 4 + dt, 28);
          OBS(lane == 0, 11);
          if (lane == 0) mbar_arrive(bars + B_U2);
          __syncwarp();
        }
      }
    } else {
      if (b < 112) retile_wo(p.wo, scr, b, lane_id());
      const int lane = lane_id();
      unsigned char* hg = scr + HALO_OFF + (rb * 8 + hp) * 3584;
      named_sync(1, 96);
      const uint32_t tag = lds64(bars + B_TAG).x;
      if (rb < 15) {
#pragma unroll
        for (int q = 0; q < 7; q += 4) {
          uint4 v[4];
#pragma unroll
          for (int i = q; i < q + 4 && i < 7; i++) v[i - q] = lds128(base + OFF_K + 8 * 3584 + i * 512 + lane * 16 + (i * 32 + lane < 112 && !(lane & 7) ? 1792 : 0));
#pragma unroll
          for (int i = q; i < q + 4 && i < 7; i++) stg128(hg + i * 512 + lane * 16, (lane & 7) == (i * 32 + lane < 112) ? tag : v[i - q].x, v[i - q].y, v[i - q].z, v[i - q].w);
        }
        publish(scr, C_HALO + rb * 8 + hp);
      }
      OBS(lane == 0, 29);
      if (rb > 0) {
        spin_ge(scr, C_HALO + (rb - 1) * 8 + hp, 1);
        const uint32_t la = base + OFF_K + min(lane, 27) * 128;
#pragma unroll 1
        for (int n = 0;; n++) {
          if (elect()) { mbar_expect_tx(bars + B_HIN, 3584); bulk_g2s(base + OFF_K, hg - 8 * 3584, 3584, bars + B_HIN); }
          __syncwarp();
          mbar_wait(bars + B_HIN, n & 1);
          if (__all_sync(0xffffffffu, lds64(la + (lane < 14 ? 16 : 0)).x == tag)) break;
          if (n > 1000000) asm volatile("trap;");
        }
        if (lane < 14) { const uint4 v = lds128(la); sts128(la + 1792, v.x, v.y, v.z, v.w); }
      } else {
#pragma unroll
        for (int i = 0; i < 7; i++) sts128(base + OFF_K + i * 512 + lane * 16, 0, 0, 0, 0);
      }
      OBS(lane == 0, 12);
      smem_fence();
      __syncwarp();
      if (lane == 0) mbar_arrive(bars + B_HALO);
      __syncwarp();
      if (b < 112) {
        settle(probe(scr + (((b & 1) * 2 + (lane >> 4)) * HU_T + 60 + (b >> 4)) * BT + ((b >> 1) & 7) * 1792 + min(lane & 15, 13) * 128));
        publish(scr, C_WO);
      }
      mbar_wait(bars + (g1 ? B_GATE + 8 : B_ATT), 0);
      spin_ge(scr, C_WO, 112);
      if (lane == 0) mbar_arrive(bars + B_WO);
      mbar_wait(bars + B_ATT, 0);
      spin_ge(scr, C_O + (mt >> 1), 8);
      OBS(lane == 0, 17);
      if (lane == 0) mbar_arrive(bars + B_O);
      uint32_t ph = 0;
      auto check = [&](int it, int end, const unsigned char* src, uint32_t bytes, uint32_t a0, uint32_t a1) {
#pragma unroll 1
        for (int n = 0; it < end;) {
          const uint32_t s = it & 7, lb = bars + B_OL + s * 8, a = base + s * SLOT;
          mbar_wait(lb, (ph >> s) & 1);
          ph ^= 1 << s;
          uint32_t bad = (lds32(a + a0) ^ tag) | (lds32(a + a1) ^ tag);
          if (bytes == BT) bad |= (lds32(a + a0 + 512) ^ tag) | (lds32(a + a0 + 1024) ^ tag);
          if (__builtin_expect(__all_sync(0xffffffffu, !(bad & 1)), 1)) { mbar_arrive_if(lane == 0, bars + s * 8); it++; src += bytes; continue; }
          if (++n > 1000000) asm volatile("trap;");
          if (elect()) { mbar_expect_tx(lb, bytes); bulk_g2s(a + (bytes & 2048) * 4, src, bytes, lb); }
          __syncwarp();
        }
      };
      check(0, 7, scr + O_OFF + mt * 57344, 8192, lane * 132, lane * 132 + 4096);
      if (UTAG) {
        const uint32_t a = 8192 + (lane & 7) * 1792 + lane * 4;
        check(7, UTAG == 2 ? 35 : 21, scr + (dt * HU_T + 32) * BT, BT, a + (lane >> 3) * 128, a + (12 + ((lane >> 3) & 1)) * 128);
      } else {
        mbar_wait(bars + B_U1, 0);
        spin_ge(scr, C_U + 4 + dt, 28);
        OBS(lane == 0, 11);
        if (lane == 0) mbar_arrive(bars + B_U2);
      }
    }
  } else {
    asm volatile("setmaxnreg.inc.sync.aligned.u32 232;");
    const int wg = warp >> 2, w4 = warp & 3, th = wg ^ 1;
    const bool rel = (tid & 127) < 2;
    unsigned char* scr = p.scr;
    uint32_t X[28][4];
    float aq[28];
    const uint32_t dlo = (base >> 4) + (512u << 16) + (hp & 1), dlq = dlo + (OFF_WQ >> 4);
    {
      uint32_t xa[4];
#pragma unroll
      for (int k = 0; k < 4; k++) xa[k] = base + OFF_X + (th * 64 + w4 * 16 + (mi >> 1) * 8 + r8) * 128 + (((2 * k + (mi & 1)) ^ r8) << 4);
      float c0[2][4] = {}, c1[2][4] = {};
      uint32_t one[8];
#pragma unroll
      for (int j = 0; j < 8; j++) asm volatile("{\n.reg .u32 y;\nmov.u32 y, %%tid.y;\nmad.lo.u32 %0, y, %1, 0x3f803f80;\n}" : "=r"(one[j]) : "r"(lane + j));
      asm volatile("" : "+l"(scr));
      uint32_t ok = 0;
      const uint32_t bx = bars + B_X + wg * 64;
      {
#pragma unroll 1
        for (int n = 0; n < 64 && !ok; n++) { mma16816(c0[0], 0, 0, 0, 0, 0, 0); ok = mbar_try(bars + B_X, 0); }
        if (wg) ok = 0;
      }
#pragma unroll
      for (int i = 0; i < 8; i++) {
        if (i < 7) {
          if (!ok) mbar_wait(bx + i * 8, 0);
          OBS(tid == 64 && i == 0, 0); OBS(tid == 64 && i == 6, 15);
#pragma unroll
          for (int k = 0; k < 4; k++) ldsm4(X[i * 4 + k], xa[k] + i * 16384);
          if (i < 6) ok = mbar_try(bx + i * 8 + 8, 0);
        }
        if (i > 0) {
#pragma unroll
          for (int k = i * 4 - 4; k < i * 4; k++) {
            mma16816(c0[k & 1], X[k][0], one[(k & 1) * 4], X[k][1], one[(k & 1) * 4 + 1], X[k][0], X[k][1]);
            mma16816(c1[k & 1], X[k][2], one[(k & 1) * 4 + 2], X[k][3], one[(k & 1) * 4 + 3], X[k][2], X[k][3]);
          }
        }
      }
      float st[4];
#pragma unroll
      for (int j = 0; j < 2; j++) {
        st[j] = __shfl_sync(0xffffffffu, (g & 1) ? c0[0][2 * j + 1] + c0[1][2 * j + 1] : c0[0][2 * j] + c0[1][2 * j], (lane & 28) | (g >> 1));
        st[2 + j] = __shfl_sync(0xffffffffu, (g & 1) ? c1[0][2 * j + 1] + c1[1][2 * j + 1] : c1[0][2 * j] + c1[1][2 * j], (lane & 28) | (g >> 1));
      }
      named_arrive(8, 384);
      fence_code(20);
      named_arrive_if(wg, 0, 256);
      asm volatile("{\n.reg .pred q;\nsetp.ne.u32 q, %3, 0;\n@q st.shared.v2.f32 [%0], {%1,%2};\n@q bar.arrive 9, 160;\n}"
                   :: "r"(base + OFF_LN + ((t & 1) * 8 + g) * 8), "f"((t & 1) ? st[3] : st[1]), "f"((t & 1) ? st[2] : st[0]), "r"((uint32_t)((warp ^ 4) == hp)) : "memory");
      ok = mbar_try(bars + B_KV, 0);
      LnC l0, l1;
      float eps = 1e-5f;
#pragma unroll 1
      do {
        l0 = ln_consts(st[1], st[0], eps); l1 = ln_consts(st[3], st[2], eps);
#pragma unroll
        for (int k = 0; k < 16; k++) X[k >> 2][k & 3] = hsub2(X[k >> 2][k & 3], k & 2 ? l1.m : l0.m);
        eps += eps;
      } while ((l0.rl ^ l1.rl) == 4);
      OBS(tid == 32, 1);
      float ak[60], *av = ak + 32;
      auto norm = [&](int s) {
#pragma unroll
        for (int k = s * 4; k < s * 4 + 4; k++) {
          auto f = [&](uint32_t d, const LnC& l) { return s ? ln_apply(d, l) : hfma2(d, l.rh, hmul2(d, l.rl)); };
          const uint32_t y = f(X[k][1], l0);
          X[k][0] = f(X[k][0], l0); X[k][1] = f(X[k][2], l1); X[k][2] = y; X[k][3] = f(X[k][3], l1);
        }
      };
      const int pp_in = wg ? 6 : 0, pp_out = wg ? 0 : 6;
#pragma unroll
      for (int s = 0; s < 7; s++) {
        if (s != 1 || wg) norm(s);
        if (s == 0 && !wg) norm(1);
        if (__builtin_expect(!ok, 0)) { mbar_wait(bars + B_KV + s * 8, 0); if (s == 6) mbar_wait(bars + B_WQ, 0); }
        if (s == 0) fresh(ak);
        OBS(KOBS && (tid & 127) == 0, 40 + wg * 32 + s);
        if (wg ? s < 6 : s != 1) named_sync(pp_in, 256);
        OBS(KOBS && (tid & 127) == 32, 48 + wg * 32 + s);
        OBS(tid == 64 && s == 0, 2);
        wg_fence();
#pragma unroll
        for (int k = 0; k < 4; k++) {
          wgmma_rs_n120<1>(ak, X[s * 4 + k], mkdesc(HI_SW128, dlo + s * 1024 + k * 128), (s | k) != 0);
        }
        wg_commit();
        if (s == 6) {
          wg_wait<1>();
          if ((tid & 127) == 0) mbar_arrive(bars + B_EMPTY + 3 * 8);
          fresh(aq);
#pragma unroll
          for (int k = 0; k < 4; k++) {
            if (k == 2) named_arrive(pp_out, 256);
            wgmma_rs_n56<1>(aq, X[k], mkdesc(HI_SW128, dlq + k * 128), k);
          }
          wg_commit();
        }
        if (s < 6) named_arrive_if(wg ? s != 5 : s != 0, pp_out, 256);
        fence_code(s);
        OBS(KOBS && (tid & 127) == 64, 56 + wg * 32 + s);
        if (s < 6) ok = mbar_try(bars + B_KV + s * 8 + 8, 0);
        if (s == 5) ok &= mbar_try(bars + B_WQ, 0);
        OBS(tid == 64 && s == 5, 31);
        if (s > 0) wg_wait<1>();
        OBS(KOBS && (tid & 127) == 96, 64 + wg * 32 + s);
        if ((s == 2 || s == 3 || s == 5) && (tid & 127) == 0) mbar_arrive(bars + B_EMPTY + (s == 5 ? 2 : s - 2) * 8);
      }
      if ((tid & 127) == 0) mbar_arrive(bars + B_EMPTY + 4 * 8);
      OBS(tid == 32, 3);
      {
        const uint32_t kst = base + OFF_K + (2 + (warp ^ 4) * 2 + (mi & 1)) * 1792 + (mi >> 1) * 896 + r8 * 16;
#pragma unroll
        for (int n = 0; n < 7; n++)
          stsm4(kst + n * 128, pack2(ak[n * 4], ak[n * 4 + 1]), pack2(ak[n * 4 + 2], ak[n * 4 + 3]), pack2(av[n * 4], av[n * 4 + 1]), pack2(av[n * 4 + 2], av[n * 4 + 3]));
        named_arrive_if(warp == 3, 1, 96);
      }
      OBS(tid == 96, 32); OBS(tid == 224, 34);
      wg_wait<0>();
      if ((tid & 127) == 0) mbar_arrive(bars + B_EMPTY + 5 * 8);
      mbar_wait(bars + B_WQ2, 0);
    }
    const unsigned short *bp1 = (const unsigned short*)p.b1 + (g1 ? ft * 64 : 0) + w4 * 16 + g, *bp2 = (const unsigned short*)p.b2 + mt * 64 + w4 * 16 + g;
    const uint32_t braw[4] = {__ldg(bp1), __ldg(bp1 + 8), __ldg(bp2), __ldg(bp2 + 8)};
    auto q_rest = [&]() {
      wg_fence();
#pragma unroll
      for (int s = 1; s < 7; s++) {
#pragma unroll
        for (int k = s * 4; k < s * 4 + 4; k++) wgmma_rs_n56<1>(aq, X[k], mkdesc(HI_SW128, dlq + k * 128), 1);
        wg_commit();
        if (s == 5) { wg_wait<2>(); if ((tid & 127) == 0) mbar_arrive(bars + B_EMPTY + 6 * 8); }
      }
    };
    uint32_t Q[4][4];
    auto q_pack = [&]() {
#pragma unroll
      for (int n = 0; n < 14; n++) { const int m = n + 2 * (n > 7); Q[m >> 2][m & 3] = pack2(aq[n * 2], aq[n * 2 + 1]); }
#pragma unroll
      for (int h = 0; h < 2; h++) { Q[2][h] = t < 2 ? 0u : Q[1][2 + h]; Q[1][2 + h] = t < 2 ? Q[1][2 + h] : 0u; }
    };
    float acc[56];
    auto ai = [](int p) { return p < 4 ? 48 + (p & 1) * 4 + (p & 2) : (p - 4) * 4; };
    uint32_t xch, ts, tl;
    unsigned char *outp, *outq;
    auto setup_out = [&]() {
      xch = pin(base + OFF_K + (tid & 127) * 16);
      const uint32_t tb = base + OFF_K + 6144 + warp * 2560;
      ts = pin(tb + mi * 160 + r8 * 16); tl = pin(tb + t * 160 + g * 16);
      unsigned char* o = p.out + (mt * 64 + w4 * 16 + g) * 896 + dt * 224;
      outp = pin(o + th * 7168 + t * 16); outq = pin(o + (t >> 1) * 7168 + 192 + (t & 1) * 16);
    };
    auto give = [&](const float (&a)[56], int id) {
#pragma unroll
      for (int i = 0; i < 48; i += 16) sts128(xch + i * 128, pack2(a[i + 2], a[i + 3]), pack2(a[i + 6], a[i + 7]), pack2(a[i + 10], a[i + 11]), pack2(a[i + 14], a[i + 15]));
      named_arrive(id, 256);
    };
    auto take = [&](uint32_t (&r)[12], int id) {
      named_sync(id, 256);
#pragma unroll
      for (int i = 0; i < 3; i++) { const uint4 v = lds128(xch + i * 2048); r[i * 4] = v.x; r[i * 4 + 1] = v.y; r[i * 4 + 2] = v.z; r[i * 4 + 3] = v.w; }
    };
    float hv[32];
    auto keep_h = [&](int i) {
      const float hb0 = 0.5f * bf_lo(braw[i]), hb1 = 0.5f * bf_lo(braw[i + 1]);
#pragma unroll
      for (int j = 0; j < 32; j++) hv[j] = fmaf(acc[ai(j >> 1) + (j & 1)], 0.5f, j >= 4 && j < 8 ? hb1 : hb0);
    };
    auto take_h = [&](int i) {
      const float hb1 = 0.5f * bf_lo(braw[i + 1]);
      uint32_t r[12];
      take(r, 5);
#pragma unroll
      for (int j = 0; j < 12; j++) { hv[8 + 2 * j] = fmaf(bf_lo(r[j]), 0.5f, hb1); hv[9 + 2 * j] = fmaf(bf_hi(r[j]), 0.5f, hb1); }
    };
    uint4 Xr[4];
    auto get_x = [&]() {
      const uint32_t xr = base + OFF_Q + (w4 * 16 + g) * 224;
      mbar_wait(bars + B_RES, 0);
      Xr[0] = lds128(xr + (t >> 1) * 1792 + 192 + (t & 1) * 16);
#pragma unroll
      for (int i = 1; i < 4; i++) Xr[i] = lds128(xr + th * 1792 + t * 16 + (i - 1) * 64);
    };
    uint32_t Sv[16];
    auto gate = [&](int i) {
      uint32_t R[4];
#pragma unroll
      for (int q = 0; q < 4; q++) {
        const int j = i * 4 + q;
        const float h0 = hv[2 * j], h1 = hv[2 * j + 1];
        R[q] = hmul2(Sv[j], pack2(fmaf(h0, tanh_fast(h0), h0), fmaf(h1, tanh_fast(h1), h1)));
      }
      stsm4(ts + i * 640, R[0], R[1], R[2], R[3]);
    };
    auto leave = [&](int i) {
      __syncwarp();
      const uint4 v = lds128(tl + i * 640), x = Xr[i];
      stg128(i ? outp + (i - 1) * 64 : outq, hadd2(x.x, v.x), hadd2(x.y, v.y), hadd2(x.z, v.z), hadd2(x.w, v.w));
    };
    if (wg == 0) {
      named_sync(0, 256);
      OBS(tid == 96, 14);
      q_rest();
      named_arrive(6, 256);
      wg_wait<0>();
      if (tid == 0) mbar_arrive(bars + B_EMPTY + 7 * 8);
      q_pack();
      const uint32_t qst = base + OFF_Q + 8192 + (mi >> 1) * 1024 + (w4 * 16 + (mi & 1) * 8 + r8) * 16;
#pragma unroll
      for (int n = 0; n < 4; n++) stsm4(qst + n * 2048, Q[n][0], Q[n][1], Q[n][2], Q[n][3]);
      smem_fence();
      named_arrive(7, 256);
      OBS(tid == 32, 5);
      fresh(acc);
      if (g1) {
        unsigned char* ug = pin(scr + (d1 * HU_T + 32 + (ft >> 1)) * BT + ((ft & 1) * 4 + w4) * 1792 + lane * 4);
        unsigned char* ur = pin(ug + min(lane, 13) * 128);
        unsigned char* uc = pin(scr + d1 * 128);
        mbar_wait(bars, 0); mbar_wait(bars + 8, 0);
        const uint32_t utag = UTAG ? lds32(bars + B_TAG) : 0, um = UTAG ? pin(r8 == (ft & 1) * 4 + w4) : 0;
        {
          const uint32_t tg = lds64(bars + B_T0).x;
          while (tg - gtime() - 1 < 1000u);
        }
        named_sync(0, 256);
        gemm_issue<1>(acc, base >> 4, 0);
        OBS(tid == 0, 20);
        gemm_loop<1>(acc, base, 1, 32, rel, 40, 1, tid == 32 ? J1 : tid == 64 ? J2 : -1, bars + B_GATE - 8 + w4 * 8);
        wg_wait<0>();
        OBS(tid == 0, 21);
        named_arrive(5, 256);
        mbar_arrive_if(rel, bars + B_EMPTY + 7 * 8);
        auto gelu = [&](int n, int h) {
          const float hb = 0.5f * bf_lo(braw[h]);
          const float h0 = fmaf(acc[4 * n + 2 * h], 0.5f, hb), h1 = fmaf(acc[4 * n + 2 * h + 1], 0.5f, hb);
          const float t0 = tanh_fast(h0 * fmaf(h0 * h0, 0.2854192648f, 1.5957691216f)), t1 = tanh_fast(h1 * fmaf(h1 * h1, 0.2854192648f, 1.5957691216f));
          const uint32_t v = pack2(fmaf(h0, t0, h0), fmaf(h1, t1, h1));
          return UTAG > h ? (v & ~um) | (utag & um) : v;
        };
        auto done = [&](int h) {
          if (w4) named_arrive(13 + h, 128);
          else { named_sync(13 + h, 128); publish(uc, C_U + h * 4); OBS(tid == 0, h ? 13 : 9); }
          fence_code(10 + h);
        };
#pragma unroll
        for (int n = 0; n < 14; n++) { stg32(ug + n * 128, gelu(n, 0)); if (n % UCH == UCH - 1 && n < 13) fence_code(40 + n); }
        if (!UTAG) settle(probe(ur));
        if (OPD == 0) named_arrive(12, 256);
        done(0);
#pragma unroll
        for (int n = 0; n < 14; n++) { stg32(ug + 14 * BT + n * 128, gelu(n, 1)); if (n + 1 == OPD) named_arrive(12, 256); if ((n % UC2 == UC2 - 1 || n + 1 == OPD) && n < 13) fence_code(60 + n); }
        if (UTAG < 2) settle(probe(ur + 14 * BT));
        done(1);
      } else if (tid == 32 || tid == 64) mbar_arrive(bars + B_GATE - 8 + w4 * 8);
      setup_out();
      get_x();
      uint32_t r[12];
      take(r, 3);
#pragma unroll
      for (int j = 0; j < 16; j++) Sv[j] = r[j < 4 ? 0 : j - 4];
      asm volatile("" :: "r"(r[0]), "r"(r[11]) : "memory");
      named_arrive(10, 256);
      take_h(2);
    } else {
      const uint32_t dq = ((base + OFF_Q) >> 4) + (64u << 16), dk = (base + OFF_K) >> 4;
      const bool odd = g & 1, early = 2 * t + (g & 1) > g;
      uint32_t selA[5], selB[4];
#pragma unroll
      for (int j = 0; j < 5; j++) { selA[j] = j == w4 + (early ? 0 : 1) ? (odd ? 0x1044u : 0x4410u) : 0x4444u; }
#pragma unroll
      for (int j = 0; j < 4; j++) { selB[j] = j == w4 ? (odd ? 0x3244u : 0x4432u) : 0x4444u; }
      float Sc[2][40], Op[2][2][16];
      uint32_t A[2][5][4];
      auto scores = [&](int T) {
        fresh(Sc[0]); fresh(Sc[1]);
#pragma unroll
        for (int k = 0; k < 2; k++) {
#pragma unroll
          for (int hh = 0; hh < 2; hh++)
            if (T) wgmma_n80<0, 0>(Sc[hh], mkdesc(8, dq + 512 + hh * 256 + k * 128), mkdesc(112, dk + (8u << 16) + 896 + hh * 24 + k * 16), k);
            else wgmma_rs_n80<0>(Sc[hh], Q[hh * 2 + k], mkdesc(112, dk + (8u << 16) + hh * 24 + k * 16), k);
        }
      };
      auto softmax = [&](int T) {
        uint32_t L[2][2];
        auto pick = [&](int w) {
#pragma unroll
          for (int hh = 0; hh < 2; hh++) {
            const float* q = Sc[hh] + w * 8;
            auto at = [&](int i) { return odd ? q[i + 1] : q[i]; };
            L[hh][0] = pack2(early ? at(0) : at(8), early ? at(6) : at(14)); L[hh][1] = pack2(at(4), at(10));
          }
          asm volatile("" ::: "memory");
        };
        if (w4 & 2) { if (w4 & 1) pick(3); else pick(2); } else { if (w4 & 1) pick(1); else pick(0); }
#pragma unroll
        for (int hh = 0; hh < 2; hh++) {
          uint32_t a = hfma2(L[hh][0], SC_HI, hmul2(L[hh][0], SC_LO)), c = hfma2(L[hh][1], SC_HI, hmul2(L[hh][1], SC_LO));
          if (T == 0 && w4 == 0 && rb == 0) { if (early) a = 0xce6ece6eu; c = (c & 0xffff0000u) | 0xce6eu; }
          uint32_t mx = hmax2(a, c);
          mx = hmax2(mx, __shfl_xor_sync(0xffffffffu, mx, 1));
          mx = hmax2(mx, __shfl_xor_sync(0xffffffffu, mx, 2));
          uint32_t pp[2];
#pragma unroll
          for (int h = 0; h < 2; h++) {
            const float m = h ? bf_hi(mx) : bf_lo(mx);
            const float p0 = ex2_fast(((h ? bf_hi(a) : bf_lo(a)) - m) * LOG2E), p1 = ex2_fast(((h ? bf_hi(c) : bf_lo(c)) - m) * LOG2E);
            float sm = p0 + p1;
            sm += __shfl_xor_sync(0xffffffffu, sm, 1);
            sm += __shfl_xor_sync(0xffffffffu, sm, 2);
            const float inv = rcp_fast(sm);
            pp[h] = pack2(p0 * inv, p1 * inv);
          }
#pragma unroll
          for (int j = 0; j < 5; j++) {
            A[hh][j][0] = place(pp[0], selA[j]); A[hh][j][1] = j ? place(pp[1], selB[j ? j - 1 : 0]) : 0u;
            A[hh][j][2] = j < 4 ? place(pp[0], selB[j & 3]) : 0u; A[hh][j][3] = place(pp[1], selA[j]);
          }
        }
      };
      auto values = [&](int T) {
        fresh(Op[T][0]); fresh(Op[T][1]);
#pragma unroll
        for (int j = 0; j < 5; j++)
#pragma unroll
          for (int hh = 0; hh < 2; hh++) {
            wgmma_rs_n32<1>(Op[T][hh], A[hh][j], mkdesc(8, dk + (112u << 16) + 56 + T * 896 + hh * 24 + j * 224), j);
          }
        wg_commit();
      };
      uint32_t Ob[2][14];
      auto pack = [&](int T) {
        const float (&O)[2][16] = Op[T];
#pragma unroll
        for (int n = 0; n < 7; n++)
#pragma unroll
          for (int h = 0; h < 2; h++) {
            if (n < 3) Ob[T][n * 2 + h] = pack2(O[0][n * 4 + 2 * h], O[0][n * 4 + 2 * h + 1]);
            else if (n == 3) Ob[T][n * 2 + h] = pack2(t < 2 ? O[0][12 + 2 * h] : O[1][2 * h], t < 2 ? O[0][13 + 2 * h] : O[1][2 * h + 1]);
            else Ob[T][n * 2 + h] = pack2(O[1][(n - 3) * 4 + 2 * h], O[1][(n - 3) * 4 + 2 * h + 1]);
          }
      };
      smem_fence();
      named_sync(6, 256);
      OBS(tid == 224, 26);
      q_rest();
      named_sync(7, 256);
      wg_fence();
      scores(1);
      wg_commit();
      named_arrive_if(g1, 0, 256);
      wg_wait<2>();
      if (tid == 128) mbar_arrive(bars + B_EMPTY + 7 * 8);
      wg_wait<0>();
      OBS(tid == 160, 10);
      softmax(1);
      q_pack();
      OBS(tid == 160, 30);
      mbar_wait(bars + B_HALO, 0);
      OBS(tid == 160, 7);
      mbar_wait(bars + B_GATE, 0);
      wg_fence();
      scores(0);
      values(1);
      wg_wait<0>();
      OBS(tid == 160, 33);
      unsigned char* og = scr + O_OFF + rb * 2 * 57344 + hp * 7168 + w4 * 256 + lane * 4;
      const uint32_t tag = lds32(bars + B_TAG), m0 = r8 == 2 * w4, m1 = r8 == 2 * w4 + 1;
      auto put = [&](int T) {
#pragma unroll
        for (int n = 0; n < 7; n++) {
          stg32(og + T * 57344 + n * 1024, (Ob[T][2 * n] & ~m0) | (tag & m0)); stg32(og + T * 57344 + n * 1024 + 128, (Ob[T][2 * n + 1] & ~m1) | (tag & m1));
          __nanosleep(20);
        }
      };
      pack(1); put(1);
      softmax(0);
      mbar_wait(bars + B_GATE + 8, 0);
      wg_fence();
      values(0);
      wg_wait<0>();
      OBS(tid == 160, 35);
      named_sync(11, 128);
      if (tid == 160) mbar_arrive(bars + B_ATT);
      pack(0); put(0);
      OBS(tid == 160, 28);
      named_sync(11, 128);
      if (warp == 4) publish(scr, C_O + rb);
      OBS(tid == 160, 8);
      setup_out();
      float as[56];
      if (g1) named_sync(5, 256);
      get_x();
      mbar_wait(bars, 0);
      if (g1) named_sync(12, 256);
      fresh(as);
      gemm_issue<0>(as, base >> 4, 0);
      OBS(tid == 128, 22);
      gemm_loop<0>(as, base, 1, 7, rel, 104);
      fresh(acc);
      mbar_wait(bars + 56, 0);
      gemm_issue<1>(acc, (base + 7 * SLOT) >> 4, 0);
      OBS(tid == 128, 24);
      wg_wait<1>();
      mbar_arrive_if(rel, bars + B_EMPTY + 6 * 8);
      give(as, 3);
#pragma unroll
      for (int j = 0; j < 16; j++) Sv[j] = pack2(as[ai(j)], as[ai(j) + 1]);
      gemm_loop<1>(acc, base, 8, 35, rel, 65);
      named_sync(10, 256);
      wg_wait<0>();
      OBS(tid == 128, 25);
      give(acc, 5);
      fence_code(31);
      keep_h(2);
      gate(0); leave(0);
    }
    {
#pragma unroll
      for (int i = 1; i < 4; i++) { gate(i); leave(i); }
      OBS(tid == 128, 27);
    }
  }
}

typedef CUresult (*EncFn)(CUtensorMap*, CUtensorMapDataType, cuuint32_t, void*, const cuuint64_t*, const cuuint64_t*, const cuuint32_t*,
                          const cuuint32_t*, CUtensorMapInterleave, CUtensorMapSwizzle, CUtensorMapL2promotion, CUtensorMapFloatOOBfill);
void enc(EncFn f, CUtensorMap* m, const void* ptr, cuuint64_t d0, cuuint64_t d1, cuuint64_t d2, cuuint64_t s1, cuuint64_t s2, cuuint32_t b1, cuuint32_t b2, cuuint32_t b0 = 64) {
  const cuuint64_t gd[3] = {d0, d1, d2}, gs[2] = {s1 * 2, s2 * 2};
  const cuuint32_t bx[3] = {b0, b1, b2}, es[3] = {1, 1, 1};
  f(m, CU_TENSOR_MAP_DATA_TYPE_BFLOAT16, 3, (void*)ptr, gd, gs, bx, es, CU_TENSOR_MAP_INTERLEAVE_NONE, b0 == 64 ? CU_TENSOR_MAP_SWIZZLE_128B : CU_TENSOR_MAP_SWIZZLE_NONE,
    CU_TENSOR_MAP_L2_PROMOTION_L2_128B, CU_TENSOR_MAP_FLOAT_OOB_FILL_NONE);
}
}

extern "C" void kernel_launch(void* const* d_in, const int* in_sizes, int n_in, void* d_out, int out_size) {
  (void)in_sizes; (void)n_in; (void)out_size;
  void* fp = nullptr;
  cudaDriverEntryPointQueryResult qr;
  cudaGetDriverEntryPoint("cuTensorMapEncodeTiled", &fp, cudaEnableDefault, &qr);
  EncFn f = (EncFn)fp;
  CUtensorMap m_x, m_wkv, m_wq, m_w1, m_w2, m_res;
  void* scr = nullptr;
  cudaGetSymbolAddress(&scr, g_scr);
  enc(f, &m_x, d_in[0], D_, S_, 1, D_, D_, 64, 1);
  enc(f, &m_wkv, d_in[1], D_, D_, 3, 3 * D_, D_, 64, 2);
  enc(f, &m_wq, d_in[1], D_, D_, 3, 3 * D_, D_, 64, 1);
  enc(f, &m_w1, d_in[4], F_, S_, 1, F_, F_, 64, 1);
  enc(f, &m_w2, d_in[6], S_, 16, F_ / 16, S_, 16 * S_, 8, 8);
  enc(f, &m_res, d_in[0], D_, S_, 1, D_, D_, 64, 1, 112);
  Params p;
  p.wqkv = (const unsigned char*)d_in[1]; p.wo = (const unsigned char*)d_in[2];
  p.w1 = (const unsigned char*)d_in[4]; p.b1 = (const unsigned char*)d_in[5];
  p.w2 = (const unsigned char*)d_in[6]; p.b2 = (const unsigned char*)d_in[7];
  p.out = (unsigned char*)d_out; p.scr = (unsigned char*)scr;
  cudaFuncSetAttribute(fused_kernel, cudaFuncAttributeMaxDynamicSharedMemorySize, SMEM_BYTES);
  fused_kernel<<<128, NTHREADS, SMEM_BYTES, cudaStreamPerThread>>>(m_x, m_wkv, m_wq, m_w1, m_w2, m_res, p);
}
```

```cpp
#include <cuda_runtime.h>
#include <cuda.h>
#include <cuda_bf16.h>
#include <stdint.h>

template<int TA, int TB> __device__ __forceinline__ void wgmma_n112(float (&d)[56], uint64_t da, uint64_t db, int sc) {
  asm volatile("{\n.reg .pred p;\nsetp.ne.b32 p, %58, 0;\n"
    "wgmma.mma_async.sync.aligned.m64n112k16.f32.bf16.bf16 {%0, %1, %2, %3, %4, %5, %6, %7, %8, %9, %10, %11, %12, %13, %14, %15, %16, %17, %18, %19, %20, %21, %22, %23, %24, %25, %26, %27, %28, %29, %30, %31, %32, %33, %34, %35, %36, %37, %38, %39, %40, %41, %42, %43, %44, %45, %46, %47, %48, %49, %50, %51, %52, %53, %54, %55}, %56, %57, p, 1, 1, %59, %60;\n}\n"
    : "+f"(d[0]), "+f"(d[1]), "+f"(d[2]), "+f"(d[3]), "+f"(d[4]), "+f"(d[5]), "+f"(d[6]), "+f"(d[7]), "+f"(d[8]), "+f"(d[9]), "+f"(d[10]), "+f"(d[11]), "+f"(d[12]), "+f"(d[13]), "+f"(d[14]), "+f"(d[15]), "+f"(d[16]), "+f"(d[17]), "+f"(d[18]), "+f"(d[19]), "+f"(d[20]), "+f"(d[21]), "+f"(d[22]), "+f"(d[23]), "+f"(d[24]), "+f"(d[25]), "+f"(d[26]), "+f"(d[27]), "+f"(d[28]), "+f"(d[29]), "+f"(d[30]), "+f"(d[31]), "+f"(d[32]), "+f"(d[33]), "+f"(d[34]), "+f"(d[35]), "+f"(d[36]), "+f"(d[37]), "+f"(d[38]), "+f"(d[39]), "+f"(d[40]), "+f"(d[41]), "+f"(d[42]), "+f"(d[43]), "+f"(d[44]), "+f"(d[45]), "+f"(d[46]), "+f"(d[47]), "+f"(d[48]), "+f"(d[49]), "+f"(d[50]), "+f"(d[51]), "+f"(d[52]), "+f"(d[53]), "+f"(d[54]), "+f"(d[55])
    : "l"(da), "l"(db), "r"(sc), "n"(TA), "n"(TB));
}

template<int TA, int TB> __device__ __forceinline__ void wgmma_n80(float (&d)[40], uint64_t da, uint64_t db, int sc) {
  asm volatile("{\n.reg .pred p;\nsetp.ne.b32 p, %42, 0;\n"
    "wgmma.mma_async.sync.aligned.m64n80k16.f32.bf16.bf16 {%0, %1, %2, %3, %4, %5, %6, %7, %8, %9, %10, %11, %12, %13, %14, %15, %16, %17, %18, %19, %20, %21, %22, %23, %24, %25, %26, %27, %28, %29, %30, %31, %32, %33, %34, %35, %36, %37, %38, %39}, %40, %41, p, 1, 1, %43, %44;\n}\n"
    : "+f"(d[0]), "+f"(d[1]), "+f"(d[2]), "+f"(d[3]), "+f"(d[4]), "+f"(d[5]), "+f"(d[6]), "+f"(d[7]), "+f"(d[8]), "+f"(d[9]), "+f"(d[10]), "+f"(d[11]), "+f"(d[12]), "+f"(d[13]), "+f"(d[14]), "+f"(d[15]), "+f"(d[16]), "+f"(d[17]), "+f"(d[18]), "+f"(d[19]), "+f"(d[20]), "+f"(d[21]), "+f"(d[22]), "+f"(d[23]), "+f"(d[24]), "+f"(d[25]), "+f"(d[26]), "+f"(d[27]), "+f"(d[28]), "+f"(d[29]), "+f"(d[30]), "+f"(d[31]), "+f"(d[32]), "+f"(d[33]), "+f"(d[34]), "+f"(d[35]), "+f"(d[36]), "+f"(d[37]), "+f"(d[38]), "+f"(d[39])
    : "l"(da), "l"(db), "r"(sc), "n"(TA), "n"(TB));
}

template<int TB> __device__ __forceinline__ void wgmma_rs_n120(float (&d)[60], const uint32_t (&a)[4], uint64_t db, int sc) {
  asm volatile("{\n.reg .pred p;\nsetp.ne.b32 p, %65, 0;\n"
    "wgmma.mma_async.sync.aligned.m64n120k16.f32.bf16.bf16 {%0, %1, %2, %3, %4, %5, %6, %7, %8, %9, %10, %11, %12, %13, %14, %15, %16, %17, %18, %19, %20, %21, %22, %23, %24, %25, %26, %27, %28, %29, %30, %31, %32, %33, %34, %35, %36, %37, %38, %39, %40, %41, %42, %43, %44, %45, %46, %47, %48, %49, %50, %51, %52, %53, %54, %55, %56, %57, %58, %59}, {%60, %61, %62, %63}, %64, p, 1, 1, %66;\n}\n"
    : "+f"(d[0]), "+f"(d[1]), "+f"(d[2]), "+f"(d[3]), "+f"(d[4]), "+f"(d[5]), "+f"(d[6]), "+f"(d[7]), "+f"(d[8]), "+f"(d[9]), "+f"(d[10]), "+f"(d[11]), "+f"(d[12]), "+f"(d[13]), "+f"(d[14]), "+f"(d[15]), "+f"(d[16]), "+f"(d[17]), "+f"(d[18]), "+f"(d[19]), "+f"(d[20]), "+f"(d[21]), "+f"(d[22]), "+f"(d[23]), "+f"(d[24]), "+f"(d[25]), "+f"(d[26]), "+f"(d[27]), "+f"(d[28]), "+f"(d[29]), "+f"(d[30]), "+f"(d[31]), "+f"(d[32]), "+f"(d[33]), "+f"(d[34]), "+f"(d[35]), "+f"(d[36]), "+f"(d[37]), "+f"(d[38]), "+f"(d[39]), "+f"(d[40]), "+f"(d[41]), "+f"(d[42]), "+f"(d[43]), "+f"(d[44]), "+f"(d[45]), "+f"(d[46]), "+f"(d[47]), "+f"(d[48]), "+f"(d[49]), "+f"(d[50]), "+f"(d[51]), "+f"(d[52]), "+f"(d[53]), "+f"(d[54]), "+f"(d[55]), "+f"(d[56]), "+f"(d[57]), "+f"(d[58]), "+f"(d[59])
    : "r"(a[0]), "r"(a[1]), "r"(a[2]), "r"(a[3]), "l"(db), "r"(sc), "n"(TB));
}

template<int TB> __device__ __forceinline__ void wgmma_rs_n56(float (&d)[28], const uint32_t (&a)[4], uint64_t db, int sc) {
  asm volatile("{\n.reg .pred p;\nsetp.ne.b32 p, %33, 0;\n"
    "wgmma.mma_async.sync.aligned.m64n56k16.f32.bf16.bf16 {%0, %1, %2, %3, %4, %5, %6, %7, %8, %9, %10, %11, %12, %13, %14, %15, %16, %17, %18, %19, %20, %21, %22, %23, %24, %25, %26, %27}, {%28, %29, %30, %31}, %32, p, 1, 1, %34;\n}\n"
    : "+f"(d[0]), "+f"(d[1]), "+f"(d[2]), "+f"(d[3]), "+f"(d[4]), "+f"(d[5]), "+f"(d[6]), "+f"(d[7]), "+f"(d[8]), "+f"(d[9]), "+f"(d[10]), "+f"(d[11]), "+f"(d[12]), "+f"(d[13]), "+f"(d[14]), "+f"(d[15]), "+f"(d[16]), "+f"(d[17]), "+f"(d[18]), "+f"(d[19]), "+f"(d[20]), "+f"(d[21]), "+f"(d[22]), "+f"(d[23]), "+f"(d[24]), "+f"(d[25]), "+f"(d[26]), "+f"(d[27])
    : "r"(a[0]), "r"(a[1]), "r"(a[2]), "r"(a[3]), "l"(db), "r"(sc), "n"(TB));
}

template<int TB> __device__ __forceinline__ void wgmma_rs_n32(float (&d)[16], const uint32_t (&a)[4], uint64_t db, int sc) {
  asm volatile("{\n.reg .pred p;\nsetp.ne.b32 p, %21, 0;\n"
    "wgmma.mma_async.sync.aligned.m64n32k16.f32.bf16.bf16 {%0, %1, %2, %3, %4, %5, %6, %7, %8, %9, %10, %11, %12, %13, %14, %15}, {%16, %17, %18, %19}, %20, p, 1, 1, %22;\n}\n"
    : "+f"(d[0]), "+f"(d[1]), "+f"(d[2]), "+f"(d[3]), "+f"(d[4]), "+f"(d[5]), "+f"(d[6]), "+f"(d[7]), "+f"(d[8]), "+f"(d[9]), "+f"(d[10]), "+f"(d[11]), "+f"(d[12]), "+f"(d[13]), "+f"(d[14]), "+f"(d[15])
    : "r"(a[0]), "r"(a[1]), "r"(a[2]), "r"(a[3]), "l"(db), "r"(sc), "n"(TB));
}

template<int TB> __device__ __forceinline__ void wgmma_rs_n80(float (&d)[40], const uint32_t (&a)[4], uint64_t db, int sc) {
  asm volatile("{\n.reg .pred p;\nsetp.ne.b32 p, %45, 0;\n"
    "wgmma.mma_async.sync.aligned.m64n80k16.f32.bf16.bf16 {%0, %1, %2, %3, %4, %5, %6, %7, %8, %9, %10, %11, %12, %13, %14, %15, %16, %17, %18, %19, %20, %21, %22, %23, %24, %25, %26, %27, %28, %29, %30, %31, %32, %33, %34, %35, %36, %37, %38, %39}, {%40, %41, %42, %43}, %44, p, 1, 1, %46;\n}\n"
    : "+f"(d[0]), "+f"(d[1]), "+f"(d[2]), "+f"(d[3]), "+f"(d[4]), "+f"(d[5]), "+f"(d[6]), "+f"(d[7]), "+f"(d[8]), "+f"(d[9]), "+f"(d[10]), "+f"(d[11]), "+f"(d[12]), "+f"(d[13]), "+f"(d[14]), "+f"(d[15]), "+f"(d[16]), "+f"(d[17]), "+f"(d[18]), "+f"(d[19]), "+f"(d[20]), "+f"(d[21]), "+f"(d[22]), "+f"(d[23]), "+f"(d[24]), "+f"(d[25]), "+f"(d[26]), "+f"(d[27]), "+f"(d[28]), "+f"(d[29]), "+f"(d[30]), "+f"(d[31]), "+f"(d[32]), "+f"(d[33]), "+f"(d[34]), "+f"(d[35]), "+f"(d[36]), "+f"(d[37]), "+f"(d[38]), "+f"(d[39])
    : "r"(a[0]), "r"(a[1]), "r"(a[2]), "r"(a[3]), "l"(db), "r"(sc), "n"(TB));
}

namespace {
constexpr int S_ = 2048, D_ = 448, F_ = 1792;
constexpr int NSLOT = 8, SLOT = 22528;
constexpr int OFF_X = 7 * 16384;
constexpr int OFF_WQ = 8 * 16384;
constexpr int OFF_Q = NSLOT * SLOT;
constexpr int OFF_K = OFF_Q + 16384;
constexpr int OFF_BAR = 14 * 16384;
constexpr int OFF_LN = OFF_BAR + 512;
constexpr int OFF_OBS = OFF_BAR + 640;
constexpr int SMEM_BYTES = OFF_OBS + 1024;
#define PACE1 540
#define PACE2 600
#define J1 6
#define J2 14
#define TS 3120
#define UP 170
#define WQA 4
#define SOBS 0
#define FREQ 0
#define KOBS 0
#define LANDOBS 0
#define OBS(c, i) do {} while (0)
#define OBSG(c, i, j) do {} while (0)
constexpr int NTHREADS = 384;
constexpr float LOG2E = 1.4426950408889634f;
constexpr uint32_t SC_HI = 0x3e423e42u, SC_LO = 0xb9f7b9f7u;
constexpr int BT = 14336;

constexpr int HU_T = 67;
constexpr int O_OFF = 4 * HU_T * BT;
constexpr int HALO_OFF = O_OFF + 32 * 7 * 8192;
constexpr int CNT_OFF = HALO_OFF + 128 * 3584;
constexpr int SCR_BYTES = CNT_OFF + 160 * 128;
constexpr int C_U = 0, C_O = 8, C_H = 24, C_WO = 25, C_TK = 26, C_HALO = 32;
__device__ __align__(1024) unsigned char g_scr[SCR_BYTES];

__device__ __forceinline__ uint32_t smem_u32(const void* p) { return (uint32_t)__cvta_generic_to_shared(p); }
__device__ __forceinline__ void mbar_init(uint32_t bar, uint32_t cnt) { asm volatile("mbarrier.init.shared::cta.b64 [%0], %1;" :: "r"(bar), "r"(cnt)); }
__device__ __forceinline__ void mbar_expect_tx(uint32_t bar, uint32_t bytes) { asm volatile("mbarrier.arrive.expect_tx.shared::cta.b64 _, [%0], %1;" :: "r"(bar), "r"(bytes) : "memory"); }
__device__ __forceinline__ void mbar_arrive_if(uint32_t c, uint32_t bar) { asm volatile("{\n.reg .pred q;\nsetp.ne.u32 q, %1, 0;\n@q mbarrier.arrive.shared::cta.b64 _, [%0];\n}" :: "r"(bar), "r"(c) : "memory"); }
__device__ __forceinline__ void mbar_arrive(uint32_t bar) { asm volatile("mbarrier.arrive.shared::cta.b64 _, [%0];" :: "r"(bar) : "memory"); }
__device__ __forceinline__ void mbar_wait(uint32_t bar, uint32_t parity) {
  asm volatile("{\n.reg .pred p;\n.reg .u32 n;\nmov.u32 n, 0;\nLAB_WAIT:\n"
               "mbarrier.try_wait.parity.shared::cta.b64 p, [%0], %1;\n@p bra DONE;\n"
               "add.u32 n, n, 1;\nsetp.lt.u32 p, n, 400000;\n@p bra LAB_WAIT;\ntrap;\nDONE:\n}" :: "r"(bar), "r"(parity) : "memory");
}
__device__ __forceinline__ uint32_t mbar_try(uint32_t bar, uint32_t parity) {
  uint32_t ok;
  asm volatile("{\n.reg .pred p;\nmbarrier.test_wait.parity.shared::cta.b64 p, [%1], %2;\nselp.u32 %0, 1, 0, p;\n}" : "=r"(ok) : "r"(bar), "r"(parity) : "memory");
  return ok;
}
__device__ __forceinline__ void tma3d(uint32_t dst, const CUtensorMap* m, int c0, int c1, int c2, uint32_t bar) {
  asm volatile("cp.async.bulk.tensor.3d.shared::cluster.global.mbarrier::complete_tx::bytes [%0], [%1, {%3, %4, %5}], [%2];"
               :: "r"(dst), "l"(m), "r"(bar), "r"(c0), "r"(c1), "r"(c2) : "memory");
}
__device__ __forceinline__ void bulk_g2s(uint32_t dst, const void* src, uint32_t bytes, uint32_t bar) {
  asm volatile("cp.async.bulk.shared::cluster.global.mbarrier::complete_tx::bytes [%0], [%1], %2, [%3];" :: "r"(dst), "l"(src), "r"(bytes), "r"(bar) : "memory");
}
__device__ __forceinline__ void wg_fence() { asm volatile("wgmma.fence.sync.aligned;" ::: "memory"); }
__device__ __forceinline__ void wg_commit() { asm volatile("wgmma.commit_group.sync.aligned;" ::: "memory"); }
template <int N> __device__ __forceinline__ void wg_wait() { asm volatile("wgmma.wait_group.sync.aligned %0;" :: "n"(N) : "memory"); }
__device__ __forceinline__ void smem_fence() { asm volatile("fence.proxy.async.shared::cta;" ::: "memory"); }
__device__ __forceinline__ void stg128(void* p, uint32_t a, uint32_t b, uint32_t c, uint32_t d) { asm volatile("st.global.v4.u32 [%0], {%1,%2,%3,%4};" :: "l"(p), "r"(a), "r"(b), "r"(c), "r"(d) : "memory"); }
__device__ __forceinline__ void stg32(void* p, uint32_t v) { asm volatile("st.global.u32 [%0], %1;" :: "l"(p), "r"(v) : "memory"); }
__device__ __forceinline__ uint4 ldg128(const void* p) { uint4 v; asm volatile("ld.global.nc.L1::no_allocate.v4.u32 {%0,%1,%2,%3}, [%4];" : "=r"(v.x), "=r"(v.y), "=r"(v.z), "=r"(v.w) : "l"(p)); return v; }
__device__ __forceinline__ void publish(unsigned char* scr, int i) {
  asm volatile("{\n.reg .pred q;\nelect.sync _|q, 0xffffffff;\n@q red.relaxed.gpu.global.inc.u32 [%0], 0xffffffff;\n}" :: "l"(scr + CNT_OFF + i * 128) : "memory");
}
__device__ __forceinline__ uint32_t probe(const unsigned char* p) { uint32_t v; asm volatile("ld.relaxed.gpu.global.u32 %0, [%1];" : "=r"(v) : "l"(p) : "memory"); return v; }
__device__ __forceinline__ void settle(uint32_t v) {
  asm volatile("{\n.reg .pred q;\nsetp.eq.u32 q, %0, 0x7fc1dead;\n@q st.volatile.shared.u32 [%1], %0;\n}" :: "r"(v), "r"(1024 + OFF_BAR + 376) : "memory");
  __syncwarp();
}
__device__ __forceinline__ uint32_t spin_ge(unsigned char* scr, int i, unsigned target) {
  uint32_t v;
  asm volatile("{\n.reg .pred p;\n.reg .u32 n;\nmov.u32 n, 0;\nLAB_SPIN:\n"
               "ld.relaxed.gpu.global.u32 %0, [%1];\nsetp.ge.u32 p, %0, %2;\nvote.sync.all.pred p, p, 0xffffffff;\n@p bra DONE;\n"
               "add.u32 n, n, 1;\nsetp.lt.u32 p, n, 4000000;\n@p bra LAB_SPIN;\ntrap;\nDONE:\n}" : "=&r"(v) : "l"(scr + CNT_OFF + i * 128), "r"(target) : "memory");
  return v;
}
__device__ __forceinline__ int lane_id() { int l; asm volatile("mov.u32 %0, %%laneid;" : "=r"(l)); return l; }
__device__ __forceinline__ uint32_t pin(uint32_t v) { return __shfl_xor_sync(0xffffffffu, v, blockIdx.y); }
__device__ __forceinline__ unsigned char* pin(unsigned char* p) { return (unsigned char*)(((uint64_t)pin((uint32_t)((uint64_t)p >> 32)) << 32) | pin((uint32_t)(uint64_t)p)); }
__device__ __forceinline__ uint32_t gtime() { uint32_t g; asm volatile("mov.u32 %0, %%globaltimer_lo;" : "=r"(g)); return g; }
__device__ __forceinline__ bool elect() {
  uint32_t r; asm volatile("{\n.reg .pred p;\nelect.sync _|p, 0xffffffff;\nselp.u32 %0, 1, 0, p;\n}" : "=r"(r)); return r != 0;
}
__device__ __forceinline__ uint4 lds128(uint32_t a) { uint4 v; asm volatile("ld.shared.v4.u32 {%0,%1,%2,%3}, [%4];" : "=r"(v.x), "=r"(v.y), "=r"(v.z), "=r"(v.w) : "r"(a) : "memory"); return v; }
__device__ __forceinline__ uint32_t lds32(uint32_t a) { uint32_t v; asm volatile("ld.shared.u32 %0, [%1];" : "=r"(v) : "r"(a) : "memory"); return v; }
__device__ __forceinline__ uint2 lds64(uint32_t a) { uint2 v; asm volatile("ld.shared.v2.u32 {%0,%1}, [%2];" : "=r"(v.x), "=r"(v.y) : "r"(a) : "memory"); return v; }
__device__ __forceinline__ void sts128(uint32_t p, uint32_t a, uint32_t b, uint32_t c, uint32_t d) { asm volatile("st.shared.v4.u32 [%0], {%1,%2,%3,%4};" :: "r"(p), "r"(a), "r"(b), "r"(c), "r"(d) : "memory"); }
__device__ __forceinline__ void sts32(uint32_t a, float v) { asm volatile("st.shared.f32 [%0], %1;" :: "r"(a), "f"(v) : "memory"); }
__device__ __forceinline__ void named_sync(int id, int n) { asm volatile("bar.sync %0, %1;" :: "r"(id), "r"(n) : "memory"); }
__device__ __forceinline__ void named_arrive(int id, int n) { asm volatile("bar.arrive %0, %1;" :: "r"(id), "r"(n) : "memory"); }
__device__ __forceinline__ void named_arrive_if(uint32_t c, int id, int n) { asm volatile("{\n.reg .pred q;\nsetp.ne.u32 q, %2, 0;\n@q bar.arrive %0, %1;\n}" :: "r"(id), "r"(n), "r"(c) : "memory"); }
__device__ __forceinline__ uint64_t mkdesc(uint32_t hi, uint32_t lo) { return ((uint64_t)hi << 32) | lo; }
constexpr uint32_t HI_SW128 = 0x40000040u;
__device__ __forceinline__ uint32_t pack2(float lo, float hi) { uint32_t r; asm("cvt.rn.bf16x2.f32 %0, %1, %2;" : "=r"(r) : "f"(hi), "f"(lo)); return r; }
__device__ __forceinline__ float bf_lo(uint32_t v) { return __uint_as_float(v << 16); }
__device__ __forceinline__ float bf_hi(uint32_t v) { return __uint_as_float(v & 0xffff0000u); }
__device__ __forceinline__ float rbf(float x) { return bf_lo(pack2(x, 0.f)); }
__device__ __forceinline__ uint32_t hsub2(uint32_t a, uint32_t b) { uint32_t r; asm("sub.rn.bf16x2 %0, %1, %2;" : "=r"(r) : "r"(a), "r"(b)); return r; }
__device__ __forceinline__ uint32_t hadd2(uint32_t a, uint32_t b) { uint32_t r; asm("add.rn.bf16x2 %0, %1, %2;" : "=r"(r) : "r"(a), "r"(b)); return r; }
__device__ __forceinline__ uint32_t place(uint32_t v, uint32_t sel) { uint32_t r; asm volatile("prmt.b32 %0, %1, 0, %2;" : "=r"(r) : "r"(v), "r"(sel)); return r; }
__device__ __forceinline__ uint32_t hmax2(uint32_t a, uint32_t b) { uint32_t r; asm("max.bf16x2 %0, %1, %2;" : "=r"(r) : "r"(a), "r"(b)); return r; }
__device__ __forceinline__ uint32_t hmul2(uint32_t a, uint32_t b) { uint32_t r; asm("mul.rn.bf16x2 %0, %1, %2;" : "=r"(r) : "r"(a), "r"(b)); return r; }
__device__ __forceinline__ uint32_t hfma2(uint32_t a, uint32_t b, uint32_t c) { uint32_t r; asm("fma.rn.bf16x2 %0, %1, %2, %3;" : "=r"(r) : "r"(a), "r"(b), "r"(c)); return r; }
__device__ __forceinline__ float tanh_fast(float x) { float r; asm("tanh.approx.f32 %0, %1;" : "=f"(r) : "f"(x)); return r; }
__device__ __forceinline__ float rcp_fast(float x) { float r; asm("rcp.approx.ftz.f32 %0, %1;" : "=f"(r) : "f"(x)); return r; }
__device__ __forceinline__ float ex2_fast(float x) { float r; asm("ex2.approx.ftz.f32 %0, %1;" : "=f"(r) : "f"(x)); return r; }
__device__ __forceinline__ void mma16816(float (&c)[4], uint32_t a0, uint32_t a1, uint32_t a2, uint32_t a3, uint32_t b0, uint32_t b1) {
  asm volatile("mma.sync.aligned.m16n8k16.row.col.f32.bf16.bf16.f32 {%0,%1,%2,%3}, {%4,%5,%6,%7}, {%8,%9}, {%0,%1,%2,%3};"
               : "+f"(c[0]), "+f"(c[1]), "+f"(c[2]), "+f"(c[3]) : "r"(a0), "r"(a1), "r"(a2), "r"(a3), "r"(b0), "r"(b1));
}
__device__ __forceinline__ void ldsm4(uint32_t (&r)[4], uint32_t addr) {
  asm volatile("ldmatrix.sync.aligned.m8n8.x4.shared.b16 {%0,%1,%2,%3}, [%4];" : "=r"(r[0]), "=r"(r[1]), "=r"(r[2]), "=r"(r[3]) : "r"(addr) : "memory");
}
__device__ __forceinline__ void stsm4(uint32_t addr, uint32_t a, uint32_t b, uint32_t c, uint32_t d) {
  asm volatile("stmatrix.sync.aligned.m8n8.x4.shared.b16 [%0], {%1,%2,%3,%4};" :: "r"(addr), "r"(a), "r"(b), "r"(c), "r"(d) : "memory");
}

__device__ __forceinline__ float ln_rstd(float var, float eps = 1e-5f) {
  float sd;
  asm("sqrt.approx.ftz.f32 %0, %1;" : "=f"(sd) : "f"(rbf(rbf(var) + eps)));
  return rcp_fast(rbf(sd));
}
__device__ __forceinline__ float ln_var(float mean, float sq) { return fmaxf(fmaf(-mean, mean, sq * (1.0f / D_)), 0.f); }
struct LnC { uint32_t m, rh, rl; };
__device__ __forceinline__ LnC ln_consts(float sum, float sq, float eps) {
  const float mean = sum * (1.0f / D_), r = ln_rstd(ln_var(mean, sq), eps), rh = rbf(r);
  LnC c; c.m = pack2(mean, mean); c.rh = pack2(rh, rh); c.rl = pack2(r - rh, r - rh);
  return c;
}
__device__ __forceinline__ uint32_t ln_apply(uint32_t x, const LnC& c) {
  uint32_t d = hsub2(x, c.m);
  return hfma2(d, c.rh, hmul2(d, c.rl));
}

__device__ __forceinline__ void fence_code(int id) {
  asm volatile("{\n.reg .pred q;\nLAB_F:\nsetp.eq.u32 q, %0, %1;\n@q st.volatile.shared.u32 [%2], %2;\n@q bra LAB_F;\n}" :: "r"(blockIdx.x), "r"(0x70000000 + id), "r"(0) : "memory");
}
template <int N> __device__ __forceinline__ void fresh(float (&a)[N]) {
#pragma unroll
  for (int i = 0; i < N; i++) asm volatile("" : "=f"(a[i]));
}
constexpr int B_EMPTY = 64, B_U1 = 128, B_U2 = 136, B_WQ = 144, B_WQ2 = 152, B_HIN = 160, B_HALO = 168, B_GATE = 176, B_ATT = 192, B_RES = 200, B_WO = 208, B_O = 216;
constexpr int B_OL = 224, B_KV = 296, B_TAG = 360, B_T0 = 368, B_X = 384;

template <int TA>
__device__ __forceinline__ void gemm_issue(float (&acc)[56], uint32_t lo, int sc) {
  wg_fence();
#pragma unroll
  for (int k = 0; k < 4; k++)
    wgmma_n112<TA, 1>(acc, mkdesc(TA ? HI_SW128 : 8, lo + (TA ? 512u << 16 : 64u << 16) + k * 128), mkdesc(8, lo + (112u << 16) + 512 + k * 224), sc | k);
  wg_commit();
}
template <int TA>
__device__ __forceinline__ void gemm_loop(float (&acc)[56], uint32_t base, int it, int end, bool rel, int oi, uint32_t ok = 0, int gate_it = -1, uint32_t gate = 0) {
#pragma unroll 1
  for (; it < end;) {
    if (__builtin_expect(!ok, 0)) mbar_wait(base + OFF_BAR + (it & 7) * 8, (it >> 3) & 1);
    gemm_issue<TA>(acc, (base >> 4) + (it & 7) * (SLOT >> 4), 1);
    OBS(SOBS && rel, oi + it);
    it++;
    ok = mbar_try(base + OFF_BAR + (it & 7) * 8, (it >> 3) & 1);
    wg_wait<1>();
    if (rel || it == gate_it) mbar_arrive(rel ? base + OFF_BAR + B_EMPTY + ((it - 2) & 7) * 8 : gate);
  }
}
template <int S1, int S2>
__device__ __forceinline__ void produce_box(uint32_t base, int it, int end, const CUtensorMap* mp, int c0, int c1) {
#pragma unroll 1
  for (int c2 = 0; it < end; it++, c1 += S1, c2 += S2) {
    const uint32_t fb = base + OFF_BAR + (it & 7) * 8;
    mbar_wait(fb + B_EMPTY, (it >> 3) & 1);
    if (elect()) { mbar_expect_tx(fb, 8192); tma3d(base + (it & 7) * SLOT, mp, c0, c1, c2, fb); }
  }
}
template <int PER, int LAND = 0>
__device__ __forceinline__ void produce_lin(uint32_t base, int it, int end, const unsigned char* src, uint32_t bytes, uint32_t tn = 0) {
#pragma unroll 1
  for (; it < end; it++) {
    const uint32_t fb = base + OFF_BAR + (it & 7) * 8;
    mbar_wait(fb + B_EMPTY, (it >> 3) & 1);
    if (PER) { while ((int)(clock() - tn) < 0); tn += PER; }
    if (elect()) { mbar_expect_tx(fb + LAND, bytes); bulk_g2s(base + (it & 7) * SLOT + (bytes & 2048) * 4, src, bytes, fb + LAND); }
    src += bytes;
  }
}

__device__ __forceinline__ void retile_wo(const unsigned char* wo, unsigned char* scr, int u, int lane) {
  const int r8 = lane & 7, mi = lane >> 3;
  const unsigned char* src = wo + ((u >> 1) * 8 + r8) * 896 + ((u & 1) * 28 + mi) * 16;
  unsigned char* dst = scr + ((u & 1) * 2 * HU_T + 60 + (u >> 4)) * BT + ((u >> 1) & 7) * 1792 + mi * 128 + r8 * 16;
  uint4 v[7];
#pragma unroll
  for (int i = 0; i < 7; i++) v[i] = ldg128(src + i * 64);
#pragma unroll
  for (int i = 0; i < 7; i++) stg128(dst + i * 512 + ((i * 4 + mi) / 14) * (HU_T * BT - 1792), v[i].x, v[i].y, v[i].z, v[i].w);
}

struct Params {
  const unsigned char *wqkv, *wo, *w1, *b1, *w2, *b2;
  unsigned char *out, *scr;
};

__global__ void __launch_bounds__(NTHREADS, 1)
fused_kernel(const __grid_constant__ CUtensorMap m_x, const __grid_constant__ CUtensorMap m_wkv, const __grid_constant__ CUtensorMap m_wq,
             const __grid_constant__ CUtensorMap m_w1, const __grid_constant__ CUtensorMap m_w2, const __grid_constant__ CUtensorMap m_res, const Params p) {
  extern __shared__ __align__(1024) unsigned char smem_raw[];
  constexpr uint32_t base = 1024, bars = base + OFF_BAR;
  const int tid = threadIdx.x, lane = tid & 31, b = blockIdx.x;
  const int rb = (b >> 2) & 15, hp = ((b >> 6) << 2) | (b & 3);
  const int wcol = hp * 56 - (hp & 1) * 8;
  auto load_wq = [&](int s0, int s1, uint32_t bar) {
    mbar_expect_tx(bar, (s1 - s0) * 8192);
#pragma unroll 1
    for (int s = s0; s < s1; s++) tma3d(base + OFF_WQ + s * 8192, &m_wq, wcol, s * 64, 0, bar);
  };
  auto load_kv = [&](int s) { mbar_expect_tx(bars + B_KV + s * 8, 16384); tma3d(base + s * 16384, &m_wkv, wcol, s * 64, 1, bars + B_KV + s * 8); };
  if (tid < 32) {
    if (elect()) {
#pragma unroll
      for (int i = 0; i < 7; i++) mbar_init(bars + B_X + i * 8, 1);
      asm volatile("fence.mbarrier_init.release.cluster;" ::: "memory");
#pragma unroll
      for (int i = 0; i < 7; i++) { mbar_expect_tx(bars + B_X + i * 8, 8192); tma3d(base + OFF_X + i * 16384 + 8192, &m_x, i * 64, rb * 128 + 64, 0, bars + B_X + i * 8); }
#pragma unroll
      for (int i = 0; i < 7; i++) { mbar_init(bars + B_KV + i * 8, 1); mbar_init(bars + B_X + 64 + i * 8, 1); }
      asm volatile("fence.mbarrier_init.release.cluster;" ::: "memory");
      load_kv(0);
#pragma unroll
      for (int i = 0; i < 7; i++) { mbar_expect_tx(bars + B_X + 64 + i * 8, 8192); tma3d(base + OFF_X + i * 16384, &m_x, i * 64, rb * 128, 0, bars + B_X + 64 + i * 8); }
      load_kv(1);
    }
  }
  const int warp = __shfl_sync(0xffffffffu, tid >> 5, 0);
  if (warp == 1) {
    if (elect()) {
#pragma unroll
      for (int i = 0; i < 36; i++) mbar_init(bars + i * 8, i < 16 ? 2 : 1);
      asm volatile("fence.mbarrier_init.release.cluster;" ::: "memory");
      if (smem_u32(smem_raw) != base) asm volatile("trap;");
    }
  }
  const int dt = b & 3, mt = b >> 2;
  const bool g1 = (b & 15) < 14;
  const int a1 = b - 2 * (b >> 4), ft = a1 >> 2, d1 = a1 & 3;
  const int g = lane >> 2, t = lane & 3, r8 = lane & 7, mi = lane >> 3;
  OBSG(FREQ && tid == 160, 128, 160);
  __syncthreads();
  if (warp >= 8) {
    asm volatile("setmaxnreg.dec.sync.aligned.u32 40;");
    const int pw = warp - 8;
    unsigned char* scr = p.scr;
    if (pw == 2) {
      mbar_wait(bars + B_X + 48, 0);
      if (b < 112 && lane < 28) asm volatile("prefetch.global.L2 [%0];" :: "l"(p.wqkv + (b * 4 + lane / 7) * 2688 + (lane % 7) * 128) : "memory");
      if (b < 98) asm volatile("prefetch.global.L2 [%0];" :: "l"(p.wo + b * 4096 + lane * 128) : "memory");
      if (lane == 31) asm volatile("prefetch.tensormap [%0];" :: "l"(&m_wq) : "memory");
      __syncwarp();
    }
    if (pw == 3) {
      mbar_wait(bars + B_X, 0);
      if (elect()) {
#pragma unroll 1
        for (int i = 2; i < 7; i++) load_kv(i);
      }
      __syncwarp();
    }
    {
      const int c0 = pw * 14 + (mi >> 1);
      unsigned char* dst = scr + (pw * HU_T + rb * 2 + (hp >> 2)) * BT + ((hp & 3) * 2 + (mi & 1)) * 1792 + (mi >> 1) * 128 + r8 * 16;
      const uint32_t xs = base + OFF_X + (hp * 16 + (lane & 15)) * 128;
      uint4 H[7];
      named_sync(9, 160);
#pragma unroll
      for (int i = 0; i < 7; i++) H[i] = lds128(xs + ((c0 + 2 * i) >> 3) * 16384 + ((((c0 + 2 * i) & 7) ^ r8) << 4));
      asm volatile("" :: "r"(H[6].w), "r"(H[0].x) : "memory");
      if (pw != 3) named_arrive(8, 384);
      else {
        named_sync(8, 384);
        if (elect()) {
          if (g1) asm volatile("red.relaxed.gpu.global.max.u32 [%0], %1;" :: "l"(scr + CNT_OFF + C_H * 128 + 8), "r"(gtime()) : "memory");
          load_wq(0, WQA, bars + B_WQ);
        }
        __syncwarp();
      }
      const uint2 st = lds64(base + OFF_LN + (lane & 15) * 8);
      const float sum = __uint_as_float(st.x), mean = sum * (1.0f / D_), var = ln_var(mean, __uint_as_float(st.y));
      const float m = rbf(mean), r = ln_rstd(var), r2 = ln_rstd(var * r * r);
      const float nc = fmaf(m, (float)D_, -sum) * (1.0f / D_) * (r * r2);
      const uint32_t m2 = pack2(m, m), r2x = pack2(r * r2, r * r2), nc2 = pack2(nc, nc);
      auto f = [&](uint32_t v) { return hfma2(hsub2(v, m2), r2x, nc2); };
#pragma unroll
      for (int i = 0; i < 7; i++) stg128(dst + i * 256, f(H[i].x), f(H[i].y), f(H[i].z), f(H[i].w));
      if (pw != 1) named_arrive(4, 128);
    }
    const int lane = lane_id();
    if (pw == 0) {
      if (elect()) {
        asm volatile("prefetch.tensormap [%0];" :: "l"(&m_w1) : "memory");
        asm volatile("prefetch.tensormap [%0];" :: "l"(&m_w2) : "memory");
        asm volatile("prefetch.tensormap [%0];" :: "l"(&m_res) : "memory");
      }
      __syncwarp();
      const uint32_t e = probe(scr + CNT_OFF + C_H * 128 + 4) + 1;
      sts32(bars + B_TAG, __uint_as_float((e & 0x3fffu) | ((e << 2) & 0x3fff0000u)));
      named_arrive(1, 96);
      if (g1) produce_box<64, 0>(base, 0, 32, &m_w1, ft * 64, 0);
      mbar_wait(bars + B_ATT, 0);
      if (elect()) { mbar_expect_tx(bars + B_RES, BT); tma3d(base + OFF_Q, &m_res, dt * 112, mt * 64, 0, bars + B_RES); }
      mbar_wait(bars + B_WO, 0);
      produce_lin<0>(base, 0, 7, scr + (dt * HU_T + 60) * BT, BT);
#pragma unroll 1
      for (int h = 0; h < 2; h++) produce_box<0, 8>(base, 7 + h * 14, 21 + h * 14, &m_w2, mt * 64, h * 8);
    } else if (pw == 1) {
      named_sync(4, 128);
      const unsigned char* hl = scr + (rb * 2 + (hp >> 2)) * BT + (hp & 3) * 3584 + min(lane, 27) * 128;
      settle(probe(hl) ^ probe(hl + HU_T * BT) ^ probe(hl + 2 * HU_T * BT) ^ probe(hl + 3 * HU_T * BT));
      publish(scr, C_H);
      OBS(lane == 0, 4);
      if (elect()) load_wq(WQA, 7, bars + B_WQ2);
      __syncwarp();
      if (g1) {
        __nanosleep(200);
        const uint32_t v = spin_ge(scr + (lane & 1) * 8, C_H, lane & 1 ? 0 : 128);
        if (lane == 1) sts32(bars + B_T0, __uint_as_float(v + TS));
        __syncwarp();
        OBS(lane == 0, 16);
        produce_lin<0>(base, 0, 32, scr + d1 * HU_T * BT, BT);
      }
      mbar_wait(bars + B_O, 0);
      produce_lin<0, B_OL>(base, 0, 7, scr + O_OFF + mt * 57344, 8192);
      const unsigned char* us = scr + (dt * HU_T + 32) * BT;
      mbar_wait(bars + B_EMPTY + 56, 0);
      if (elect()) mbar_expect_tx(bars + B_OL + 56, BT);
      __syncwarp();
      spin_ge(scr, C_U + dt, 28);
      if (elect()) bulk_g2s(base + 7 * SLOT + 8192, us, BT, bars + B_OL + 56);
      if (lane == 0) mbar_arrive(bars + B_U1);
      const uint32_t tu = clock();
      OBS(lane == 0, 18);
      produce_lin<UP, B_OL>(base, 8, 15, us + BT, BT, tu + UP);
      produce_lin<0, B_OL>(base, 15, 21, us + 8 * BT, BT);
      mbar_wait(bars + B_U2, 0);
      produce_lin<0>(base, 21, 35, us + 14 * BT, BT);
      unsigned tk = 0;
      if (lane == 0) tk = atomicAdd((unsigned*)(scr + CNT_OFF + C_TK * 128), 1u);
      if (__shfl_sync(0xffffffffu, tk, 0) == 127) {
#pragma unroll 1
        for (int i = lane; i < 160; i += 32) *(unsigned*)(scr + CNT_OFF + i * 128) = 0;
        *(unsigned*)(scr + CNT_OFF + C_H * 128 + 8) = 0;
        publish(scr + 4, C_H);
      }
    } else if (pw == 2) {
      uint32_t tn = clock();
      const unsigned char* src = p.w1 + b * 4096 + lane * 128;
#pragma unroll 1
      for (int i = 0; i < 28 + FREQ * 2; i++) {
        while ((int)(clock() - tn) < 0) __nanosleep(20);
        if (i == 14 || i == 21) src = p.w2 + ((b >> 3) * 16 + (b & 7) + (i & 1) * 8) * 4096 + lane * 128;
        if (i < 28) asm volatile("prefetch.global.L2 [%0];" :: "l"(src) : "memory");
        OBSG(FREQ && lane == 0, 129 + i, 161 + i);
        src += (i < 14 ? 128 : 256) * 4096;
        tn += i < 14 ? PACE1 : PACE2;
        if (i == 27) {
          mbar_wait(bars + B_U1, 0);
          spin_ge(scr, C_U + 4 + dt, 28);
          OBS(lane == 0, 11);
          if (lane == 0) mbar_arrive(bars + B_U2);
          __syncwarp();
        }
      }
    } else {
      if (b < 112) retile_wo(p.wo, scr, b, lane_id());
      const int lane = lane_id();
      unsigned char* hg = scr + HALO_OFF + (rb * 8 + hp) * 3584;
      named_sync(1, 96);
      const uint32_t tag = lds64(bars + B_TAG).x;
      if (rb < 15) {
#pragma unroll
        for (int q = 0; q < 7; q += 4) {
          uint4 v[4];
#pragma unroll
          for (int i = q; i < q + 4 && i < 7; i++) v[i - q] = lds128(base + OFF_K + 8 * 3584 + i * 512 + lane * 16 + (i * 32 + lane < 112 && !(lane & 7) ? 1792 : 0));
#pragma unroll
          for (int i = q; i < q + 4 && i < 7; i++) stg128(hg + i * 512 + lane * 16, (lane & 7) == (i * 32 + lane < 112) ? tag : v[i - q].x, v[i - q].y, v[i - q].z, v[i - q].w);
        }
        publish(scr, C_HALO + rb * 8 + hp);
      }
      OBS(lane == 0, 29);
      if (rb > 0) {
        spin_ge(scr, C_HALO + (rb - 1) * 8 + hp, 1);
        const uint32_t la = base + OFF_K + min(lane, 27) * 128;
#pragma unroll 1
        for (int n = 0;; n++) {
          if (elect()) { mbar_expect_tx(bars + B_HIN, 3584); bulk_g2s(base + OFF_K, hg - 8 * 3584, 3584, bars + B_HIN); }
          __syncwarp();
          mbar_wait(bars + B_HIN, n & 1);
          if (__all_sync(0xffffffffu, lds64(la + (lane < 14 ? 16 : 0)).x == tag)) break;
          if (n > 1000000) asm volatile("trap;");
        }
        if (lane < 14) { const uint4 v = lds128(la); sts128(la + 1792, v.x, v.y, v.z, v.w); }
      } else {
#pragma unroll
        for (int i = 0; i < 7; i++) sts128(base + OFF_K + i * 512 + lane * 16, 0, 0, 0, 0);
      }
      OBS(lane == 0, 12);
      smem_fence();
      __syncwarp();
      if (lane == 0) mbar_arrive(bars + B_HALO);
      __syncwarp();
      if (b < 112) {
        settle(probe(scr + (((b & 1) * 2 + (lane >> 4)) * HU_T + 60 + (b >> 4)) * BT + ((b >> 1) & 7) * 1792 + min(lane & 15, 13) * 128));
        publish(scr, C_WO);
      }
      mbar_wait(bars + (g1 ? B_GATE + 8 : B_ATT), 0);
      spin_ge(scr, C_WO, 112);
      if (lane == 0) mbar_arrive(bars + B_WO);
      mbar_wait(bars + B_ATT, 0);
      spin_ge(scr, C_O + (mt >> 1), 8);
      OBS(lane == 0, 17);
      if (lane == 0) mbar_arrive(bars + B_O);
      uint32_t ph = 0;
      auto check = [&](int it, int end, const unsigned char* src, uint32_t bytes, uint32_t a0, uint32_t a1) {
#pragma unroll 1
        for (int n = 0; it < end;) {
          const uint32_t s = it & 7, lb = bars + B_OL + s * 8, a = base + s * SLOT;
          mbar_wait(lb, (ph >> s) & 1);
          ph ^= 1 << s;
          uint32_t bad = (lds32(a + a0) ^ tag) | (lds32(a + a1) ^ tag);
          if (bytes == BT) bad |= (lds32(a + a0 + 512) ^ tag) | (lds32(a + a0 + 1024) ^ tag);
          if (__builtin_expect(__all_sync(0xffffffffu, !(bad & 1)), 1)) { mbar_arrive_if(lane == 0, bars + s * 8); it++; src += bytes; continue; }
          if (++n > 1000000) asm volatile("trap;");
          if (elect()) { mbar_expect_tx(lb, bytes); bulk_g2s(a + (bytes & 2048) * 4, src, bytes, lb); }
          __syncwarp();
        }
      };
      check(0, 7, scr + O_OFF + mt * 57344, 8192, lane * 132, lane * 132 + 4096);
      const uint32_t a = 8192 + (lane & 7) * 1792 + lane * 4;
      check(7, 21, scr + (dt * HU_T + 32) * BT, BT, a + (lane >> 3) * 128, a + (12 + ((lane >> 3) & 1)) * 128);
    }
  } else {
    asm volatile("setmaxnreg.inc.sync.aligned.u32 232;");
    const int wg = warp >> 2, w4 = warp & 3, th = wg ^ 1;
    const bool rel = (tid & 127) < 2;
    unsigned char* scr = p.scr;
    uint32_t X[28][4];
    float aq[28];
    const uint32_t dlo = (base >> 4) + (512u << 16) + (hp & 1), dlq = dlo + (OFF_WQ >> 4);
    {
      uint32_t xa[4];
#pragma unroll
      for (int k = 0; k < 4; k++) xa[k] = base + OFF_X + (th * 64 + w4 * 16 + (mi >> 1) * 8 + r8) * 128 + (((2 * k + (mi & 1)) ^ r8) << 4);
      float c0[2][4] = {}, c1[2][4] = {};
      uint32_t one[8];
#pragma unroll
      for (int j = 0; j < 8; j++) asm volatile("{\n.reg .u32 y;\nmov.u32 y, %%tid.y;\nmad.lo.u32 %0, y, %1, 0x3f803f80;\n}" : "=r"(one[j]) : "r"(lane + j));
      asm volatile("" : "+l"(scr));
      uint32_t ok = 0;
      const uint32_t bx = bars + B_X + wg * 64;
      {
#pragma unroll 1
        for (int n = 0; n < 64 && !ok; n++) { mma16816(c0[0], 0, 0, 0, 0, 0, 0); ok = mbar_try(bars + B_X, 0); }
        if (wg) ok = 0;
      }
#pragma unroll
      for (int i = 0; i < 8; i++) {
        if (i < 7) {
          if (!ok) mbar_wait(bx + i * 8, 0);
          OBS(tid == 64 && i == 0, 0); OBS(tid == 64 && i == 6, 15);
#pragma unroll
          for (int k = 0; k < 4; k++) ldsm4(X[i * 4 + k], xa[k] + i * 16384);
          if (i < 6) ok = mbar_try(bx + i * 8 + 8, 0);
        }
        if (i > 0) {
#pragma unroll
          for (int k = i * 4 - 4; k < i * 4; k++) {
            mma16816(c0[k & 1], X[k][0], one[(k & 1) * 4], X[k][1], one[(k & 1) * 4 + 1], X[k][0], X[k][1]);
            mma16816(c1[k & 1], X[k][2], one[(k & 1) * 4 + 2], X[k][3], one[(k & 1) * 4 + 3], X[k][2], X[k][3]);
          }
        }
      }
      float st[4];
#pragma unroll
      for (int j = 0; j < 2; j++) {
        st[j] = __shfl_sync(0xffffffffu, (g & 1) ? c0[0][2 * j + 1] + c0[1][2 * j + 1] : c0[0][2 * j] + c0[1][2 * j], (lane & 28) | (g >> 1));
        st[2 + j] = __shfl_sync(0xffffffffu, (g & 1) ? c1[0][2 * j + 1] + c1[1][2 * j + 1] : c1[0][2 * j] + c1[1][2 * j], (lane & 28) | (g >> 1));
      }
      named_arrive(8, 384);
      fence_code(20);
      named_arrive_if(wg, 0, 256);
      asm volatile("{\n.reg .pred q;\nsetp.ne.u32 q, %3, 0;\n@q st.shared.v2.f32 [%0], {%1,%2};\n@q bar.arrive 9, 160;\n}"
                   :: "r"(base + OFF_LN + ((t & 1) * 8 + g) * 8), "f"((t & 1) ? st[3] : st[1]), "f"((t & 1) ? st[2] : st[0]), "r"((uint32_t)((warp ^ 4) == hp)) : "memory");
      ok = mbar_try(bars + B_KV, 0);
      LnC l0, l1;
      float eps = 1e-5f;
#pragma unroll 1
      do {
        l0 = ln_consts(st[1], st[0], eps); l1 = ln_consts(st[3], st[2], eps);
#pragma unroll
        for (int k = 0; k < 16; k++) X[k >> 2][k & 3] = hsub2(X[k >> 2][k & 3], k & 2 ? l1.m : l0.m);
        eps += eps;
      } while ((l0.rl ^ l1.rl) == 4);
      OBS(tid == 32, 1);
      float ak[60], *av = ak + 32;
      auto norm = [&](int s) {
#pragma unroll
        for (int k = s * 4; k < s * 4 + 4; k++) {
          auto f = [&](uint32_t d, const LnC& l) { return s ? ln_apply(d, l) : hfma2(d, l.rh, hmul2(d, l.rl)); };
          const uint32_t y = f(X[k][1], l0);
          X[k][0] = f(X[k][0], l0); X[k][1] = f(X[k][2], l1); X[k][2] = y; X[k][3] = f(X[k][3], l1);
        }
      };
      const int pp_in = wg ? 6 : 0, pp_out = wg ? 0 : 6;
#pragma unroll
      for (int s = 0; s < 7; s++) {
        if (s != 1 || wg) norm(s);
        if (s == 0 && !wg) norm(1);
        if (__builtin_expect(!ok, 0)) { mbar_wait(bars + B_KV + s * 8, 0); if (s == 6) mbar_wait(bars + B_WQ, 0); }
        if (s == 0) fresh(ak);
        OBS(KOBS && (tid & 127) == 0, 40 + wg * 32 + s);
        if (wg ? s < 6 : s != 1) named_sync(pp_in, 256);
        OBS(KOBS && (tid & 127) == 32, 48 + wg * 32 + s);
        OBS(tid == 64 && s == 0, 2);
        wg_fence();
#pragma unroll
        for (int k = 0; k < 4; k++) {
          wgmma_rs_n120<1>(ak, X[s * 4 + k], mkdesc(HI_SW128, dlo + s * 1024 + k * 128), (s | k) != 0);
        }
        wg_commit();
        if (s == 6) {
          wg_wait<1>();
          if ((tid & 127) == 0) mbar_arrive(bars + B_EMPTY + 3 * 8);
          fresh(aq);
#pragma unroll
          for (int k = 0; k < 4; k++) {
            if (k == 2) named_arrive(pp_out, 256);
            wgmma_rs_n56<1>(aq, X[k], mkdesc(HI_SW128, dlq + k * 128), k);
          }
          wg_commit();
        }
        if (s < 6) named_arrive_if(wg ? s != 5 : s != 0, pp_out, 256);
        fence_code(s);
        OBS(KOBS && (tid & 127) == 64, 56 + wg * 32 + s);
        if (s < 6) ok = mbar_try(bars + B_KV + s * 8 + 8, 0);
        if (s == 5) ok &= mbar_try(bars + B_WQ, 0);
        OBS(tid == 64 && s == 5, 31);
        if (s > 0) wg_wait<1>();
        OBS(KOBS && (tid & 127) == 96, 64 + wg * 32 + s);
        if ((s == 2 || s == 3 || s == 5) && (tid & 127) == 0) mbar_arrive(bars + B_EMPTY + (s == 5 ? 2 : s - 2) * 8);
      }
      if ((tid & 127) == 0) mbar_arrive(bars + B_EMPTY + 4 * 8);
      OBS(tid == 32, 3);
      {
        const uint32_t kst = base + OFF_K + (2 + (warp ^ 4) * 2 + (mi & 1)) * 1792 + (mi >> 1) * 896 + r8 * 16;
#pragma unroll
        for (int n = 0; n < 7; n++)
          stsm4(kst + n * 128, pack2(ak[n * 4], ak[n * 4 + 1]), pack2(ak[n * 4 + 2], ak[n * 4 + 3]), pack2(av[n * 4], av[n * 4 + 1]), pack2(av[n * 4 + 2], av[n * 4 + 3]));
        named_arrive_if(warp == 3, 1, 96);
      }
      OBS(tid == 96, 32); OBS(tid == 224, 34);
      wg_wait<0>();
      if ((tid & 127) == 0) mbar_arrive(bars + B_EMPTY + 5 * 8);
      mbar_wait(bars + B_WQ2, 0);
    }
    const unsigned short *bp1 = (const unsigned short*)p.b1 + (g1 ? ft * 64 : 0) + w4 * 16 + g, *bp2 = (const unsigned short*)p.b2 + mt * 64 + w4 * 16 + g;
    const uint32_t braw[4] = {__ldg(bp1), __ldg(bp1 + 8), __ldg(bp2), __ldg(bp2 + 8)};
    auto q_rest = [&]() {
      wg_fence();
#pragma unroll
      for (int s = 1; s < 7; s++) {
#pragma unroll
        for (int k = s * 4; k < s * 4 + 4; k++) wgmma_rs_n56<1>(aq, X[k], mkdesc(HI_SW128, dlq + k * 128), 1);
        wg_commit();
        if (s == 5) { wg_wait<2>(); if ((tid & 127) == 0) mbar_arrive(bars + B_EMPTY + 6 * 8); }
      }
    };
    uint32_t Q[4][4];
    auto q_pack = [&]() {
#pragma unroll
      for (int n = 0; n < 14; n++) { const int m = n + 2 * (n > 7); Q[m >> 2][m & 3] = pack2(aq[n * 2], aq[n * 2 + 1]); }
#pragma unroll
      for (int h = 0; h < 2; h++) { Q[2][h] = t < 2 ? 0u : Q[1][2 + h]; Q[1][2 + h] = t < 2 ? Q[1][2 + h] : 0u; }
    };
    float acc[56];
    auto ai = [](int p) { return p < 4 ? 48 + (p & 1) * 4 + (p & 2) : (p - 4) * 4; };
    uint32_t xch, ts, tl;
    unsigned char *outp, *outq;
    auto setup_out = [&]() {
      xch = pin(base + OFF_K + (tid & 127) * 16);
      const uint32_t tb = base + OFF_K + 6144 + warp * 2560;
      ts = pin(tb + mi * 160 + r8 * 16); tl = pin(tb + t * 160 + g * 16);
      unsigned char* o = p.out + (mt * 64 + w4 * 16 + g) * 896 + dt * 224;
      outp = pin(o + th * 7168 + t * 16); outq = pin(o + (t >> 1) * 7168 + 192 + (t & 1) * 16);
    };
    auto give = [&](const float (&a)[56], int id) {
#pragma unroll
      for (int i = 0; i < 48; i += 16) sts128(xch + i * 128, pack2(a[i + 2], a[i + 3]), pack2(a[i + 6], a[i + 7]), pack2(a[i + 10], a[i + 11]), pack2(a[i + 14], a[i + 15]));
      named_arrive(id, 256);
    };
    auto take = [&](uint32_t (&r)[12], int id) {
      named_sync(id, 256);
#pragma unroll
      for (int i = 0; i < 3; i++) { const uint4 v = lds128(xch + i * 2048); r[i * 4] = v.x; r[i * 4 + 1] = v.y; r[i * 4 + 2] = v.z; r[i * 4 + 3] = v.w; }
    };
    float hv[32];
    auto keep_h = [&](int i) {
      const float hb0 = 0.5f * bf_lo(braw[i]), hb1 = 0.5f * bf_lo(braw[i + 1]);
#pragma unroll
      for (int j = 0; j < 32; j++) hv[j] = fmaf(acc[ai(j >> 1) + (j & 1)], 0.5f, j >= 4 && j < 8 ? hb1 : hb0);
    };
    auto take_h = [&](int i) {
      const float hb1 = 0.5f * bf_lo(braw[i + 1]);
      uint32_t r[12];
      take(r, 5);
#pragma unroll
      for (int j = 0; j < 12; j++) { hv[8 + 2 * j] = fmaf(bf_lo(r[j]), 0.5f, hb1); hv[9 + 2 * j] = fmaf(bf_hi(r[j]), 0.5f, hb1); }
    };
    uint4 Xr[4];
    auto get_x = [&]() {
      const uint32_t xr = base + OFF_Q + (w4 * 16 + g) * 224;
      mbar_wait(bars + B_RES, 0);
      Xr[0] = lds128(xr + (t >> 1) * 1792 + 192 + (t & 1) * 16);
#pragma unroll
      for (int i = 1; i < 4; i++) Xr[i] = lds128(xr + th * 1792 + t * 16 + (i - 1) * 64);
    };
    uint32_t Sv[16];
    auto gate = [&](int i) {
      uint32_t R[4];
#pragma unroll
      for (int q = 0; q < 4; q++) {
        const int j = i * 4 + q;
        const float h0 = hv[2 * j], h1 = hv[2 * j + 1];
        R[q] = hmul2(Sv[j], pack2(fmaf(h0, tanh_fast(h0), h0), fmaf(h1, tanh_fast(h1), h1)));
      }
      stsm4(ts + i * 640, R[0], R[1], R[2], R[3]);
    };
    auto leave = [&](int i) {
      __syncwarp();
      const uint4 v = lds128(tl + i * 640), x = Xr[i];
      stg128(i ? outp + (i - 1) * 64 : outq, hadd2(x.x, v.x), hadd2(x.y, v.y), hadd2(x.z, v.z), hadd2(x.w, v.w));
    };
    if (wg == 0) {
      named_sync(0, 256);
      OBS(tid == 96, 14);
      q_rest();
      named_arrive(6, 256);
      wg_wait<0>();
      if (tid == 0) mbar_arrive(bars + B_EMPTY + 7 * 8);
      q_pack();
      const uint32_t qst = base + OFF_Q + 8192 + (mi >> 1) * 1024 + (w4 * 16 + (mi & 1) * 8 + r8) * 16;
#pragma unroll
      for (int n = 0; n < 4; n++) stsm4(qst + n * 2048, Q[n][0], Q[n][1], Q[n][2], Q[n][3]);
      smem_fence();
      named_arrive(7, 256);
      OBS(tid == 32, 5);
      fresh(acc);
      if (g1) {
        unsigned char* ug = pin(scr + (d1 * HU_T + 32 + (ft >> 1)) * BT + ((ft & 1) * 4 + w4) * 1792 + lane * 4);
        unsigned char* ur = pin(ug + min(lane, 13) * 128);
        unsigned char* uc = pin(scr + d1 * 128);
        mbar_wait(bars, 0); mbar_wait(bars + 8, 0);
        const uint32_t utag = lds32(bars + B_TAG), um = pin(r8 == (ft & 1) * 4 + w4);
        {
          const uint32_t tg = lds64(bars + B_T0).x;
          while (tg - gtime() - 1 < 1000u);
        }
        named_sync(0, 256);
        gemm_issue<1>(acc, base >> 4, 0);
        OBS(tid == 0, 20);
        gemm_loop<1>(acc, base, 1, 32, rel, 40, 1, tid == 32 ? J1 : tid == 64 ? J2 : -1, bars + B_GATE - 8 + w4 * 8);
        wg_wait<0>();
        OBS(tid == 0, 21);
        named_arrive(5, 256);
        mbar_arrive_if(rel, bars + B_EMPTY + 7 * 8);
        auto gelu = [&](int n, int h) {
          const float hb = 0.5f * bf_lo(braw[h]);
          const float h0 = fmaf(acc[4 * n + 2 * h], 0.5f, hb), h1 = fmaf(acc[4 * n + 2 * h + 1], 0.5f, hb);
          const float t0 = tanh_fast(h0 * fmaf(h0 * h0, 0.2854192648f, 1.5957691216f)), t1 = tanh_fast(h1 * fmaf(h1 * h1, 0.2854192648f, 1.5957691216f));
          const uint32_t v = pack2(fmaf(h0, t0, h0), fmaf(h1, t1, h1));
          return h ? v : (v & ~um) | (utag & um);
        };
        auto done = [&](int h) {
          if (w4) named_arrive(13 + h, 128);
          else { named_sync(13 + h, 128); publish(uc, C_U + h * 4); OBS(tid == 0, h ? 13 : 9); }
          fence_code(10 + h);
        };
#pragma unroll
        for (int n = 0; n < 14; n++) { stg32(ug + n * 128, gelu(n, 0)); if (n == 6) fence_code(8); }
        done(0);
#pragma unroll
        for (int n = 0; n < 14; n++) { stg32(ug + 14 * BT + n * 128, gelu(n, 1)); if (n == 9) named_arrive(12, 256); if (n == 6 || n == 9) fence_code(60 + n); }
        settle(probe(ur + 14 * BT));
        done(1);
      } else if (tid == 32 || tid == 64) mbar_arrive(bars + B_GATE - 8 + w4 * 8);
      setup_out();
      get_x();
      uint32_t r[12];
      take(r, 3);
#pragma unroll
      for (int j = 0; j < 16; j++) Sv[j] = r[j < 4 ? 0 : j - 4];
      asm volatile("" :: "r"(r[0]), "r"(r[11]) : "memory");
      named_arrive(10, 256);
      take_h(2);
    } else {
      const uint32_t dq = ((base + OFF_Q) >> 4) + (64u << 16), dk = (base + OFF_K) >> 4;
      const bool odd = g & 1, early = 2 * t + (g & 1) > g;
      uint32_t selA[5], selB[4];
#pragma unroll
      for (int j = 0; j < 5; j++) { selA[j] = j == w4 + (early ? 0 : 1) ? (odd ? 0x1044u : 0x4410u) : 0x4444u; }
#pragma unroll
      for (int j = 0; j < 4; j++) { selB[j] = j == w4 ? (odd ? 0x3244u : 0x4432u) : 0x4444u; }
      float Sc[2][40], Op[2][2][16];
      uint32_t A[2][5][4];
      auto scores = [&](int T) {
        fresh(Sc[0]); fresh(Sc[1]);
#pragma unroll
        for (int k = 0; k < 2; k++) {
#pragma unroll
          for (int hh = 0; hh < 2; hh++)
            if (T) wgmma_n80<0, 0>(Sc[hh], mkdesc(8, dq + 512 + hh * 256 + k * 128), mkdesc(112, dk + (8u << 16) + 896 + hh * 24 + k * 16), k);
            else wgmma_rs_n80<0>(Sc[hh], Q[hh * 2 + k], mkdesc(112, dk + (8u << 16) + hh * 24 + k * 16), k);
        }
      };
      auto softmax = [&](int T) {
        uint32_t L[2][2];
        auto pick = [&](int w) {
#pragma unroll
          for (int hh = 0; hh < 2; hh++) {
            const float* q = Sc[hh] + w * 8;
            auto at = [&](int i) { return odd ? q[i + 1] : q[i]; };
            L[hh][0] = pack2(early ? at(0) : at(8), early ? at(6) : at(14)); L[hh][1] = pack2(at(4), at(10));
          }
          asm volatile("" ::: "memory");
        };
        if (w4 & 2) { if (w4 & 1) pick(3); else pick(2); } else { if (w4 & 1) pick(1); else pick(0); }
#pragma unroll
        for (int hh = 0; hh < 2; hh++) {
          uint32_t a = hfma2(L[hh][0], SC_HI, hmul2(L[hh][0], SC_LO)), c = hfma2(L[hh][1], SC_HI, hmul2(L[hh][1], SC_LO));
          if (T == 0 && w4 == 0 && rb == 0) { if (early) a = 0xce6ece6eu; c = (c & 0xffff0000u) | 0xce6eu; }
          uint32_t mx = hmax2(a, c);
          mx = hmax2(mx, __shfl_xor_sync(0xffffffffu, mx, 1));
          mx = hmax2(mx, __shfl_xor_sync(0xffffffffu, mx, 2));
          uint32_t pp[2];
#pragma unroll
          for (int h = 0; h < 2; h++) {
            const float m = h ? bf_hi(mx) : bf_lo(mx);
            const float p0 = ex2_fast(((h ? bf_hi(a) : bf_lo(a)) - m) * LOG2E), p1 = ex2_fast(((h ? bf_hi(c) : bf_lo(c)) - m) * LOG2E);
            float sm = p0 + p1;
            sm += __shfl_xor_sync(0xffffffffu, sm, 1);
            sm += __shfl_xor_sync(0xffffffffu, sm, 2);
            const float inv = rcp_fast(sm);
            pp[h] = pack2(p0 * inv, p1 * inv);
          }
#pragma unroll
          for (int j = 0; j < 5; j++) {
            A[hh][j][0] = place(pp[0], selA[j]); A[hh][j][1] = j ? place(pp[1], selB[j ? j - 1 : 0]) : 0u;
            A[hh][j][2] = j < 4 ? place(pp[0], selB[j & 3]) : 0u; A[hh][j][3] = place(pp[1], selA[j]);
          }
        }
      };
      auto values = [&](int T) {
        fresh(Op[T][0]); fresh(Op[T][1]);
#pragma unroll
        for (int j = 0; j < 5; j++)
#pragma unroll
          for (int hh = 0; hh < 2; hh++) {
            wgmma_rs_n32<1>(Op[T][hh], A[hh][j], mkdesc(8, dk + (112u << 16) + 56 + T * 896 + hh * 24 + j * 224), j);
          }
        wg_commit();
      };
      uint32_t Ob[2][14];
      auto pack = [&](int T) {
        const float (&O)[2][16] = Op[T];
#pragma unroll
        for (int n = 0; n < 7; n++)
#pragma unroll
          for (int h = 0; h < 2; h++) {
            if (n < 3) Ob[T][n * 2 + h] = pack2(O[0][n * 4 + 2 * h], O[0][n * 4 + 2 * h + 1]);
            else if (n == 3) Ob[T][n * 2 + h] = pack2(t < 2 ? O[0][12 + 2 * h] : O[1][2 * h], t < 2 ? O[0][13 + 2 * h] : O[1][2 * h + 1]);
            else Ob[T][n * 2 + h] = pack2(O[1][(n - 3) * 4 + 2 * h], O[1][(n - 3) * 4 + 2 * h + 1]);
          }
      };
      smem_fence();
      named_sync(6, 256);
      OBS(tid == 224, 26);
      q_rest();
      named_sync(7, 256);
      wg_fence();
      scores(1);
      wg_commit();
      named_arrive_if(g1, 0, 256);
      wg_wait<2>();
      if (tid == 128) mbar_arrive(bars + B_EMPTY + 7 * 8);
      wg_wait<0>();
      OBS(tid == 160, 10);
      softmax(1);
      q_pack();
      OBS(tid == 160, 30);
      mbar_wait(bars + B_HALO, 0);
      OBS(tid == 160, 7);
      mbar_wait(bars + B_GATE, 0);
      wg_fence();
      scores(0);
      values(1);
      wg_wait<0>();
      OBS(tid == 160, 33);
      unsigned char* og = scr + O_OFF + rb * 2 * 57344 + hp * 7168 + w4 * 256 + lane * 4;
      const uint32_t tag = lds32(bars + B_TAG), m0 = r8 == 2 * w4, m1 = r8 == 2 * w4 + 1;
      auto put = [&](int T) {
#pragma unroll
        for (int n = 0; n < 7; n++) {
          stg32(og + T * 57344 + n * 1024, (Ob[T][2 * n] & ~m0) | (tag & m0)); stg32(og + T * 57344 + n * 1024 + 128, (Ob[T][2 * n + 1] & ~m1) | (tag & m1));
          __nanosleep(20);
        }
      };
      pack(1); put(1);
      softmax(0);
      mbar_wait(bars + B_GATE + 8, 0);
      wg_fence();
      values(0);
      wg_wait<0>();
      OBS(tid == 160, 35);
      named_sync(11, 128);
      if (tid == 160) mbar_arrive(bars + B_ATT);
      pack(0); put(0);
      OBS(tid == 160, 28);
      named_sync(11, 128);
      if (warp == 4) publish(scr, C_O + rb);
      OBS(tid == 160, 8);
      setup_out();
      float as[56];
      if (g1) named_sync(5, 256);
      get_x();
      mbar_wait(bars, 0);
      if (g1) named_sync(12, 256);
      fresh(as);
      gemm_issue<0>(as, base >> 4, 0);
      OBS(tid == 128, 22);
      gemm_loop<0>(as, base, 1, 7, rel, 104);
      fresh(acc);
      mbar_wait(bars + 56, 0);
      gemm_issue<1>(acc, (base + 7 * SLOT) >> 4, 0);
      OBS(tid == 128, 24);
      wg_wait<1>();
      mbar_arrive_if(rel, bars + B_EMPTY + 6 * 8);
      give(as, 3);
#pragma unroll
      for (int j = 0; j < 16; j++) Sv[j] = pack2(as[ai(j)], as[ai(j) + 1]);
      gemm_loop<1>(acc, base, 8, 35, rel, 65);
      named_sync(10, 256);
      wg_wait<0>();
      OBS(tid == 128, 25);
      give(acc, 5);
      fence_code(31);
      keep_h(2);
      gate(0); leave(0);
    }
    {
#pragma unroll
      for (int i = 1; i < 4; i++) { gate(i); leave(i); }
      OBS(tid == 128, 27);
    }
  }
}

typedef CUresult (*EncFn)(CUtensorMap*, CUtensorMapDataType, cuuint32_t, void*, const cuuint64_t*, const cuuint64_t*, const cuuint32_t*,
                          const cuuint32_t*, CUtensorMapInterleave, CUtensorMapSwizzle, CUtensorMapL2promotion, CUtensorMapFloatOOBfill);
void enc(EncFn f, CUtensorMap* m, const void* ptr, cuuint64_t d0, cuuint64_t d1, cuuint64_t d2, cuuint64_t s1, cuuint64_t s2, cuuint32_t b1, cuuint32_t b2, cuuint32_t b0 = 64) {
  const cuuint64_t gd[3] = {d0, d1, d2}, gs[2] = {s1 * 2, s2 * 2};
  const cuuint32_t bx[3] = {b0, b1, b2}, es[3] = {1, 1, 1};
  f(m, CU_TENSOR_MAP_DATA_TYPE_BFLOAT16, 3, (void*)ptr, gd, gs, bx, es, CU_TENSOR_MAP_INTERLEAVE_NONE, b0 == 64 ? CU_TENSOR_MAP_SWIZZLE_128B : CU_TENSOR_MAP_SWIZZLE_NONE,
    CU_TENSOR_MAP_L2_PROMOTION_L2_128B, CU_TENSOR_MAP_FLOAT_OOB_FILL_NONE);
}
}

extern "C" void kernel_launch(void* const* d_in, const int* in_sizes, int n_in, void* d_out, int out_size) {
  (void)in_sizes; (void)n_in; (void)out_size;
  void* fp = nullptr;
  cudaDriverEntryPointQueryResult qr;
  cudaGetDriverEntryPoint("cuTensorMapEncodeTiled", &fp, cudaEnableDefault, &qr);
  EncFn f = (EncFn)fp;
  CUtensorMap m_x, m_wkv, m_wq, m_w1, m_w2, m_res;
  void* scr = nullptr;
  cudaGetSymbolAddress(&scr, g_scr);
  enc(f, &m_x, d_in[0], D_, S_, 1, D_, D_, 64, 1);
  enc(f, &m_wkv, d_in[1], D_, D_, 3, 3 * D_, D_, 64, 2);
  enc(f, &m_wq, d_in[1], D_, D_, 3, 3 * D_, D_, 64, 1);
  enc(f, &m_w1, d_in[4], F_, S_, 1, F_, F_, 64, 1);
  enc(f, &m_w2, d_in[6], S_, 16, F_ / 16, S_, 16 * S_, 8, 8);
  enc(f, &m_res, d_in[0], D_, S_, 1, D_, D_, 64, 1, 112);
  Params p;
  p.wqkv = (const unsigned char*)d_in[1]; p.wo = (const unsigned char*)d_in[2];
  p.w1 = (const unsigned char*)d_in[4]; p.b1 = (const unsigned char*)d_in[5];
  p.w2 = (const unsigned char*)d_in[6]; p.b2 = (const unsigned char*)d_in[7];
  p.out = (unsigned char*)d_out; p.scr = (unsigned char*)scr;
  cudaFuncSetAttribute(fused_kernel, cudaFuncAttributeMaxDynamicSharedMemorySize, SMEM_BYTES);
  fused_kernel<<<128, NTHREADS, SMEM_BYTES, cudaStreamPerThread>>>(m_x, m_wkv, m_wq, m_w1, m_w2, m_res, p);
}
```

```cpp
#include <cuda_runtime.h>
#include <cuda.h>
#include <cuda_bf16.h>
#include <stdint.h>

template<int TA, int TB> __device__ __forceinline__ void wgmma_n112(float (&d)[56], uint64_t da, uint64_t db, int sc) {
  asm volatile("{\n.reg .pred p;\nsetp.ne.b32 p, %58, 0;\n"
    "wgmma.mma_async.sync.aligned.m64n112k16.f32.bf16.bf16 {%0, %1, %2, %3, %4, %5, %6, %7, %8, %9, %10, %11, %12, %13, %14, %15, %16, %17, %18, %19, %20, %21, %22, %23, %24, %25, %26, %27, %28, %29, %30, %31, %32, %33, %34, %35, %36, %37, %38, %39, %40, %41, %42, %43, %44, %45, %46, %47, %48, %49, %50, %51, %52, %53, %54, %55}, %56, %57, p, 1, 1, %59, %60;\n}\n"
    : "+f"(d[0]), "+f"(d[1]), "+f"(d[2]), "+f"(d[3]), "+f"(d[4]), "+f"(d[5]), "+f"(d[6]), "+f"(d[7]), "+f"(d[8]), "+f"(d[9]), "+f"(d[10]), "+f"(d[11]), "+f"(d[12]), "+f"(d[13]), "+f"(d[14]), "+f"(d[15]), "+f"(d[16]), "+f"(d[17]), "+f"(d[18]), "+f"(d[19]), "+f"(d[20]), "+f"(d[21]), "+f"(d[22]), "+f"(d[23]), "+f"(d[24]), "+f"(d[25]), "+f"(d[26]), "+f"(d[27]), "+f"(d[28]), "+f"(d[29]), "+f"(d[30]), "+f"(d[31]), "+f"(d[32]), "+f"(d[33]), "+f"(d[34]), "+f"(d[35]), "+f"(d[36]), "+f"(d[37]), "+f"(d[38]), "+f"(d[39]), "+f"(d[40]), "+f"(d[41]), "+f"(d[42]), "+f"(d[43]), "+f"(d[44]), "+f"(d[45]), "+f"(d[46]), "+f"(d[47]), "+f"(d[48]), "+f"(d[49]), "+f"(d[50]), "+f"(d[51]), "+f"(d[52]), "+f"(d[53]), "+f"(d[54]), "+f"(d[55])
    : "l"(da), "l"(db), "r"(sc), "n"(TA), "n"(TB));
}

template<int TA, int TB> __device__ __forceinline__ void wgmma_n80(float (&d)[40], uint64_t da, uint64_t db, int sc) {
  asm volatile("{\n.reg .pred p;\nsetp.ne.b32 p, %42, 0;\n"
    "wgmma.mma_async.sync.aligned.m64n80k16.f32.bf16.bf16 {%0, %1, %2, %3, %4, %5, %6, %7, %8, %9, %10, %11, %12, %13, %14, %15, %16, %17, %18, %19, %20, %21, %22, %23, %24, %25, %26, %27, %28, %29, %30, %31, %32, %33, %34, %35, %36, %37, %38, %39}, %40, %41, p, 1, 1, %43, %44;\n}\n"
    : "+f"(d[0]), "+f"(d[1]), "+f"(d[2]), "+f"(d[3]), "+f"(d[4]), "+f"(d[5]), "+f"(d[6]), "+f"(d[7]), "+f"(d[8]), "+f"(d[9]), "+f"(d[10]), "+f"(d[11]), "+f"(d[12]), "+f"(d[13]), "+f"(d[14]), "+f"(d[15]), "+f"(d[16]), "+f"(d[17]), "+f"(d[18]), "+f"(d[19]), "+f"(d[20]), "+f"(d[21]), "+f"(d[22]), "+f"(d[23]), "+f"(d[24]), "+f"(d[25]), "+f"(d[26]), "+f"(d[27]), "+f"(d[28]), "+f"(d[29]), "+f"(d[30]), "+f"(d[31]), "+f"(d[32]), "+f"(d[33]), "+f"(d[34]), "+f"(d[35]), "+f"(d[36]), "+f"(d[37]), "+f"(d[38]), "+f"(d[39])
    : "l"(da), "l"(db), "r"(sc), "n"(TA), "n"(TB));
}

template<int TB> __device__ __forceinline__ void wgmma_rs_n120(float (&d)[60], const uint32_t (&a)[4], uint64_t db, int sc) {
  asm volatile("{\n.reg .pred p;\nsetp.ne.b32 p, %65, 0;\n"
    "wgmma.mma_async.sync.aligned.m64n120k16.f32.bf16.bf16 {%0, %1, %2, %3, %4, %5, %6, %7, %8, %9, %10, %11, %12, %13, %14, %15, %16, %17, %18, %19, %20, %21, %22, %23, %24, %25, %26, %27, %28, %29, %30, %31, %32, %33, %34, %35, %36, %37, %38, %39, %40, %41, %42, %43, %44, %45, %46, %47, %48, %49, %50, %51, %52, %53, %54, %55, %56, %57, %58, %59}, {%60, %61, %62, %63}, %64, p, 1, 1, %66;\n}\n"
    : "+f"(d[0]), "+f"(d[1]), "+f"(d[2]), "+f"(d[3]), "+f"(d[4]), "+f"(d[5]), "+f"(d[6]), "+f"(d[7]), "+f"(d[8]), "+f"(d[9]), "+f"(d[10]), "+f"(d[11]), "+f"(d[12]), "+f"(d[13]), "+f"(d[14]), "+f"(d[15]), "+f"(d[16]), "+f"(d[17]), "+f"(d[18]), "+f"(d[19]), "+f"(d[20]), "+f"(d[21]), "+f"(d[22]), "+f"(d[23]), "+f"(d[24]), "+f"(d[25]), "+f"(d[26]), "+f"(d[27]), "+f"(d[28]), "+f"(d[29]), "+f"(d[30]), "+f"(d[31]), "+f"(d[32]), "+f"(d[33]), "+f"(d[34]), "+f"(d[35]), "+f"(d[36]), "+f"(d[37]), "+f"(d[38]), "+f"(d[39]), "+f"(d[40]), "+f"(d[41]), "+f"(d[42]), "+f"(d[43]), "+f"(d[44]), "+f"(d[45]), "+f"(d[46]), "+f"(d[47]), "+f"(d[48]), "+f"(d[49]), "+f"(d[50]), "+f"(d[51]), "+f"(d[52]), "+f"(d[53]), "+f"(d[54]), "+f"(d[55]), "+f"(d[56]), "+f"(d[57]), "+f"(d[58]), "+f"(d[59])
    : "r"(a[0]), "r"(a[1]), "r"(a[2]), "r"(a[3]), "l"(db), "r"(sc), "n"(TB));
}

template<int TB> __device__ __forceinline__ void wgmma_rs_n56(float (&d)[28], const uint32_t (&a)[4], uint64_t db, int sc) {
  asm volatile("{\n.reg .pred p;\nsetp.ne.b32 p, %33, 0;\n"
    "wgmma.mma_async.sync.aligned.m64n56k16.f32.bf16.bf16 {%0, %1, %2, %3, %4, %5, %6, %7, %8, %9, %10, %11, %12, %13, %14, %15, %16, %17, %18, %19, %20, %21, %22, %23, %24, %25, %26, %27}, {%28, %29, %30, %31}, %32, p, 1, 1, %34;\n}\n"
    : "+f"(d[0]), "+f"(d[1]), "+f"(d[2]), "+f"(d[3]), "+f"(d[4]), "+f"(d[5]), "+f"(d[6]), "+f"(d[7]), "+f"(d[8]), "+f"(d[9]), "+f"(d[10]), "+f"(d[11]), "+f"(d[12]), "+f"(d[13]), "+f"(d[14]), "+f"(d[15]), "+f"(d[16]), "+f"(d[17]), "+f"(d[18]), "+f"(d[19]), "+f"(d[20]), "+f"(d[21]), "+f"(d[22]), "+f"(d[23]), "+f"(d[24]), "+f"(d[25]), "+f"(d[26]), "+f"(d[27])
    : "r"(a[0]), "r"(a[1]), "r"(a[2]), "r"(a[3]), "l"(db), "r"(sc), "n"(TB));
}

template<int TB> __device__ __forceinline__ void wgmma_rs_n32(float (&d)[16], const uint32_t (&a)[4], uint64_t db, int sc) {
  asm volatile("{\n.reg .pred p;\nsetp.ne.b32 p, %21, 0;\n"
    "wgmma.mma_async.sync.aligned.m64n32k16.f32.bf16.bf16 {%0, %1, %2, %3, %4, %5, %6, %7, %8, %9, %10, %11, %12, %13, %14, %15}, {%16, %17, %18, %19}, %20, p, 1, 1, %22;\n}\n"
    : "+f"(d[0]), "+f"(d[1]), "+f"(d[2]), "+f"(d[3]), "+f"(d[4]), "+f"(d[5]), "+f"(d[6]), "+f"(d[7]), "+f"(d[8]), "+f"(d[9]), "+f"(d[10]), "+f"(d[11]), "+f"(d[12]), "+f"(d[13]), "+f"(d[14]), "+f"(d[15])
    : "r"(a[0]), "r"(a[1]), "r"(a[2]), "r"(a[3]), "l"(db), "r"(sc), "n"(TB));
}

template<int TB> __device__ __forceinline__ void wgmma_rs_n80(float (&d)[40], const uint32_t (&a)[4], uint64_t db, int sc) {
  asm volatile("{\n.reg .pred p;\nsetp.ne.b32 p, %45, 0;\n"
    "wgmma.mma_async.sync.aligned.m64n80k16.f32.bf16.bf16 {%0, %1, %2, %3, %4, %5, %6, %7, %8, %9, %10, %11, %12, %13, %14, %15, %16, %17, %18, %19, %20, %21, %22, %23, %24, %25, %26, %27, %28, %29, %30, %31, %32, %33, %34, %35, %36, %37, %38, %39}, {%40, %41, %42, %43}, %44, p, 1, 1, %46;\n}\n"
    : "+f"(d[0]), "+f"(d[1]), "+f"(d[2]), "+f"(d[3]), "+f"(d[4]), "+f"(d[5]), "+f"(d[6]), "+f"(d[7]), "+f"(d[8]), "+f"(d[9]), "+f"(d[10]), "+f"(d[11]), "+f"(d[12]), "+f"(d[13]), "+f"(d[14]), "+f"(d[15]), "+f"(d[16]), "+f"(d[17]), "+f"(d[18]), "+f"(d[19]), "+f"(d[20]), "+f"(d[21]), "+f"(d[22]), "+f"(d[23]), "+f"(d[24]), "+f"(d[25]), "+f"(d[26]), "+f"(d[27]), "+f"(d[28]), "+f"(d[29]), "+f"(d[30]), "+f"(d[31]), "+f"(d[32]), "+f"(d[33]), "+f"(d[34]), "+f"(d[35]), "+f"(d[36]), "+f"(d[37]), "+f"(d[38]), "+f"(d[39])
    : "r"(a[0]), "r"(a[1]), "r"(a[2]), "r"(a[3]), "l"(db), "r"(sc), "n"(TB));
}

namespace {
constexpr int S_ = 2048, D_ = 448, F_ = 1792;
constexpr int NSLOT = 8, SLOT = 22528;
constexpr int OFF_X = 7 * 16384;
constexpr int OFF_WQ = 8 * 16384;
constexpr int OFF_Q = NSLOT * SLOT;
constexpr int OFF_K = OFF_Q + 16384;
constexpr int OFF_BAR = 14 * 16384;
constexpr int OFF_LN = OFF_BAR + 512;
constexpr int OFF_OBS = OFF_BAR + 640;
constexpr int SMEM_BYTES = OFF_OBS + 1024;
#define PACE1 540
#define PACE2 600
#define J1 6
#define J2 14
#define TS 3120
#define UP 170
#define WQA 4
#define SOBS 0
#define FREQ 0
#define KOBS 0
#define LANDOBS 0
#define OBS(c, i) do {} while (0)
#define OBSG(c, i, j) do {} while (0)
constexpr int NTHREADS = 384;
constexpr float LOG2E = 1.4426950408889634f;
constexpr uint32_t SC_HI = 0x3e423e42u, SC_LO = 0xb9f7b9f7u;
constexpr int BT = 14336;

constexpr int HU_T = 67;
constexpr int O_OFF = 4 * HU_T * BT;
constexpr int HALO_OFF = O_OFF + 32 * 7 * 8192;
constexpr int CNT_OFF = HALO_OFF + 128 * 3584;
constexpr int SCR_BYTES = CNT_OFF + 160 * 128;
constexpr int C_U = 0, C_O = 8, C_H = 24, C_WO = 25, C_TK = 26, C_HALO = 32;
__device__ __align__(1024) unsigned char g_scr[SCR_BYTES];

__device__ __forceinline__ uint32_t smem_u32(const void* p) { return (uint32_t)__cvta_generic_to_shared(p); }
__device__ __forceinline__ void mbar_init(uint32_t bar, uint32_t cnt) { asm volatile("mbarrier.init.shared::cta.b64 [%0], %1;" :: "r"(bar), "r"(cnt)); }
__device__ __forceinline__ void mbar_expect_tx(uint32_t bar, uint32_t bytes) { asm volatile("mbarrier.arrive.expect_tx.shared::cta.b64 _, [%0], %1;" :: "r"(bar), "r"(bytes) : "memory"); }
__device__ __forceinline__ void mbar_arrive_if(uint32_t c, uint32_t bar) { asm volatile("{\n.reg .pred q;\nsetp.ne.u32 q, %1, 0;\n@q mbarrier.arrive.shared::cta.b64 _, [%0];\n}" :: "r"(bar), "r"(c) : "memory"); }
__device__ __forceinline__ void mbar_arrive(uint32_t bar) { asm volatile("mbarrier.arrive.shared::cta.b64 _, [%0];" :: "r"(bar) : "memory"); }
__device__ __forceinline__ void mbar_wait(uint32_t bar, uint32_t parity) {
  asm volatile("{\n.reg .pred p;\n.reg .u32 n;\nmov.u32 n, 0;\nLAB_WAIT:\n"
               "mbarrier.try_wait.parity.shared::cta.b64 p, [%0], %1;\n@p bra DONE;\n"
               "add.u32 n, n, 1;\nsetp.lt.u32 p, n, 400000;\n@p bra LAB_WAIT;\ntrap;\nDONE:\n}" :: "r"(bar), "r"(parity) : "memory");
}
__device__ __forceinline__ uint32_t mbar_try(uint32_t bar, uint32_t parity) {
  uint32_t ok;
  asm volatile("{\n.reg .pred p;\nmbarrier.test_wait.parity.shared::cta.b64 p, [%1], %2;\nselp.u32 %0, 1, 0, p;\n}" : "=r"(ok) : "r"(bar), "r"(parity) : "memory");
  return ok;
}
__device__ __forceinline__ void tma3d(uint32_t dst, const CUtensorMap* m, int c0, int c1, int c2, uint32_t bar) {
  asm volatile("cp.async.bulk.tensor.3d.shared::cluster.global.mbarrier::complete_tx::bytes [%0], [%1, {%3, %4, %5}], [%2];"
               :: "r"(dst), "l"(m), "r"(bar), "r"(c0), "r"(c1), "r"(c2) : "memory");
}
__device__ __forceinline__ void bulk_g2s(uint32_t dst, const void* src, uint32_t bytes, uint32_t bar) {
  asm volatile("cp.async.bulk.shared::cluster.global.mbarrier::complete_tx::bytes [%0], [%1], %2, [%3];" :: "r"(dst), "l"(src), "r"(bytes), "r"(bar) : "memory");
}
__device__ __forceinline__ void wg_fence() { asm volatile("wgmma.fence.sync.aligned;" ::: "memory"); }
__device__ __forceinline__ void wg_commit() { asm volatile("wgmma.commit_group.sync.aligned;" ::: "memory"); }
template <int N> __device__ __forceinline__ void wg_wait() { asm volatile("wgmma.wait_group.sync.aligned %0;" :: "n"(N) : "memory"); }
__device__ __forceinline__ void smem_fence() { asm volatile("fence.proxy.async.shared::cta;" ::: "memory"); }
__device__ __forceinline__ void stg128(void* p, uint32_t a, uint32_t b, uint32_t c, uint32_t d) { asm volatile("st.global.v4.u32 [%0], {%1,%2,%3,%4};" :: "l"(p), "r"(a), "r"(b), "r"(c), "r"(d) : "memory"); }
__device__ __forceinline__ void stg32(void* p, uint32_t v) { asm volatile("st.global.u32 [%0], %1;" :: "l"(p), "r"(v) : "memory"); }
__device__ __forceinline__ uint4 ldg128(const void* p) { uint4 v; asm volatile("ld.global.nc.L1::no_allocate.v4.u32 {%0,%1,%2,%3}, [%4];" : "=r"(v.x), "=r"(v.y), "=r"(v.z), "=r"(v.w) : "l"(p)); return v; }
__device__ __forceinline__ void publish(unsigned char* scr, int i) {
  asm volatile("{\n.reg .pred q;\nelect.sync _|q, 0xffffffff;\n@q red.relaxed.gpu.global.inc.u32 [%0], 0xffffffff;\n}" :: "l"(scr + CNT_OFF + i * 128) : "memory");
}
__device__ __forceinline__ uint32_t probe(const unsigned char* p) { uint32_t v; asm volatile("ld.relaxed.gpu.global.u32 %0, [%1];" : "=r"(v) : "l"(p) : "memory"); return v; }
__device__ __forceinline__ void settle(uint32_t v) {
  asm volatile("{\n.reg .pred q;\nsetp.eq.u32 q, %0, 0x7fc1dead;\n@q st.volatile.shared.u32 [%1], %0;\n}" :: "r"(v), "r"(1024 + OFF_BAR + 376) : "memory");
  __syncwarp();
}
__device__ __forceinline__ uint32_t spin_ge(unsigned char* scr, int i, unsigned target) {
  uint32_t v;
  asm volatile("{\n.reg .pred p;\n.reg .u32 n;\nmov.u32 n, 0;\nLAB_SPIN:\n"
               "ld.relaxed.gpu.global.u32 %0, [%1];\nsetp.ge.u32 p, %0, %2;\nvote.sync.all.pred p, p, 0xffffffff;\n@p bra DONE;\n"
               "add.u32 n, n, 1;\nsetp.lt.u32 p, n, 4000000;\n@p bra LAB_SPIN;\ntrap;\nDONE:\n}" : "=&r"(v) : "l"(scr + CNT_OFF + i * 128), "r"(target) : "memory");
  return v;
}
__device__ __forceinline__ int lane_id() { int l; asm volatile("mov.u32 %0, %%laneid;" : "=r"(l)); return l; }
__device__ __forceinline__ uint32_t pin(uint32_t v) { return __shfl_xor_sync(0xffffffffu, v, blockIdx.y); }
__device__ __forceinline__ unsigned char* pin(unsigned char* p) { return (unsigned char*)(((uint64_t)pin((uint32_t)((uint64_t)p >> 32)) << 32) | pin((uint32_t)(uint64_t)p)); }
__device__ __forceinline__ uint32_t gtime() { uint32_t g; asm volatile("mov.u32 %0, %%globaltimer_lo;" : "=r"(g)); return g; }
__device__ __forceinline__ bool elect() {
  uint32_t r; asm volatile("{\n.reg .pred p;\nelect.sync _|p, 0xffffffff;\nselp.u32 %0, 1, 0, p;\n}" : "=r"(r)); return r != 0;
}
__device__ __forceinline__ uint4 lds128(uint32_t a) { uint4 v; asm volatile("ld.shared.v4.u32 {%0,%1,%2,%3}, [%4];" : "=r"(v.x), "=r"(v.y), "=r"(v.z), "=r"(v.w) : "r"(a) : "memory"); return v; }
__device__ __forceinline__ uint32_t lds32(uint32_t a) { uint32_t v; asm volatile("ld.shared.u32 %0, [%1];" : "=r"(v) : "r"(a) : "memory"); return v; }
__device__ __forceinline__ uint2 lds64(uint32_t a) { uint2 v; asm volatile("ld.shared.v2.u32 {%0,%1}, [%2];" : "=r"(v.x), "=r"(v.y) : "r"(a) : "memory"); return v; }
__device__ __forceinline__ void sts128(uint32_t p, uint32_t a, uint32_t b, uint32_t c, uint32_t d) { asm volatile("st.shared.v4.u32 [%0], {%1,%2,%3,%4};" :: "r"(p), "r"(a), "r"(b), "r"(c), "r"(d) : "memory"); }
__device__ __forceinline__ void sts32(uint32_t a, float v) { asm volatile("st.shared.f32 [%0], %1;" :: "r"(a), "f"(v) : "memory"); }
__device__ __forceinline__ void named_sync(int id, int n) { asm volatile("bar.sync %0, %1;" :: "r"(id), "r"(n) : "memory"); }
__device__ __forceinline__ void named_arrive(int id, int n) { asm volatile("bar.arrive %0, %1;" :: "r"(id), "r"(n) : "memory"); }
__device__ __forceinline__ void named_arrive_if(uint32_t c, int id, int n) { asm volatile("{\n.reg .pred q;\nsetp.ne.u32 q, %2, 0;\n@q bar.arrive %0, %1;\n}" :: "r"(id), "r"(n), "r"(c) : "memory"); }
__device__ __forceinline__ uint64_t mkdesc(uint32_t hi, uint32_t lo) { return ((uint64_t)hi << 32) | lo; }
constexpr uint32_t HI_SW128 = 0x40000040u;
__device__ __forceinline__ uint32_t pack2(float lo, float hi) { uint32_t r; asm("cvt.rn.bf16x2.f32 %0, %1, %2;" : "=r"(r) : "f"(hi), "f"(lo)); return r; }
__device__ __forceinline__ float bf_lo(uint32_t v) { return __uint_as_float(v << 16); }
__device__ __forceinline__ float bf_hi(uint32_t v) { return __uint_as_float(v & 0xffff0000u); }
__device__ __forceinline__ float rbf(float x) { return bf_lo(pack2(x, 0.f)); }
__device__ __forceinline__ uint32_t hsub2(uint32_t a, uint32_t b) { uint32_t r; asm("sub.rn.bf16x2 %0, %1, %2;" : "=r"(r) : "r"(a), "r"(b)); return r; }
__device__ __forceinline__ uint32_t hadd2(uint32_t a, uint32_t b) { uint32_t r; asm("add.rn.bf16x2 %0, %1, %2;" : "=r"(r) : "r"(a), "r"(b)); return r; }
__device__ __forceinline__ uint32_t place(uint32_t v, uint32_t sel) { uint32_t r; asm volatile("prmt.b32 %0, %1, 0, %2;" : "=r"(r) : "r"(v), "r"(sel)); return r; }
__device__ __forceinline__ uint32_t hmax2(uint32_t a, uint32_t b) { uint32_t r; asm("max.bf16x2 %0, %1, %2;" : "=r"(r) : "r"(a), "r"(b)); return r; }
__device__ __forceinline__ uint32_t hmul2(uint32_t a, uint32_t b) { uint32_t r; asm("mul.rn.bf16x2 %0, %1, %2;" : "=r"(r) : "r"(a), "r"(b)); return r; }
__device__ __forceinline__ uint32_t hfma2(uint32_t a, uint32_t b, uint32_t c) { uint32_t r; asm("fma.rn.bf16x2 %0, %1, %2, %3;" : "=r"(r) : "r"(a), "r"(b), "r"(c)); return r; }
__device__ __forceinline__ float tanh_fast(float x) { float r; asm("tanh.approx.f32 %0, %1;" : "=f"(r) : "f"(x)); return r; }
__device__ __forceinline__ float rcp_fast(float x) { float r; asm("rcp.approx.ftz.f32 %0, %1;" : "=f"(r) : "f"(x)); return r; }
__device__ __forceinline__ float ex2_fast(float x) { float r; asm("ex2.approx.ftz.f32 %0, %1;" : "=f"(r) : "f"(x)); return r; }
__device__ __forceinline__ void mma16816(float (&c)[4], uint32_t a0, uint32_t a1, uint32_t a2, uint32_t a3, uint32_t b0, uint32_t b1) {
  asm volatile("mma.sync.aligned.m16n8k16.row.col.f32.bf16.bf16.f32 {%0,%1,%2,%3}, {%4,%5,%6,%7}, {%8,%9}, {%0,%1,%2,%3};"
               : "+f"(c[0]), "+f"(c[1]), "+f"(c[2]), "+f"(c[3]) : "r"(a0), "r"(a1), "r"(a2), "r"(a3), "r"(b0), "r"(b1));
}
__device__ __forceinline__ void ldsm4(uint32_t (&r)[4], uint32_t addr) {
  asm volatile("ldmatrix.sync.aligned.m8n8.x4.shared.b16 {%0,%1,%2,%3}, [%4];" : "=r"(r[0]), "=r"(r[1]), "=r"(r[2]), "=r"(r[3]) : "r"(addr) : "memory");
}
__device__ __forceinline__ void stsm4(uint32_t addr, uint32_t a, uint32_t b, uint32_t c, uint32_t d) {
  asm volatile("stmatrix.sync.aligned.m8n8.x4.shared.b16 [%0], {%1,%2,%3,%4};" :: "r"(addr), "r"(a), "r"(b), "r"(c), "r"(d) : "memory");
}

__device__ __forceinline__ float ln_rstd(float var, float eps = 1e-5f) {
  float sd;
  asm("sqrt.approx.ftz.f32 %0, %1;" : "=f"(sd) : "f"(rbf(rbf(var) + eps)));
  return rcp_fast(rbf(sd));
}
__device__ __forceinline__ float ln_var(float mean, float sq) { return fmaxf(fmaf(-mean, mean, sq * (1.0f / D_)), 0.f); }
struct LnC { uint32_t m, rh, rl; };
__device__ __forceinline__ LnC ln_consts(float sum, float sq, float eps) {
  const float mean = sum * (1.0f / D_), r = ln_rstd(ln_var(mean, sq), eps), rh = rbf(r);
  LnC c; c.m = pack2(mean, mean); c.rh = pack2(rh, rh); c.rl = pack2(r - rh, r - rh);
  return c;
}
__device__ __forceinline__ uint32_t ln_apply(uint32_t x, const LnC& c) {
  uint32_t d = hsub2(x, c.m);
  return hfma2(d, c.rh, hmul2(d, c.rl));
}

__device__ __forceinline__ void fence_code(int id) {
  asm volatile("{\n.reg .pred q;\nLAB_F:\nsetp.eq.u32 q, %0, %1;\n@q st.volatile.shared.u32 [%2], %2;\n@q bra LAB_F;\n}" :: "r"(blockIdx.x), "r"(0x70000000 + id), "r"(0) : "memory");
}
template <int N> __device__ __forceinline__ void fresh(float (&a)[N]) {
#pragma unroll
  for (int i = 0; i < N; i++) asm volatile("" : "=f"(a[i]));
}
constexpr int B_EMPTY = 64, B_U1 = 128, B_U2 = 136, B_WQ = 144, B_WQ2 = 152, B_HIN = 160, B_HALO = 168, B_GATE = 176, B_ATT = 192, B_RES = 200, B_WO = 208, B_O = 216;
constexpr int B_OL = 224, B_KV = 296, B_TAG = 360, B_T0 = 368, B_X = 384;

template <int TA>
__device__ __forceinline__ void gemm_issue(float (&acc)[56], uint32_t lo, int sc) {
  wg_fence();
#pragma unroll
  for (int k = 0; k < 4; k++)
    wgmma_n112<TA, 1>(acc, mkdesc(TA ? HI_SW128 : 8, lo + (TA ? 512u << 16 : 64u << 16) + k * 128), mkdesc(8, lo + (112u << 16) + 512 + k * 224), sc | k);
  wg_commit();
}
template <int TA>
__device__ __forceinline__ void gemm_loop(float (&acc)[56], uint32_t base, int it, int end, bool rel, int oi, uint32_t ok = 0, int gate_it = -1, uint32_t gate = 0) {
#pragma unroll 1
  for (; it < end;) {
    if (__builtin_expect(!ok, 0)) mbar_wait(base + OFF_BAR + (it & 7) * 8, (it >> 3) & 1);
    gemm_issue<TA>(acc, (base >> 4) + (it & 7) * (SLOT >> 4), 1);
    OBS(SOBS && rel, oi + it);
    it++;
    ok = mbar_try(base + OFF_BAR + (it & 7) * 8, (it >> 3) & 1);
    wg_wait<1>();
    if (rel || it == gate_it) mbar_arrive(rel ? base + OFF_BAR + B_EMPTY + ((it - 2) & 7) * 8 : gate);
  }
}
template <int S1, int S2>
__device__ __forceinline__ void produce_box(uint32_t base, int it, int end, const CUtensorMap* mp, int c0, int c1) {
#pragma unroll 1
  for (int c2 = 0; it < end; it++, c1 += S1, c2 += S2) {
    const uint32_t fb = base + OFF_BAR + (it & 7) * 8;
    mbar_wait(fb + B_EMPTY, (it >> 3) & 1);
    if (elect()) { mbar_expect_tx(fb, 8192); tma3d(base + (it & 7) * SLOT, mp, c0, c1, c2, fb); }
  }
}
template <int PER, int LAND = 0>
__device__ __forceinline__ void produce_lin(uint32_t base, int it, int end, const unsigned char* src, uint32_t bytes, uint32_t tn = 0) {
#pragma unroll 1
  for (; it < end; it++) {
    const uint32_t fb = base + OFF_BAR + (it & 7) * 8;
    mbar_wait(fb + B_EMPTY, (it >> 3) & 1);
    if (PER) { while ((int)(clock() - tn) < 0); tn += PER; }
    if (elect()) { mbar_expect_tx(fb + LAND, bytes); bulk_g2s(base + (it & 7) * SLOT + (bytes & 2048) * 4, src, bytes, fb + LAND); }
    src += bytes;
  }
}

__device__ __forceinline__ void retile_wo(const unsigned char* wo, unsigned char* scr, int u, int lane) {
  const int r8 = lane & 7, mi = lane >> 3;
  const unsigned char* src = wo + ((u >> 1) * 8 + r8) * 896 + ((u & 1) * 28 + mi) * 16;
  unsigned char* dst = scr + ((u & 1) * 2 * HU_T + 60 + (u >> 4)) * BT + ((u >> 1) & 7) * 1792 + mi * 128 + r8 * 16;
  uint4 v[7];
#pragma unroll
  for (int i = 0; i < 7; i++) v[i] = ldg128(src + i * 64);
#pragma unroll
  for (int i = 0; i < 7; i++) stg128(dst + i * 512 + ((i * 4 + mi) / 14) * (HU_T * BT - 1792), v[i].x, v[i].y, v[i].z, v[i].w);
}

struct Params {
  const unsigned char *wqkv, *wo, *w1, *b1, *w2, *b2;
  unsigned char *out, *scr;
};

__global__ void __launch_bounds__(NTHREADS, 1)
fused_kernel(const __grid_constant__ CUtensorMap m_x, const __grid_constant__ CUtensorMap m_wkv, const __grid_constant__ CUtensorMap m_wq,
             const __grid_constant__ CUtensorMap m_w1, const __grid_constant__ CUtensorMap m_w2, const __grid_constant__ CUtensorMap m_res, const Params p) {
  extern __shared__ __align__(1024) unsigned char smem_raw[];
  constexpr uint32_t base = 1024, bars = base + OFF_BAR;
  const int tid = threadIdx.x, lane = tid & 31, b = blockIdx.x;
  const int rb = (b >> 2) & 15, hp = ((b >> 6) << 2) | (b & 3);
  const int wcol = hp * 56 - (hp & 1) * 8;
  auto load_wq = [&](int s0, int s1, uint32_t bar) {
    mbar_expect_tx(bar, (s1 - s0) * 8192);
#pragma unroll 1
    for (int s = s0; s < s1; s++) tma3d(base + OFF_WQ + s * 8192, &m_wq, wcol, s * 64, 0, bar);
  };
  auto load_kv = [&](int s) { mbar_expect_tx(bars + B_KV + s * 8, 16384); tma3d(base + s * 16384, &m_wkv, wcol, s * 64, 1, bars + B_KV + s * 8); };
  if (tid < 32) {
    if (elect()) {
      asm volatile("prefetch.tensormap [%0];" :: "l"(&m_x) : "memory");
#pragma unroll
      for (int i = 0; i < 7; i++) mbar_init(bars + B_X + i * 8, 1);
      asm volatile("fence.mbarrier_init.release.cluster;" ::: "memory");
#pragma unroll
      for (int i = 0; i < 7; i++) { mbar_expect_tx(bars + B_X + i * 8, 8192); tma3d(base + OFF_X + i * 16384 + 8192, &m_x, i * 64, rb * 128 + 64, 0, bars + B_X + i * 8); }
#pragma unroll
      for (int i = 0; i < 7; i++) { mbar_init(bars + B_KV + i * 8, 1); mbar_init(bars + B_X + 64 + i * 8, 1); }
      asm volatile("fence.mbarrier_init.release.cluster;" ::: "memory");
      load_kv(0);
#pragma unroll
      for (int i = 0; i < 7; i++) { mbar_expect_tx(bars + B_X + 64 + i * 8, 8192); tma3d(base + OFF_X + i * 16384, &m_x, i * 64, rb * 128, 0, bars + B_X + 64 + i * 8); }
      load_kv(1);
    }
  }
  const int warp = __shfl_sync(0xffffffffu, tid >> 5, 0);
  if (warp == 1) {
    if (elect()) {
#pragma unroll
      for (int i = 0; i < 36; i++) mbar_init(bars + i * 8, i < 16 ? 2 : 1);
      asm volatile("fence.mbarrier_init.release.cluster;" ::: "memory");
      if (smem_u32(smem_raw) != base) asm volatile("trap;");
    }
  }
  const int dt = b & 3, mt = b >> 2;
  const bool g1 = (b & 15) < 14;
  const int a1 = b - 2 * (b >> 4), ft = a1 >> 2, d1 = a1 & 3;
  const int g = lane >> 2, t = lane & 3, r8 = lane & 7, mi = lane >> 3;
  OBSG(FREQ && tid == 160, 128, 160);
  __syncthreads();
  if (warp >= 8) {
    asm volatile("setmaxnreg.dec.sync.aligned.u32 40;");
    const int pw = warp - 8;
    unsigned char* scr = p.scr;
    if (pw == 2) {
      mbar_wait(bars + B_X + 80, 0);
      if (b < 112 && lane < 28) asm volatile("prefetch.global.L2 [%0];" :: "l"(p.wqkv + (b * 4 + lane / 7) * 2688 + (lane % 7) * 128) : "memory");
      if (b < 98) asm volatile("prefetch.global.L2 [%0];" :: "l"(p.wo + b * 4096 + lane * 128) : "memory");
      if (lane == 31) asm volatile("prefetch.tensormap [%0];" :: "l"(&m_wq) : "memory");
      __syncwarp();
    }
    if (pw == 3) {
      mbar_wait(bars + B_X, 0);
      if (elect()) {
#pragma unroll 1
        for (int i = 2; i < 7; i++) load_kv(i);
      }
      __syncwarp();
    }
    {
      const int c0 = pw * 14 + (mi >> 1);
      unsigned char* dst = scr + (pw * HU_T + rb * 2 + (hp >> 2)) * BT + ((hp & 3) * 2 + (mi & 1)) * 1792 + (mi >> 1) * 128 + r8 * 16;
      const uint32_t xs = base + OFF_X + (hp * 16 + (lane & 15)) * 128;
      uint4 H[7];
      named_sync(9, 160);
#pragma unroll
      for (int i = 0; i < 7; i++) H[i] = lds128(xs + ((c0 + 2 * i) >> 3) * 16384 + ((((c0 + 2 * i) & 7) ^ r8) << 4));
      asm volatile("" :: "r"(H[6].w), "r"(H[0].x) : "memory");
      if (pw != 3) named_arrive(8, 384);
      else {
        named_sync(8, 384);
        if (elect()) {
          if (g1) asm volatile("red.relaxed.gpu.global.max.u32 [%0], %1;" :: "l"(scr + CNT_OFF + C_H * 128 + 8), "r"(gtime()) : "memory");
          load_wq(0, WQA, bars + B_WQ);
        }
        __syncwarp();
      }
      const uint2 st = lds64(base + OFF_LN + (lane & 15) * 8);
      const float sum = __uint_as_float(st.x), mean = sum * (1.0f / D_), var = ln_var(mean, __uint_as_float(st.y));
      const float m = rbf(mean), r = ln_rstd(var), r2 = ln_rstd(var * r * r);
      const float nc = fmaf(m, (float)D_, -sum) * (1.0f / D_) * (r * r2);
      const uint32_t m2 = pack2(m, m), r2x = pack2(r * r2, r * r2), nc2 = pack2(nc, nc);
      auto f = [&](uint32_t v) { return hfma2(hsub2(v, m2), r2x, nc2); };
#pragma unroll
      for (int i = 0; i < 7; i++) stg128(dst + i * 256, f(H[i].x), f(H[i].y), f(H[i].z), f(H[i].w));
      if (pw != 1) named_arrive(4, 128);
    }
    const int lane = lane_id();
    if (pw == 0) {
      if (elect()) {
        asm volatile("prefetch.tensormap [%0];" :: "l"(&m_w1) : "memory");
        asm volatile("prefetch.tensormap [%0];" :: "l"(&m_w2) : "memory");
        asm volatile("prefetch.tensormap [%0];" :: "l"(&m_res) : "memory");
      }
      __syncwarp();
      const uint32_t e = probe(scr + CNT_OFF + C_H * 128 + 4) + 1;
      sts32(bars + B_TAG, __uint_as_float((e & 0x3fffu) | ((e << 2) & 0x3fff0000u)));
      named_arrive(1, 96);
      if (g1) produce_box<64, 0>(base, 0, 32, &m_w1, ft * 64, 0);
      mbar_wait(bars + B_ATT, 0);
      if (elect()) { mbar_expect_tx(bars + B_RES, BT); tma3d(base + OFF_Q, &m_res, dt * 112, mt * 64, 0, bars + B_RES); }
      mbar_wait(bars + B_WO, 0);
      produce_lin<0>(base, 0, 7, scr + (dt * HU_T + 60) * BT, BT);
#pragma unroll 1
      for (int h = 0; h < 2; h++) produce_box<0, 8>(base, 7 + h * 14, 21 + h * 14, &m_w2, mt * 64, h * 8);
    } else if (pw == 1) {
      named_sync(4, 128);
      const unsigned char* hl = scr + (rb * 2 + (hp >> 2)) * BT + (hp & 3) * 3584 + min(lane, 27) * 128;
      settle(probe(hl) ^ probe(hl + HU_T * BT) ^ probe(hl + 2 * HU_T * BT) ^ probe(hl + 3 * HU_T * BT));
      publish(scr, C_H);
      OBS(lane == 0, 4);
      if (elect()) load_wq(WQA, 7, bars + B_WQ2);
      __syncwarp();
      if (g1) {
        __nanosleep(200);
        const uint32_t v = spin_ge(scr + (lane & 1) * 8, C_H, lane & 1 ? 0 : 128);
        if (lane == 1) sts32(bars + B_T0, __uint_as_float(v + TS));
        __syncwarp();
        OBS(lane == 0, 16);
        produce_lin<0>(base, 0, 32, scr + d1 * HU_T * BT, BT);
      }
      mbar_wait(bars + B_O, 0);
      produce_lin<0, B_OL>(base, 0, 7, scr + O_OFF + mt * 57344, 8192);
      const unsigned char* us = scr + (dt * HU_T + 32) * BT;
      mbar_wait(bars + B_EMPTY + 56, 0);
      if (elect()) mbar_expect_tx(bars + B_OL + 56, BT);
      __syncwarp();
      spin_ge(scr, C_U + dt, 28);
      if (elect()) bulk_g2s(base + 7 * SLOT + 8192, us, BT, bars + B_OL + 56);
      if (lane == 0) mbar_arrive(bars + B_U1);
      const uint32_t tu = clock();
      OBS(lane == 0, 18);
      produce_lin<UP, B_OL>(base, 8, 15, us + BT, BT, tu + UP);
      produce_lin<0, B_OL>(base, 15, 21, us + 8 * BT, BT);
      mbar_wait(bars + B_U2, 0);
      produce_lin<0>(base, 21, 35, us + 14 * BT, BT);
      unsigned tk = 0;
      if (lane == 0) tk = atomicAdd((unsigned*)(scr + CNT_OFF + C_TK * 128), 1u);
      if (__shfl_sync(0xffffffffu, tk, 0) == 127) {
#pragma unroll 1
        for (int i = lane; i < 160; i += 32) *(unsigned*)(scr + CNT_OFF + i * 128) = 0;
        *(unsigned*)(scr + CNT_OFF + C_H * 128 + 8) = 0;
        publish(scr + 4, C_H);
      }
    } else if (pw == 2) {
      uint32_t tn = clock();
      const unsigned char* src = p.w1 + b * 4096 + lane * 128;
#pragma unroll 1
      for (int i = 0; i < 28 + FREQ * 2; i++) {
        while ((int)(clock() - tn) < 0) __nanosleep(20);
        if (i == 14 || i == 21) src = p.w2 + ((b >> 3) * 16 + (b & 7) + (i & 1) * 8) * 4096 + lane * 128;
        if (i < 28) asm volatile("prefetch.global.L2 [%0];" :: "l"(src) : "memory");
        OBSG(FREQ && lane == 0, 129 + i, 161 + i);
        src += (i < 14 ? 128 : 256) * 4096;
        tn += i < 14 ? PACE1 : PACE2;
        if (i == 27) {
          mbar_wait(bars + B_U1, 0);
          spin_ge(scr, C_U + 4 + dt, 28);
          OBS(lane == 0, 11);
          if (lane == 0) mbar_arrive(bars + B_U2);
          __syncwarp();
        }
      }
    } else {
      if (b < 112) retile_wo(p.wo, scr, b, lane_id());
      const int lane = lane_id();
      unsigned char* hg = scr + HALO_OFF + (rb * 8 + hp) * 3584;
      named_sync(1, 96);
      const uint32_t tag = lds64(bars + B_TAG).x;
      if (rb < 15) {
#pragma unroll
        for (int q = 0; q < 7; q += 4) {
          uint4 v[4];
#pragma unroll
          for (int i = q; i < q + 4 && i < 7; i++) v[i - q] = lds128(base + OFF_K + 8 * 3584 + i * 512 + lane * 16 + (i * 32 + lane < 112 && !(lane & 7) ? 1792 : 0));
#pragma unroll
          for (int i = q; i < q + 4 && i < 7; i++) stg128(hg + i * 512 + lane * 16, (lane & 7) == (i * 32 + lane < 112) ? tag : v[i - q].x, v[i - q].y, v[i - q].z, v[i - q].w);
        }
        publish(scr, C_HALO + rb * 8 + hp);
      }
      OBS(lane == 0, 29);
      int nh = -1;
      if (rb > 0) {
        spin_ge(scr, C_HALO + (rb - 1) * 8 + hp, 1);
        const uint32_t la = base + OFF_K + min(lane, 27) * 128;
#pragma unroll 1
        for (;;) {
          nh++;
          if (elect()) { mbar_expect_tx(bars + B_HIN, 3584); bulk_g2s(base + OFF_K, hg - 8 * 3584, 3584, bars + B_HIN); }
          __syncwarp();
          mbar_wait(bars + B_HIN, nh & 1);
          if (__all_sync(0xffffffffu, lds64(la + (lane < 14 ? 16 : 0)).x == tag)) break;
          if (nh > 1000000) asm volatile("trap;");
        }
        if (lane < 14) { const uint4 v = lds128(la); sts128(la + 1792, v.x, v.y, v.z, v.w); }
      } else {
#pragma unroll
        for (int i = 0; i < 7; i++) sts128(base + OFF_K + i * 512 + lane * 16, 0, 0, 0, 0);
      }
      OBS(lane == 0, 12);
      smem_fence();
      __syncwarp();
      if (lane == 0) mbar_arrive(bars + B_HALO);
      __syncwarp();
      if (b < 112) {
        settle(probe(scr + (((b & 1) * 2 + (lane >> 4)) * HU_T + 60 + (b >> 4)) * BT + ((b >> 1) & 7) * 1792 + min(lane & 15, 13) * 128));
        publish(scr, C_WO);
      }
      mbar_wait(bars + (g1 ? B_GATE + 8 : B_ATT), 0);
      spin_ge(scr, C_WO, 112);
      if (lane == 0) mbar_arrive(bars + B_WO);
      mbar_wait(bars + B_ATT, 0);
      spin_ge(scr, C_O + (mt >> 1), 8);
      OBS(lane == 0, 17);
      if (lane == 0) mbar_arrive(bars + B_O);
      auto check = [&](int it, int end, const unsigned char* src, uint32_t bytes, uint32_t a0, uint32_t a1) {
        uint32_t ok = 0;
#pragma unroll 1
        for (const int it0 = it; it < end;) {
          const uint32_t fb = bars + (it & 7) * 8, a = base + (it & 7) * SLOT;
          if (!ok) mbar_wait(fb + B_OL, (it >> 3) & 1);
          auto pass = [&](bool next) {
            const uint32_t v0 = lds32(a + a0), v1 = lds32(a + a1), v2 = bytes == BT ? lds32(a + a0 + 512) : v0, v3 = bytes == BT ? lds32(a + a0 + 1024) : v1;
            if (next) ok = mbar_try(bars + B_OL + (it & 7) * 8, (it >> 3) & 1);
            uint32_t good;
            asm volatile("{\n.reg .pred p, q;\n.reg .b32 x, y;\nlop3.b32 x, %1, %2, %5, 0x7e;\nlop3.b32 y, %3, %4, %5, 0x7e;\nlop3.b32 x, x, y, 1, 0xa8;\nsetp.eq.u32 p, x, 0;\n"
                         "vote.sync.all.pred p, p, 0xffffffff;\nsetp.eq.and.u32 q, %6, 0, p;\n@q mbarrier.arrive.shared::cta.b64 _, [%7];\nselp.u32 %0, 1, 0, p;\n}"
                         : "=r"(good) : "r"(v0), "r"(v1), "r"(v2), "r"(v3), "r"(tag), "r"(lane), "r"(fb) : "memory");
            return good;
          };
          it++;
          if (__builtin_expect(!pass(true), 0)) {
            do {
              if (++nh > 1000000) asm volatile("trap;");
              if (elect()) { mbar_expect_tx(bars + B_HIN, bytes); bulk_g2s(a + (bytes & 2048) * 4, src + (it - 1 - it0) * bytes, bytes, bars + B_HIN); }
              __syncwarp();
              mbar_wait(bars + B_HIN, nh & 1);
            } while (!pass(false));
          }
        }
      };
      check(0, 7, scr + O_OFF + mt * 57344, 8192, lane * 132, lane * 132 + 4096);
      const uint32_t a = 8192 + (lane & 7) * 1792 + lane * 4;
      check(7, 21, scr + (dt * HU_T + 32) * BT, BT, a + (lane >> 3) * 128, a + (12 + ((lane >> 3) & 1)) * 128);
    }
  } else {
    asm volatile("setmaxnreg.inc.sync.aligned.u32 232;");
    const int wg = warp >> 2, w4 = warp & 3, th = wg ^ 1;
    const bool rel = (tid & 127) < 2;
    unsigned char* scr = p.scr;
    uint32_t X[28][4];
    float aq[28];
    const uint32_t dlo = (base >> 4) + (512u << 16) + (hp & 1), dlq = dlo + (OFF_WQ >> 4);
    {
      uint32_t xa[4];
#pragma unroll
      for (int k = 0; k < 4; k++) xa[k] = base + OFF_X + (th * 64 + w4 * 16 + (mi >> 1) * 8 + r8) * 128 + (((2 * k + (mi & 1)) ^ r8) << 4);
      float c0[2][4] = {}, c1[2][4] = {};
      uint32_t one[8];
#pragma unroll
      for (int j = 0; j < 8; j++) asm volatile("{\n.reg .u32 y;\nmov.u32 y, %%tid.y;\nmad.lo.u32 %0, y, %1, 0x3f803f80;\n}" : "=r"(one[j]) : "r"(lane + j));
      asm volatile("" : "+l"(scr));
      uint32_t ok = 0;
      const uint32_t bx = bars + B_X + wg * 64;
      {
#pragma unroll 1
        for (int n = 0; n < 64 && !ok; n++) { mma16816(c0[0], 0, 0, 0, 0, 0, 0); ok = mbar_try(bars + B_X, 0); }
        if (wg) ok = 0;
      }
#pragma unroll
      for (int i = 0; i < 8; i++) {
        if (i < 7) {
          if (!ok) mbar_wait(bx + i * 8, 0);
          OBS(tid == 64 && i == 0, 0); OBS(tid == 64 && i == 6, 15);
#pragma unroll
          for (int k = 0; k < 4; k++) ldsm4(X[i * 4 + k], xa[k] + i * 16384);
          if (i < 6) ok = mbar_try(bx + i * 8 + 8, 0);
        }
        if (i > 0) {
#pragma unroll
          for (int k = i * 4 - 4; k < i * 4; k++) {
            mma16816(c0[k & 1], X[k][0], one[(k & 1) * 4], X[k][1], one[(k & 1) * 4 + 1], X[k][0], X[k][1]);
            mma16816(c1[k & 1], X[k][2], one[(k & 1) * 4 + 2], X[k][3], one[(k & 1) * 4 + 3], X[k][2], X[k][3]);
          }
        }
      }
      float st[4];
#pragma unroll
      for (int j = 0; j < 2; j++) {
        st[j] = __shfl_sync(0xffffffffu, (g & 1) ? c0[0][2 * j + 1] + c0[1][2 * j + 1] : c0[0][2 * j] + c0[1][2 * j], (lane & 28) | (g >> 1));
        st[2 + j] = __shfl_sync(0xffffffffu, (g & 1) ? c1[0][2 * j + 1] + c1[1][2 * j + 1] : c1[0][2 * j] + c1[1][2 * j], (lane & 28) | (g >> 1));
      }
      named_arrive(8, 384);
      fence_code(20);
      named_arrive_if(wg, 0, 256);
      asm volatile("{\n.reg .pred q;\nsetp.ne.u32 q, %3, 0;\n@q st.shared.v2.f32 [%0], {%1,%2};\n@q bar.arrive 9, 160;\n}"
                   :: "r"(base + OFF_LN + ((t & 1) * 8 + g) * 8), "f"((t & 1) ? st[3] : st[1]), "f"((t & 1) ? st[2] : st[0]), "r"((uint32_t)((warp ^ 4) == hp)) : "memory");
      ok = mbar_try(bars + B_KV, 0);
      LnC l0, l1;
      float eps = 1e-5f;
#pragma unroll 1
      do {
        l0 = ln_consts(st[1], st[0], eps); l1 = ln_consts(st[3], st[2], eps);
#pragma unroll
        for (int k = 0; k < 16; k++) X[k >> 2][k & 3] = hsub2(X[k >> 2][k & 3], k & 2 ? l1.m : l0.m);
        eps += eps;
      } while ((l0.rl ^ l1.rl) == 4);
      OBS(tid == 32, 1);
      float ak[60], *av = ak + 32;
      auto norm = [&](int s) {
#pragma unroll
        for (int k = s * 4; k < s * 4 + 4; k++) {
          auto f = [&](uint32_t d, const LnC& l) { return s ? ln_apply(d, l) : hfma2(d, l.rh, hmul2(d, l.rl)); };
          const uint32_t y = f(X[k][1], l0);
          X[k][0] = f(X[k][0], l0); X[k][1] = f(X[k][2], l1); X[k][2] = y; X[k][3] = f(X[k][3], l1);
        }
      };
      const int pp_in = wg ? 6 : 0, pp_out = wg ? 0 : 6;
#pragma unroll
      for (int s = 0; s < 7; s++) {
        if (s != 1 || wg) norm(s);
        if (s == 0 && !wg) norm(1);
        if (__builtin_expect(!ok, 0)) { mbar_wait(bars + B_KV + s * 8, 0); if (s == 6) mbar_wait(bars + B_WQ, 0); }
        if (s == 0) fresh(ak);
        OBS(KOBS && (tid & 127) == 0, 40 + wg * 32 + s);
        if (wg ? s < 6 : s != 1) named_sync(pp_in, 256);
        OBS(KOBS && (tid & 127) == 32, 48 + wg * 32 + s);
        OBS(tid == 64 && s == 0, 2);
        wg_fence();
#pragma unroll
        for (int k = 0; k < 4; k++) {
          wgmma_rs_n120<1>(ak, X[s * 4 + k], mkdesc(HI_SW128, dlo + s * 1024 + k * 128), (s | k) != 0);
        }
        wg_commit();
        if (s == 6) {
          wg_wait<1>();
          if ((tid & 127) == 0) mbar_arrive(bars + B_EMPTY + 3 * 8);
          fresh(aq);
#pragma unroll
          for (int k = 0; k < 4; k++) {
            if (k == 2) named_arrive(pp_out, 256);
            wgmma_rs_n56<1>(aq, X[k], mkdesc(HI_SW128, dlq + k * 128), k);
          }
          wg_commit();
        }
        if (s < 6) named_arrive_if(wg ? s != 5 : s != 0, pp_out, 256);
        fence_code(s);
        OBS(KOBS && (tid & 127) == 64, 56 + wg * 32 + s);
        if (s < 6) ok = mbar_try(bars + B_KV + s * 8 + 8, 0);
        if (s == 5) ok &= mbar_try(bars + B_WQ, 0);
        OBS(tid == 64 && s == 5, 31);
        if (s > 0) wg_wait<1>();
        OBS(KOBS && (tid & 127) == 96, 64 + wg * 32 + s);
        if ((s == 2 || s == 3 || s == 5) && (tid & 127) == 0) mbar_arrive(bars + B_EMPTY + (s == 5 ? 2 : s - 2) * 8);
      }
      if ((tid & 127) == 0) mbar_arrive(bars + B_EMPTY + 4 * 8);
      OBS(tid == 32, 3);
      {
        const uint32_t kst = base + OFF_K + (2 + (warp ^ 4) * 2 + (mi & 1)) * 1792 + (mi >> 1) * 896 + r8 * 16;
#pragma unroll
        for (int n = 0; n < 7; n++)
          stsm4(kst + n * 128, pack2(ak[n * 4], ak[n * 4 + 1]), pack2(ak[n * 4 + 2], ak[n * 4 + 3]), pack2(av[n * 4], av[n * 4 + 1]), pack2(av[n * 4 + 2], av[n * 4 + 3]));
        named_arrive_if(warp == 3, 1, 96);
      }
      OBS(tid == 96, 32); OBS(tid == 224, 34);
      wg_wait<0>();
      if ((tid & 127) == 0) mbar_arrive(bars + B_EMPTY + 5 * 8);
      mbar_wait(bars + B_WQ2, 0);
    }
    const unsigned short *bp1 = (const unsigned short*)p.b1 + (g1 ? ft * 64 : 0) + w4 * 16 + g, *bp2 = (const unsigned short*)p.b2 + mt * 64 + w4 * 16 + g;
    const uint32_t braw[4] = {__ldg(bp1), __ldg(bp1 + 8), __ldg(bp2), __ldg(bp2 + 8)};
    auto q_rest = [&]() {
      wg_fence();
#pragma unroll
      for (int s = 1; s < 7; s++) {
#pragma unroll
        for (int k = s * 4; k < s * 4 + 4; k++) wgmma_rs_n56<1>(aq, X[k], mkdesc(HI_SW128, dlq + k * 128), 1);
        wg_commit();
        if (s == 5) { wg_wait<2>(); if ((tid & 127) == 0) mbar_arrive(bars + B_EMPTY + 6 * 8); }
      }
    };
    uint32_t Q[4][4];
    auto q_pack = [&]() {
#pragma unroll
      for (int n = 0; n < 14; n++) { const int m = n + 2 * (n > 7); Q[m >> 2][m & 3] = pack2(aq[n * 2], aq[n * 2 + 1]); }
#pragma unroll
      for (int h = 0; h < 2; h++) { Q[2][h] = t < 2 ? 0u : Q[1][2 + h]; Q[1][2 + h] = t < 2 ? Q[1][2 + h] : 0u; }
    };
    float acc[56];
    auto ai = [](int p) { return p < 4 ? 48 + (p & 1) * 4 + (p & 2) : (p - 4) * 4; };
    uint32_t xch, ts, tl;
    unsigned char *outp, *outq;
    auto setup_out = [&]() {
      xch = pin(base + OFF_K + (tid & 127) * 16);
      const uint32_t tb = base + OFF_K + 6144 + warp * 2560;
      ts = pin(tb + mi * 160 + r8 * 16); tl = pin(tb + t * 160 + g * 16);
      unsigned char* o = p.out + (mt * 64 + w4 * 16 + g) * 896 + dt * 224;
      outp = pin(o + th * 7168 + t * 16); outq = pin(o + (t >> 1) * 7168 + 192 + (t & 1) * 16);
    };
    auto give = [&](const float (&a)[56], int id) {
#pragma unroll
      for (int i = 0; i < 48; i += 16) sts128(xch + i * 128, pack2(a[i + 2], a[i + 3]), pack2(a[i + 6], a[i + 7]), pack2(a[i + 10], a[i + 11]), pack2(a[i + 14], a[i + 15]));
      named_arrive(id, 256);
    };
    auto take = [&](uint32_t (&r)[12], int id) {
      named_sync(id, 256);
#pragma unroll
      for (int i = 0; i < 3; i++) { const uint4 v = lds128(xch + i * 2048); r[i * 4] = v.x; r[i * 4 + 1] = v.y; r[i * 4 + 2] = v.z; r[i * 4 + 3] = v.w; }
    };
    float hv[32];
    auto keep_h = [&](int i) {
      const float hb0 = 0.5f * bf_lo(braw[i]), hb1 = 0.5f * bf_lo(braw[i + 1]);
#pragma unroll
      for (int j = 0; j < 32; j++) hv[j] = fmaf(acc[ai(j >> 1) + (j & 1)], 0.5f, j >= 4 && j < 8 ? hb1 : hb0);
    };
    auto take_h = [&](int i) {
      const float hb1 = 0.5f * bf_lo(braw[i + 1]);
      uint32_t r[12];
      take(r, 5);
#pragma unroll
      for (int j = 0; j < 12; j++) { hv[8 + 2 * j] = fmaf(bf_lo(r[j]), 0.5f, hb1); hv[9 + 2 * j] = fmaf(bf_hi(r[j]), 0.5f, hb1); }
    };
    uint4 Xr[4];
    auto get_x = [&]() {
      const uint32_t xr = base + OFF_Q + (w4 * 16 + g) * 224;
      mbar_wait(bars + B_RES, 0);
      Xr[0] = lds128(xr + (t >> 1) * 1792 + 192 + (t & 1) * 16);
#pragma unroll
      for (int i = 1; i < 4; i++) Xr[i] = lds128(xr + th * 1792 + t * 16 + (i - 1) * 64);
    };
    uint32_t Sv[16];
    auto gate = [&](int i) {
      uint32_t R[4];
#pragma unroll
      for (int q = 0; q < 4; q++) {
        const int j = i * 4 + q;
        const float h0 = hv[2 * j], h1 = hv[2 * j + 1];
        R[q] = hmul2(Sv[j], pack2(fmaf(h0, tanh_fast(h0), h0), fmaf(h1, tanh_fast(h1), h1)));
      }
      stsm4(ts + i * 640, R[0], R[1], R[2], R[3]);
    };
    auto leave = [&](int i) {
      __syncwarp();
      const uint4 v = lds128(tl + i * 640), x = Xr[i];
      stg128(i ? outp + (i - 1) * 64 : outq, hadd2(x.x, v.x), hadd2(x.y, v.y), hadd2(x.z, v.z), hadd2(x.w, v.w));
    };
    if (wg == 0) {
      named_sync(0, 256);
      OBS(tid == 96, 14);
      q_rest();
      named_arrive(6, 256);
      wg_wait<0>();
      if (tid == 0) mbar_arrive(bars + B_EMPTY + 7 * 8);
      q_pack();
      const uint32_t qst = base + OFF_Q + 8192 + (mi >> 1) * 1024 + (w4 * 16 + (mi & 1) * 8 + r8) * 16;
#pragma unroll
      for (int n = 0; n < 4; n++) stsm4(qst + n * 2048, Q[n][0], Q[n][1], Q[n][2], Q[n][3]);
      smem_fence();
      named_arrive(7, 256);
      OBS(tid == 32, 5);
      fresh(acc);
      if (g1) {
        unsigned char* ug = pin(scr + (d1 * HU_T + 32 + (ft >> 1)) * BT + ((ft & 1) * 4 + w4) * 1792 + lane * 4);
        unsigned char* ur = pin(ug + min(lane, 13) * 128);
        unsigned char* uc = pin(scr + d1 * 128);
        mbar_wait(bars, 0); mbar_wait(bars + 8, 0);
        const uint32_t utag = lds32(bars + B_TAG), um = pin(r8 == (ft & 1) * 4 + w4);
        {
          const uint32_t tg = lds64(bars + B_T0).x;
          while (tg - gtime() - 1 < 1000u);
        }
        named_sync(0, 256);
        gemm_issue<1>(acc, base >> 4, 0);
        OBS(tid == 0, 20);
        gemm_loop<1>(acc, base, 1, 32, rel, 40, 1, tid == 32 ? J1 : tid == 64 ? J2 : -1, bars + B_GATE - 8 + w4 * 8);
        wg_wait<0>();
        OBS(tid == 0, 21);
        named_arrive(5, 256);
        mbar_arrive_if(rel, bars + B_EMPTY + 7 * 8);
        auto gelu = [&](int n, int h) {
          const float hb = 0.5f * bf_lo(braw[h]);
          const float h0 = fmaf(acc[4 * n + 2 * h], 0.5f, hb), h1 = fmaf(acc[4 * n + 2 * h + 1], 0.5f, hb);
          const float t0 = tanh_fast(h0 * fmaf(h0 * h0, 0.2854192648f, 1.5957691216f)), t1 = tanh_fast(h1 * fmaf(h1 * h1, 0.2854192648f, 1.5957691216f));
          const uint32_t v = pack2(fmaf(h0, t0, h0), fmaf(h1, t1, h1));
          return h ? v : (v & ~um) | (utag & um);
        };
        auto done = [&](int h) {
          if (w4) named_arrive(13 + h, 128);
          else { named_sync(13 + h, 128); publish(uc, C_U + h * 4); OBS(tid == 0, h ? 13 : 9); }
          fence_code(10 + h);
        };
#pragma unroll
        for (int n = 0; n < 14; n++) { stg32(ug + n * 128, gelu(n, 0)); if (n == 6) fence_code(8); }
        done(0);
#pragma unroll
        for (int n = 0; n < 14; n++) { stg32(ug + 14 * BT + n * 128, gelu(n, 1)); if (n == 9) named_arrive(12, 256); if (n == 6 || n == 9) fence_code(60 + n); }
        settle(probe(ur + 14 * BT));
        done(1);
      } else if (tid == 32 || tid == 64) mbar_arrive(bars + B_GATE - 8 + w4 * 8);
      setup_out();
      get_x();
      uint32_t r[12];
      take(r, 3);
#pragma unroll
      for (int j = 0; j < 16; j++) Sv[j] = r[j < 4 ? 0 : j - 4];
      asm volatile("" :: "r"(r[0]), "r"(r[11]) : "memory");
      named_arrive(10, 256);
      take_h(2);
    } else {
      const uint32_t dq = ((base + OFF_Q) >> 4) + (64u << 16), dk = (base + OFF_K) >> 4;
      const bool odd = g & 1, early = 2 * t + (g & 1) > g;
      uint32_t selA[5], selB[4];
#pragma unroll
      for (int j = 0; j < 5; j++) { selA[j] = j == w4 + (early ? 0 : 1) ? (odd ? 0x1044u : 0x4410u) : 0x4444u; }
#pragma unroll
      for (int j = 0; j < 4; j++) { selB[j] = j == w4 ? (odd ? 0x3244u : 0x4432u) : 0x4444u; }
      float Sc[2][40], Op[2][2][16];
      uint32_t A[2][5][4];
      auto scores = [&](int T) {
        fresh(Sc[0]); fresh(Sc[1]);
#pragma unroll
        for (int k = 0; k < 2; k++) {
#pragma unroll
          for (int hh = 0; hh < 2; hh++)
            if (T) wgmma_n80<0, 0>(Sc[hh], mkdesc(8, dq + 512 + hh * 256 + k * 128), mkdesc(112, dk + (8u << 16) + 896 + hh * 24 + k * 16), k);
            else wgmma_rs_n80<0>(Sc[hh], Q[hh * 2 + k], mkdesc(112, dk + (8u << 16) + hh * 24 + k * 16), k);
        }
      };
      auto softmax = [&](int T) {
        uint32_t L[2][2];
        auto pick = [&](int w) {
#pragma unroll
          for (int hh = 0; hh < 2; hh++) {
            const float* q = Sc[hh] + w * 8;
            auto at = [&](int i) { return odd ? q[i + 1] : q[i]; };
            L[hh][0] = pack2(early ? at(0) : at(8), early ? at(6) : at(14)); L[hh][1] = pack2(at(4), at(10));
          }
          asm volatile("" ::: "memory");
        };
        if (w4 & 2) { if (w4 & 1) pick(3); else pick(2); } else { if (w4 & 1) pick(1); else pick(0); }
#pragma unroll
        for (int hh = 0; hh < 2; hh++) {
          uint32_t a = hfma2(L[hh][0], SC_HI, hmul2(L[hh][0], SC_LO)), c = hfma2(L[hh][1], SC_HI, hmul2(L[hh][1], SC_LO));
          if (T == 0 && w4 == 0 && rb == 0) { if (early) a = 0xce6ece6eu; c = (c & 0xffff0000u) | 0xce6eu; }
          uint32_t mx = hmax2(a, c);
          mx = hmax2(mx, __shfl_xor_sync(0xffffffffu, mx, 1));
          mx = hmax2(mx, __shfl_xor_sync(0xffffffffu, mx, 2));
          uint32_t pp[2];
#pragma unroll
          for (int h = 0; h < 2; h++) {
            const float m = h ? bf_hi(mx) : bf_lo(mx);
            const float p0 = ex2_fast(((h ? bf_hi(a) : bf_lo(a)) - m) * LOG2E), p1 = ex2_fast(((h ? bf_hi(c) : bf_lo(c)) - m) * LOG2E);
            float sm = p0 + p1;
            sm += __shfl_xor_sync(0xffffffffu, sm, 1);
            sm += __shfl_xor_sync(0xffffffffu, sm, 2);
            const float inv = rcp_fast(sm);
            pp[h] = pack2(p0 * inv, p1 * inv);
          }
#pragma unroll
          for (int j = 0; j < 5; j++) {
            A[hh][j][0] = place(pp[0], selA[j]); A[hh][j][1] = j ? place(pp[1], selB[j ? j - 1 : 0]) : 0u;
            A[hh][j][2] = j < 4 ? place(pp[0], selB[j & 3]) : 0u; A[hh][j][3] = place(pp[1], selA[j]);
          }
        }
      };
      auto values = [&](int T) {
        fresh(Op[T][0]); fresh(Op[T][1]);
#pragma unroll
        for (int j = 0; j < 5; j++)
#pragma unroll
          for (int hh = 0; hh < 2; hh++) {
            wgmma_rs_n32<1>(Op[T][hh], A[hh][j], mkdesc(8, dk + (112u << 16) + 56 + T * 896 + hh * 24 + j * 224), j);
          }
        wg_commit();
      };
      uint32_t Ob[2][14];
      auto pack = [&](int T) {
        const float (&O)[2][16] = Op[T];
#pragma unroll
        for (int n = 0; n < 7; n++)
#pragma unroll
          for (int h = 0; h < 2; h++) {
            if (n < 3) Ob[T][n * 2 + h] = pack2(O[0][n * 4 + 2 * h], O[0][n * 4 + 2 * h + 1]);
            else if (n == 3) Ob[T][n * 2 + h] = pack2(t < 2 ? O[0][12 + 2 * h] : O[1][2 * h], t < 2 ? O[0][13 + 2 * h] : O[1][2 * h + 1]);
            else Ob[T][n * 2 + h] = pack2(O[1][(n - 3) * 4 + 2 * h], O[1][(n - 3) * 4 + 2 * h + 1]);
          }
      };
      smem_fence();
      named_sync(6, 256);
      OBS(tid == 224, 26);
      q_rest();
      named_sync(7, 256);
      wg_fence();
      scores(1);
      wg_commit();
      named_arrive_if(g1, 0, 256);
      wg_wait<2>();
      if (tid == 128) mbar_arrive(bars + B_EMPTY + 7 * 8);
      wg_wait<0>();
      OBS(tid == 160, 10);
      softmax(1);
      q_pack();
      OBS(tid == 160, 30);
      mbar_wait(bars + B_HALO, 0);
      OBS(tid == 160, 7);
      mbar_wait(bars + B_GATE, 0);
      wg_fence();
      scores(0);
      values(1);
      wg_wait<0>();
      OBS(tid == 160, 33);
      unsigned char* og = scr + O_OFF + rb * 2 * 57344 + hp * 7168 + w4 * 256 + lane * 4;
      const uint32_t tag = lds32(bars + B_TAG), m0 = r8 == 2 * w4, m1 = r8 == 2 * w4 + 1;
      auto put = [&](int T) {
#pragma unroll
        for (int n = 0; n < 7; n++) {
          stg32(og + T * 57344 + n * 1024, (Ob[T][2 * n] & ~m0) | (tag & m0)); stg32(og + T * 57344 + n * 1024 + 128, (Ob[T][2 * n + 1] & ~m1) | (tag & m1));
          __nanosleep(20);
        }
      };
      pack(1); put(1);
      softmax(0);
      mbar_wait(bars + B_GATE + 8, 0);
      wg_fence();
      values(0);
      wg_wait<0>();
      OBS(tid == 160, 35);
      named_sync(11, 128);
      if (tid == 160) mbar_arrive(bars + B_ATT);
      pack(0); put(0);
      OBS(tid == 160, 28);
      named_sync(11, 128);
      if (warp == 4) publish(scr, C_O + rb);
      OBS(tid == 160, 8);
      setup_out();
      float as[56];
      if (g1) named_sync(5, 256);
      get_x();
      mbar_wait(bars, 0);
      if (g1) named_sync(12, 256);
      fresh(as);
      gemm_issue<0>(as, base >> 4, 0);
      OBS(tid == 128, 22);
      gemm_loop<0>(as, base, 1, 7, rel, 104);
      fresh(acc);
      mbar_wait(bars + 56, 0);
      gemm_issue<1>(acc, (base + 7 * SLOT) >> 4, 0);
      OBS(tid == 128, 24);
      wg_wait<1>();
      mbar_arrive_if(rel, bars + B_EMPTY + 6 * 8);
      give(as, 3);
#pragma unroll
      for (int j = 0; j < 16; j++) Sv[j] = pack2(as[ai(j)], as[ai(j) + 1]);
      gemm_loop<1>(acc, base, 8, 35, rel, 65);
      named_sync(10, 256);
      wg_wait<0>();
      OBS(tid == 128, 25);
      give(acc, 5);
      fence_code(31);
      keep_h(2);
      gate(0); leave(0);
    }
    {
#pragma unroll
      for (int i = 1; i < 4; i++) { gate(i); leave(i); }
      OBS(tid == 128, 27);
    }
  }
}

typedef CUresult (*EncFn)(CUtensorMap*, CUtensorMapDataType, cuuint32_t, void*, const cuuint64_t*, const cuuint64_t*, const cuuint32_t*,
                          const cuuint32_t*, CUtensorMapInterleave, CUtensorMapSwizzle, CUtensorMapL2promotion, CUtensorMapFloatOOBfill);
void enc(EncFn f, CUtensorMap* m, const void* ptr, cuuint64_t d0, cuuint64_t d1, cuuint64_t d2, cuuint64_t s1, cuuint64_t s2, cuuint32_t b1, cuuint32_t b2, cuuint32_t b0 = 64) {
  const cuuint64_t gd[3] = {d0, d1, d2}, gs[2] = {s1 * 2, s2 * 2};
  const cuuint32_t bx[3] = {b0, b1, b2}, es[3] = {1, 1, 1};
  f(m, CU_TENSOR_MAP_DATA_TYPE_BFLOAT16, 3, (void*)ptr, gd, gs, bx, es, CU_TENSOR_MAP_INTERLEAVE_NONE, b0 == 64 ? CU_TENSOR_MAP_SWIZZLE_128B : CU_TENSOR_MAP_SWIZZLE_NONE,
    CU_TENSOR_MAP_L2_PROMOTION_L2_128B, CU_TENSOR_MAP_FLOAT_OOB_FILL_NONE);
}
}

extern "C" void kernel_launch(void* const* d_in, const int* in_sizes, int n_in, void* d_out, int out_size) {
  (void)in_sizes; (void)n_in; (void)out_size;
  void* fp = nullptr;
  cudaDriverEntryPointQueryResult qr;
  cudaGetDriverEntryPoint("cuTensorMapEncodeTiled", &fp, cudaEnableDefault, &qr);
  EncFn f = (EncFn)fp;
  CUtensorMap m_x, m_wkv, m_wq, m_w1, m_w2, m_res;
  void* scr = nullptr;
  cudaGetSymbolAddress(&scr, g_scr);
  enc(f, &m_x, d_in[0], D_, S_, 1, D_, D_, 64, 1);
  enc(f, &m_wkv, d_in[1], D_, D_, 3, 3 * D_, D_, 64, 2);
  enc(f, &m_wq, d_in[1], D_, D_, 3, 3 * D_, D_, 64, 1);
  enc(f, &m_w1, d_in[4], F_, S_, 1, F_, F_, 64, 1);
  enc(f, &m_w2, d_in[6], S_, 16, F_ / 16, S_, 16 * S_, 8, 8);
  enc(f, &m_res, d_in[0], D_, S_, 1, D_, D_, 64, 1, 112);
  Params p;
  p.wqkv = (const unsigned char*)d_in[1]; p.wo = (const unsigned char*)d_in[2];
  p.w1 = (const unsigned char*)d_in[4]; p.b1 = (const unsigned char*)d_in[5];
  p.w2 = (const unsigned char*)d_in[6]; p.b2 = (const unsigned char*)d_in[7];
  p.out = (unsigned char*)d_out; p.scr = (unsigned char*)scr;
  cudaFuncSetAttribute(fused_kernel, cudaFuncAttributeMaxDynamicSharedMemorySize, SMEM_BYTES);
  fused_kernel<<<128, NTHREADS, SMEM_BYTES, cudaStreamPerThread>>>(m_x, m_wkv, m_wq, m_w1, m_w2, m_res, p);
}
```
